```python
import torch

def _softmax(x, axis=-1):
    return torch.softmax(x, dim=axis)

def _gelu(x):
    return torch.nn.functional.gelu(x, approximate='tanh')

def _silu(x):
    return torch.nn.functional.silu(x)

def _sigmoid(x):
    return torch.sigmoid(x)

def _layernorm(x, axis=-1, eps=1e-05):
    m = x.mean(dim=axis, keepdim=True)
    v = x.var(dim=axis, keepdim=True, unbiased=False)
    return (x - m) / torch.sqrt(v + eps)

def _scatter_add(tgt, idx, src, axis=0):
    return tgt.clone().index_add_(axis, idx, src)

def _segment_sum(src, seg, n):
    out = torch.zeros((n,) + src.shape[1:], dtype=src.dtype)
    return out.index_add_(0, seg, src)

def _pad(x, pw):
    flat = tuple((v for pair in reversed(pw) for v in pair))
    return torch.nn.functional.pad(x, flat)
kernel_name = 'interleave_layers__memory_aug_recurrent_mem_tr__linear_kernel_hedgehog__prompt'

def setup_inputs():

    _w = lambda a: (lambda t: t.to(torch.bfloat16) if t.is_floating_point() else t)(torch.as_tensor(a))

    def _A_setup():
        B, S, Dm = (1, 2048, 640)
        H, Dh = (32, 192)
        M, seg = (8, 32)
        seg = min(seg, S)
        S = S // seg * seg
        return {'x': _w((lambda *s: torch.randn(*s, dtype=torch.bfloat16) * 0.05)(B, S, Dm)), 'mem0': _w((lambda *s: torch.randn(*s, dtype=torch.bfloat16) * 0.8)(B, M, Dm)), 'Wq': _w((lambda *s: torch.randn(*s, dtype=torch.bfloat16) * 1.6)(Dm, H, Dh) * Dm ** (-0.5)), 'Wk': _w((lambda *s: torch.randn(*s, dtype=torch.bfloat16) * 1.6)(Dm, H, Dh) * Dm ** (-0.5)), 'Wv': _w((lambda *s: torch.randn(*s, dtype=torch.bfloat16) * 0.8)(Dm, H, Dh) * Dm ** (-0.5)), 'Wo': _w((lambda *s: torch.randn(*s, dtype=torch.bfloat16) * 0.8)(H, Dh, Dm) * (H * Dh) ** (-0.5)), 'seg_len': seg}
    _A_in = _A_setup()

    def _B_setup():
        B, S, D, H = (1, 2048, 640, 32)
        Dh = D // H
        return {'x': _w((lambda *s: torch.randn(*s, dtype=torch.bfloat16) * 0.05)(B, S, D)), 'wqkv': _w((lambda *s: torch.randn(*s, dtype=torch.bfloat16) * 0.4)(D, 3 * D)), 'w_phi': _w((lambda *s: torch.randn(*s, dtype=torch.bfloat16) * 0.4)(H, Dh, Dh) * Dh ** (-0.5)), 'wo': _w((lambda *s: torch.randn(*s, dtype=torch.bfloat16) * 0.05)(D, D))}
    _B_in = _B_setup()
    return {'A_x': _A_in['x'], 'A_mem0': _A_in['mem0'], 'A_Wq': _A_in['Wq'], 'A_Wk': _A_in['Wk'], 'A_Wv': _A_in['Wv'], 'A_Wo': _A_in['Wo'], 'A_seg_len': _A_in['seg_len'], 'B_x': _B_in['x'], 'B_wqkv': _B_in['wqkv'], 'B_w_phi': _B_in['w_phi'], 'B_wo': _B_in['wo']}

def reference(A_x, A_mem0, A_Wq, A_Wk, A_Wv, A_Wo, A_seg_len, B_x, B_wqkv, B_w_phi, B_wo):

    def _A_ref(x, mem0, Wq, Wk, Wv, Wo, seg_len):
        B, S, Dm = x.shape
        H, Dh = (Wq.shape[1], Wq.shape[2])
        M = mem0.shape[1]
        scale = Dh ** (-0.5)
        n_seg = S // seg_len
        L = M + seg_len
        idx = torch.arange(L)
        mask = (idx[:, None] < M) | (idx[:, None] >= idx[None, :])
        mem = mem0
        outs = []
        for s in range(n_seg):
            xs = x[:, s * seg_len:(s + 1) * seg_len, :].clone()
            h = torch.concatenate([mem, xs], axis=1)
            q = torch.einsum('btd,dhe->bhte', h, Wq)
            k = torch.einsum('btd,dhe->bhte', h, Wk)
            v = torch.einsum('btd,dhe->bhte', h, Wv)
            scores = torch.einsum('bhqe,bhke->bhqk', q, k) * scale
            scores = torch.where(mask[None, None], scores, -1000000000.0)
            p = _softmax(scores, axis=-1)
            o = torch.einsum('bhqk,bhke->bhqe', p, v)
            o = torch.einsum('bhte,hed->btd', o, Wo)
            mem = o[:, :M, :].clone()
            outs.append(o[:, M:, :])
        return torch.concatenate(outs, axis=1)

    def _B_ref(x, wqkv, w_phi, wo):
        B, S, D = x.shape
        H = 32
        Dh = D // H
        qkv = (lambda x, *d: x.permute(*d))((x @ wqkv).reshape(B, S, 3, H, Dh), 2, 0, 3, 1, 4)
        q, k, v = (qkv[0], qkv[1], qkv[2])
        pq = torch.einsum('bhsd,hdf->bhsf', q, w_phi)
        pk = torch.einsum('bhsd,hdf->bhsf', k, w_phi)
        phi_q = torch.concatenate([_softmax(pq, axis=-1), _softmax(-pq, axis=-1)], axis=-1)
        phi_k = torch.concatenate([_softmax(pk, axis=-1), _softmax(-pk, axis=-1)], axis=-1)
        kv = torch.einsum('bhsf,bhsd->bhfd', phi_k, v)
        z = torch.einsum('bhsf->bhf', phi_k)
        num = torch.einsum('bhqf,bhfd->bhqd', phi_q, kv)
        den = torch.einsum('bhqf,bhf->bhq', phi_q, z)[..., None] + 1e-06
        o = num / den
        return (lambda x, *d: x.permute(*d))(o, 0, 2, 1, 3).reshape(B, S, D) @ wo
    x = A_x
    x = x + _A_ref(_layernorm(x, axis=-1), A_mem0, A_Wq, A_Wk, A_Wv, A_Wo, A_seg_len)
    x = x + _B_ref(_layernorm(x, axis=-1), B_wqkv, B_w_phi, B_wo)
    x = x + _A_ref(_layernorm(x, axis=-1), A_mem0, A_Wq, A_Wk, A_Wv, A_Wo, A_seg_len)
    x = x + _B_ref(_layernorm(x, axis=-1), B_wqkv, B_w_phi, B_wo)
    return x
```

```cpp
#include <cuda_runtime.h>
#include <cuda_bf16.h>
#include <cuda_fp16.h>
#include <cuda.h>
#include <stdint.h>

typedef __nv_bfloat16 bf16;

constexpr int S_LEN = 2048, DM = 640, NH = 32, DH = 192, NMEM = 8, SEG = 32, NSEG = 64;
constexpr int HD = NH * DH;
constexpr int NKEY = NMEM + SEG;
constexpr int SLAB = 64 * NKEY * 2;
constexpr int AR_STEP_BYTES = 24 * 1024;
constexpr int BDH = 20, BF = 40;

__device__ __align__(1024) bf16 g_xn[S_LEN * DM];
__device__ __align__(1024) bf16 g_kv[(size_t)NSEG * NH * 2 * DH * NKEY];
__device__ __align__(1024) bf16 g_o[(size_t)S_LEN * HD];
__device__ __align__(1024) bf16 g_xa[S_LEN * DM];
__device__ __align__(1024) bf16 g_xb[S_LEN * DM];
__device__ __align__(32768) uint32_t g_ar[NSEG * AR_STEP_BYTES / 4];
#define RTS 10
constexpr int RT_SPLIT = RTS;
constexpr int ACC_ROWS = (16 - RT_SPLIT) * 128;
#define BSL 1
#define FROWS 16
__device__ __align__(1024) float g_acc[BSL ? 256 : 2 * ACC_ROWS * DM];
#define CTAIL 1
constexpr int NSL = 48;
__device__ __align__(1024) bf16 g_sl[BSL ? NSL * 128 * DM : 512];
__device__ __align__(1024) float g_cs[10 * 3 * DM];
__device__ __align__(1024) bf16 g_wb1[3 * DM * DM];
__device__ __align__(1024) uint4 g_wb2[DM * DM / 8];
__device__ __align__(1024) bf16 g_bo[S_LEN * DM];
__device__ __align__(1024) uint4 g_qf[16 * NH * 12 * 256];
struct __align__(1024) Sync {
  uint32_t kv[NSEG * NH];
  uint32_t o[16 * 16];
  uint32_t bkv_cnt[8], bo_cnt[16];
  uint32_t pro[4];
  uint32_t wmax[96];
  uint32_t pad1[4];
  uint32_t head, pad0[31];
  uint32_t zeroed, pad[31];
  uint32_t gst[16 * NH];
  uint32_t wcnt[16 * 8];
  float2 rstat[S_LEN];
};
__device__ __align__(1024) Sync g_sync[2];
__device__ uint32_t g_kw;
__device__ __align__(1024) float g_bkv[NH * BF * 24];

#define GT(k, e)
#define WS(e_, v_)
#undef TLOG
#undef TM
#undef PT
#undef XT
#define XT(i, e)
#define TLOG(id, ta)
#define TM(i)
#define PT(k, e)
#define DEVI __device__ __forceinline__
constexpr int SPIN_LIMIT = 20000;
DEVI uint32_t smem_u32(const void* p) { return (uint32_t)__cvta_generic_to_shared(p); }
DEVI uint32_t clk32() { uint64_t c; asm volatile("mov.u64 %0, %%clock64;" : "=l"(c)); return (uint32_t)c; }
DEVI uint32_t mapa(uint32_t a, uint32_t r) { uint32_t o; asm("mapa.shared::cluster.u32 %0, %1, %2;" : "=r"(o) : "r"(a), "r"(r)); return o; }
DEVI void mbar_init(uint32_t bar, uint32_t cnt) { asm volatile("mbarrier.init.shared::cta.b64 [%0], %1;" :: "r"(bar), "r"(cnt) : "memory"); }
DEVI void mbar_expect(uint32_t bar, uint32_t bytes) { asm volatile("mbarrier.arrive.expect_tx.shared::cta.b64 _, [%0], %1;" :: "r"(bar), "r"(bytes) : "memory"); }
DEVI void mbar_arrive(uint32_t bar) { asm volatile("mbarrier.arrive.shared::cta.b64 _, [%0];" :: "r"(bar) : "memory"); }
DEVI void mbar_arrive_cluster(uint32_t rbar) { asm volatile("mbarrier.arrive.relaxed.cluster.shared::cluster.b64 _, [%0];" :: "r"(rbar) : "memory"); }
DEVI bool mbar_try(uint32_t bar, uint32_t par) {
  uint32_t ok;
  asm volatile("{.reg .pred p; mbarrier.try_wait.parity.shared::cta.b64 p, [%1], %2; selp.u32 %0, 1, 0, p;}" : "=r"(ok) : "r"(bar), "r"(par) : "memory");
  return ok;
}
DEVI void mbar_wait(uint32_t bar, uint32_t par) {
  int n = 0;
  while (!mbar_try(bar, par) && ++n < SPIN_LIMIT) {}
}
DEVI void bar_sync(int id, int n) { asm volatile("bar.sync %0, %1;" :: "r"(id), "r"(n) : "memory"); }
DEVI void bar_arrive(int id, int n) { asm volatile("bar.arrive %0, %1;" :: "r"(id), "r"(n) : "memory"); }
DEVI void fence_async() { asm volatile("fence.proxy.async.shared::cta;" ::: "memory"); }
#define RFEN 2
#define CEND 1
#define XFEN 1
#define WFEN 2
template <int M> DEVI void publish_bulk(uint32_t* flag) {
  if (M == 1) asm volatile("fence.proxy.async;" ::: "memory");
  if (M == 2) asm volatile("red.release.gpu.global.add.u32 [%0], 1;" :: "l"(flag) : "memory");
  else asm volatile("red.relaxed.gpu.global.add.u32 [%0], 1;" :: "l"(flag) : "memory");
}
DEVI void fence_flag_to_bulk() {
  if (RFEN == 0) asm volatile("fence.proxy.async;" ::: "memory");
  if (RFEN == 1) asm volatile("fence.proxy.async.global;" ::: "memory");
}
DEVI void cluster_sync_full() { asm volatile("barrier.cluster.arrive.release.aligned; barrier.cluster.wait.acquire.aligned;" ::: "memory"); }
DEVI void tma2d(uint32_t dst, const CUtensorMap* m, int c0, int c1, uint32_t bar) {
  asm volatile("cp.async.bulk.tensor.2d.shared::cluster.global.mbarrier::complete_tx::bytes [%0], [%1, {%3, %4}], [%2];"
               :: "r"(dst), "l"(m), "r"(bar), "r"(c0), "r"(c1) : "memory");
}
DEVI void tma3d(uint32_t dst, const CUtensorMap* m, int c0, int c1, int c2, uint32_t bar) {
  asm volatile("cp.async.bulk.tensor.3d.shared::cluster.global.mbarrier::complete_tx::bytes [%0], [%1, {%3, %4, %5}], [%2];"
               :: "r"(dst), "l"(m), "r"(bar), "r"(c0), "r"(c1), "r"(c2) : "memory");
}
DEVI void tma3d_mc(uint32_t dst, const CUtensorMap* m, int c0, int c1, int c2, uint32_t bar, uint16_t mask) {
  asm volatile("cp.async.bulk.tensor.3d.shared::cluster.global.mbarrier::complete_tx::bytes.multicast::cluster [%0], [%1, {%3, %4, %5}], [%2], %6;"
               :: "r"(dst), "l"(m), "r"(bar), "r"(c0), "r"(c1), "r"(c2), "h"(mask) : "memory");
}
DEVI void tma3d_prefetch(const CUtensorMap* m, int c0, int c1, int c2) {
  asm volatile("cp.async.bulk.prefetch.tensor.3d.L2.global [%0, {%1, %2, %3}];" :: "l"(m), "r"(c0), "r"(c1), "r"(c2) : "memory");
}
DEVI void tma2d_prefetch(const CUtensorMap* m, int c0, int c1) {
  asm volatile("cp.async.bulk.prefetch.tensor.2d.L2.global [%0, {%1, %2}];" :: "l"(m), "r"(c0), "r"(c1) : "memory");
}
#define EVF 7
DEVI uint64_t stream_policy() { uint64_t p; asm("createpolicy.fractional.L2::evict_first.b64 %0, 1.0;" : "=l"(p)); return p; }
DEVI void bulk_store(void* g, uint32_t s, uint32_t bytes) {
  if (EVF & 1) asm volatile("cp.async.bulk.global.shared::cta.bulk_group.L2::cache_hint [%0], [%1], %2, %3;" :: "l"(g), "r"(s), "r"(bytes), "l"(stream_policy()) : "memory");
  else asm volatile("cp.async.bulk.global.shared::cta.bulk_group [%0], [%1], %2;" :: "l"(g), "r"(s), "r"(bytes) : "memory");
}
DEVI void ldsm4(uint32_t (&r)[4], uint32_t a) {
  asm volatile("ldmatrix.sync.aligned.m8n8.x4.shared.b16 {%0,%1,%2,%3}, [%4];" : "=r"(r[0]), "=r"(r[1]), "=r"(r[2]), "=r"(r[3]) : "r"(a) : "memory");
}
DEVI void ldsm4t(uint32_t (&r)[4], uint32_t a) {
  asm volatile("ldmatrix.sync.aligned.m8n8.x4.trans.shared.b16 {%0,%1,%2,%3}, [%4];" : "=r"(r[0]), "=r"(r[1]), "=r"(r[2]), "=r"(r[3]) : "r"(a) : "memory");
}
DEVI void ldsm4t_p(uint32_t* r, uint32_t a) {
  asm volatile("ldmatrix.sync.aligned.m8n8.x4.trans.shared.b16 {%0,%1,%2,%3}, [%4];" : "=r"(r[0]), "=r"(r[1]), "=r"(r[2]), "=r"(r[3]) : "r"(a) : "memory");
}
DEVI void ldsm2(uint32_t (&r)[2], uint32_t a) {
  asm volatile("ldmatrix.sync.aligned.m8n8.x2.shared.b16 {%0,%1}, [%2];" : "=r"(r[0]), "=r"(r[1]) : "r"(a) : "memory");
}
DEVI void stsm4(uint32_t a, uint32_t r0, uint32_t r1, uint32_t r2, uint32_t r3) {
  asm volatile("stmatrix.sync.aligned.m8n8.x4.shared.b16 [%0], {%1,%2,%3,%4};" :: "r"(a), "r"(r0), "r"(r1), "r"(r2), "r"(r3) : "memory");
}
DEVI void mma16816(float (&d)[4], const uint32_t* a, uint32_t b0, uint32_t b1) {
  asm volatile("mma.sync.aligned.m16n8k16.row.col.f32.bf16.bf16.f32 {%0,%1,%2,%3}, {%4,%5,%6,%7}, {%8,%9}, {%0,%1,%2,%3};"
               : "+f"(d[0]), "+f"(d[1]), "+f"(d[2]), "+f"(d[3]) : "r"(a[0]), "r"(a[1]), "r"(a[2]), "r"(a[3]), "r"(b0), "r"(b1));
}
DEVI void mma1688(float (&d)[4], uint32_t a0, uint32_t a1, uint32_t b0) {
  asm volatile("mma.sync.aligned.m16n8k8.row.col.f32.bf16.bf16.f32 {%0,%1,%2,%3}, {%4,%5}, {%6}, {%0,%1,%2,%3};"
               : "+f"(d[0]), "+f"(d[1]), "+f"(d[2]), "+f"(d[3]) : "r"(a0), "r"(a1), "r"(b0));
}
DEVI uint32_t pack_bf16(float lo, float hi) { uint32_t r; asm("cvt.rn.bf16x2.f32 %0, %1, %2;" : "=r"(r) : "f"(hi), "f"(lo)); return r; }
DEVI uint32_t pack_f16(float lo, float hi) { uint32_t r; asm("cvt.rn.f16x2.f32 %0, %1, %2;" : "=r"(r) : "f"(hi), "f"(lo)); return r; }
DEVI uint32_t f16x2_to_bf16x2(uint32_t h) { float2 f = __half22float2(*reinterpret_cast<__half2*>(&h)); return pack_bf16(f.x, f.y); }
DEVI void sts32(uint32_t a, uint32_t v) { asm volatile("st.shared.u32 [%0], %1;" :: "r"(a), "r"(v) : "memory"); }
DEVI void sts64(uint32_t a, uint32_t v0, uint32_t v1) { asm volatile("st.shared.v2.u32 [%0], {%1,%2};" :: "r"(a), "r"(v0), "r"(v1) : "memory"); }
DEVI void sts128(uint32_t a, uint32_t v0, uint32_t v1, uint32_t v2, uint32_t v3) { asm volatile("st.shared.v4.u32 [%0], {%1,%2,%3,%4};" :: "r"(a), "r"(v0), "r"(v1), "r"(v2), "r"(v3) : "memory"); }
DEVI uint32_t lds32(uint32_t a) { uint32_t v; asm volatile("ld.shared.u32 %0, [%1];" : "=r"(v) : "r"(a) : "memory"); return v; }
DEVI float2 lds64f(uint32_t a) { float2 v; asm volatile("ld.shared.v2.f32 {%0,%1}, [%2];" : "=f"(v.x), "=f"(v.y) : "r"(a) : "memory"); return v; }
DEVI void lds128(uint32_t (&r)[4], uint32_t a) { asm volatile("ld.shared.v4.u32 {%0,%1,%2,%3}, [%4];" : "=r"(r[0]), "=r"(r[1]), "=r"(r[2]), "=r"(r[3]) : "r"(a) : "memory"); }
DEVI void st_async64(uint32_t a, float x, float y, uint32_t bar) {
  asm volatile("st.async.weak.shared::cluster.mbarrier::complete_tx::bytes.v2.f32 [%0], {%1,%2}, [%3];" :: "r"(a), "f"(x), "f"(y), "r"(bar) : "memory");
}
DEVI void st_async32(uint32_t a, uint32_t x, uint32_t bar) {
  asm volatile("st.async.weak.shared::cluster.mbarrier::complete_tx::bytes.b32 [%0], %1, [%2];" :: "r"(a), "r"(x), "r"(bar) : "memory");
}
DEVI void ld_relaxed128(uint32_t (&r)[4], const void* p) {
  asm volatile("ld.relaxed.gpu.global.v4.u32 {%0,%1,%2,%3}, [%4];" : "=r"(r[0]), "=r"(r[1]), "=r"(r[2]), "=r"(r[3]) : "l"(p) : "memory");
}
DEVI void red_f16x2(void* p, uint32_t v) { asm volatile("red.relaxed.gpu.global.add.noftz.f16x2 [%0], %1;" :: "l"(p), "r"(v) : "memory"); }
DEVI void red_f16x2_v4(void* p, uint32_t a, uint32_t b, uint32_t c, uint32_t d) {
  asm volatile("red.relaxed.gpu.global.add.noftz.v4.f16x2 [%0], {%1,%2,%3,%4};" :: "l"(p), "r"(a), "r"(b), "r"(c), "r"(d) : "memory");
}
DEVI void red_add2(float2* p, float a, float b) { asm volatile("red.relaxed.gpu.global.add.v2.f32 [%0], {%1,%2};" :: "l"(p), "f"(a), "f"(b) : "memory"); }
DEVI float rcp(float x) { float y; asm("rcp.approx.ftz.f32 %0, %1;" : "=f"(y) : "f"(x)); return y; }
DEVI float ex2(float x) { float y; asm("ex2.approx.ftz.f32 %0, %1;" : "=f"(y) : "f"(x)); return y; }
DEVI uint64_t mkdesc(uint32_t addr, uint32_t lbo, uint32_t sbo, uint32_t swz) {
  return (uint64_t)((addr & 0x3FFFF) >> 4) | ((uint64_t)(lbo >> 4) << 16) | ((uint64_t)(sbo >> 4) << 32) | ((uint64_t)swz << 62);
}
DEVI void wg_fence() { asm volatile("wgmma.fence.sync.aligned;" ::: "memory"); }
DEVI void wg_commit() { asm volatile("wgmma.commit_group.sync.aligned;" ::: "memory"); }
template <int N> DEVI void wg_wait() { asm volatile("wgmma.wait_group.sync.aligned %0;" :: "n"(N) : "memory"); }
#define ACC4(d, o) "+f"(d[o]), "+f"(d[o + 1]), "+f"(d[o + 2]), "+f"(d[o + 3])
constexpr uint32_t DHI_SW128 = (1024u >> 4) | (1u << 30);
DEVI uint32_t desc_lo(uint32_t addr, uint32_t lbo) { return ((addr & 0x3FFFF) >> 4) | ((lbo >> 4) << 16); }
template <int OB_, int ACC> DEVI void wgmma_rs_n32(float (&d)[16], const uint32_t* a, uint32_t b) {
  asm volatile("{.reg .b64 db; .reg .b32 tb; add.u32 tb, %20, %21; mov.b64 db, {tb, %22};\n"
               "wgmma.mma_async.sync.aligned.m64n32k16.f32.bf16.bf16 {%0,%1,%2,%3,%4,%5,%6,%7,%8,%9,%10,%11,%12,%13,%14,%15}, {%16,%17,%18,%19}, db, %23, 1, 1, 0;}"
               : ACC4(d, 0), ACC4(d, 4), ACC4(d, 8), ACC4(d, 12) : "r"(a[0]), "r"(a[1]), "r"(a[2]), "r"(a[3]), "r"(b), "n"(OB_ >> 4), "n"(DHI_SW128), "n"(ACC));
}
template <int K0, int K1, int ACC = 1> struct Unroll {
  static DEVI void kbulk(float (&d)[16], const uint32_t* W, uint32_t x) { wgmma_rs_n32<(K0 >> 2) * 4096 + (K0 & 3) * 32, ACC>(d, W + K0 * 4, x); Unroll<K0 + 1, K1>::kbulk(d, W, x); }
};
template <int K1> struct Unroll<K1, K1, 1> {
  static DEVI void kbulk(float (&)[16], const uint32_t*, uint32_t) {}
};

DEVI void wgmma_n192_nt(float (&d)[96], uint64_t a, uint64_t b, int acc) {
  asm volatile("{.reg .pred p; setp.ne.b32 p, %98, 0;\n"
               "wgmma.mma_async.sync.aligned.m64n192k16.f32.bf16.bf16 {%0,%1,%2,%3,%4,%5,%6,%7,%8,%9,%10,%11,%12,%13,%14,%15,%16,%17,%18,%19,%20,%21,%22,%23,%24,%25,%26,%27,%28,%29,%30,%31,%32,%33,%34,%35,%36,%37,%38,%39,%40,%41,%42,%43,%44,%45,%46,%47,%48,%49,%50,%51,%52,%53,%54,%55,%56,%57,%58,%59,%60,%61,%62,%63,%64,%65,%66,%67,%68,%69,%70,%71,%72,%73,%74,%75,%76,%77,%78,%79,%80,%81,%82,%83,%84,%85,%86,%87,%88,%89,%90,%91,%92,%93,%94,%95}, %96, %97, p, 1, 1, 0, 1;}"
               : ACC4(d, 0), ACC4(d, 4), ACC4(d, 8), ACC4(d, 12), ACC4(d, 16), ACC4(d, 20), ACC4(d, 24), ACC4(d, 28), ACC4(d, 32), ACC4(d, 36), ACC4(d, 40), ACC4(d, 44), ACC4(d, 48), ACC4(d, 52), ACC4(d, 56), ACC4(d, 60), ACC4(d, 64), ACC4(d, 68), ACC4(d, 72), ACC4(d, 76), ACC4(d, 80), ACC4(d, 84), ACC4(d, 88), ACC4(d, 92) : "l"(a), "l"(b), "r"(acc));
}
DEVI void wgmma_n160_nt(float (&d)[80], uint64_t a, uint64_t b, int acc) {
  asm volatile("{.reg .pred p; setp.ne.b32 p, %82, 0;\n"
               "wgmma.mma_async.sync.aligned.m64n160k16.f32.bf16.bf16 {%0,%1,%2,%3,%4,%5,%6,%7,%8,%9,%10,%11,%12,%13,%14,%15,%16,%17,%18,%19,%20,%21,%22,%23,%24,%25,%26,%27,%28,%29,%30,%31,%32,%33,%34,%35,%36,%37,%38,%39,%40,%41,%42,%43,%44,%45,%46,%47,%48,%49,%50,%51,%52,%53,%54,%55,%56,%57,%58,%59,%60,%61,%62,%63,%64,%65,%66,%67,%68,%69,%70,%71,%72,%73,%74,%75,%76,%77,%78,%79}, %80, %81, p, 1, 1, 0, 1;}"
               : ACC4(d, 0), ACC4(d, 4), ACC4(d, 8), ACC4(d, 12), ACC4(d, 16), ACC4(d, 20), ACC4(d, 24), ACC4(d, 28), ACC4(d, 32), ACC4(d, 36), ACC4(d, 40), ACC4(d, 44), ACC4(d, 48), ACC4(d, 52), ACC4(d, 56), ACC4(d, 60), ACC4(d, 64), ACC4(d, 68), ACC4(d, 72), ACC4(d, 76) : "l"(a), "l"(b), "r"(acc));
}
DEVI void wgmma_n240_nn(float (&d)[120], uint64_t a, uint64_t b, int acc) {
  asm volatile("{.reg .pred p; setp.ne.b32 p, %122, 0;\n"
               "wgmma.mma_async.sync.aligned.m64n240k16.f32.bf16.bf16 {%0,%1,%2,%3,%4,%5,%6,%7,%8,%9,%10,%11,%12,%13,%14,%15,%16,%17,%18,%19,%20,%21,%22,%23,%24,%25,%26,%27,%28,%29,%30,%31,%32,%33,%34,%35,%36,%37,%38,%39,%40,%41,%42,%43,%44,%45,%46,%47,%48,%49,%50,%51,%52,%53,%54,%55,%56,%57,%58,%59,%60,%61,%62,%63,%64,%65,%66,%67,%68,%69,%70,%71,%72,%73,%74,%75,%76,%77,%78,%79,%80,%81,%82,%83,%84,%85,%86,%87,%88,%89,%90,%91,%92,%93,%94,%95,%96,%97,%98,%99,%100,%101,%102,%103,%104,%105,%106,%107,%108,%109,%110,%111,%112,%113,%114,%115,%116,%117,%118,%119}, %120, %121, p, 1, 1, 0, 0;}"
               : ACC4(d, 0), ACC4(d, 4), ACC4(d, 8), ACC4(d, 12), ACC4(d, 16), ACC4(d, 20), ACC4(d, 24), ACC4(d, 28), ACC4(d, 32), ACC4(d, 36), ACC4(d, 40), ACC4(d, 44), ACC4(d, 48), ACC4(d, 52), ACC4(d, 56), ACC4(d, 60), ACC4(d, 64), ACC4(d, 68), ACC4(d, 72), ACC4(d, 76), ACC4(d, 80), ACC4(d, 84), ACC4(d, 88), ACC4(d, 92), ACC4(d, 96), ACC4(d, 100), ACC4(d, 104), ACC4(d, 108), ACC4(d, 112), ACC4(d, 116) : "l"(a), "l"(b), "r"(acc));
}
DEVI void wgmma_n80_nt(float (&d)[40], uint64_t a, uint64_t b, int acc) {
  asm volatile("{.reg .pred p; setp.ne.b32 p, %42, 0;\n"
               "wgmma.mma_async.sync.aligned.m64n80k16.f32.bf16.bf16 {%0,%1,%2,%3,%4,%5,%6,%7,%8,%9,%10,%11,%12,%13,%14,%15,%16,%17,%18,%19,%20,%21,%22,%23,%24,%25,%26,%27,%28,%29,%30,%31,%32,%33,%34,%35,%36,%37,%38,%39}, %40, %41, p, 1, 1, 0, 1;}"
               : ACC4(d, 0), ACC4(d, 4), ACC4(d, 8), ACC4(d, 12), ACC4(d, 16), ACC4(d, 20), ACC4(d, 24), ACC4(d, 28), ACC4(d, 32), ACC4(d, 36) : "l"(a), "l"(b), "r"(acc));
}

#define ACQ 0
DEVI uint32_t ld_acquire(const uint32_t* p) {
  uint32_t v;
  if (ACQ) asm volatile("ld.acquire.gpu.global.u32 %0, [%1];" : "=r"(v) : "l"(p) : "memory");
  else asm volatile("ld.relaxed.gpu.global.u32 %0, [%1];" : "=r"(v) : "l"(p) : "memory");
  return v;
}
DEVI uint4 ldcg_if(const void* p, bool on) {
  uint4 v;
  asm volatile("{.reg .pred p; setp.ne.u32 p, %5, 0; mov.u32 %0, 0; mov.u32 %1, 0; mov.u32 %2, 0; mov.u32 %3, 0;\n"
               "@p ld.global.cg.v4.u32 {%0,%1,%2,%3}, [%4];}" : "=&r"(v.x), "=&r"(v.y), "=&r"(v.z), "=&r"(v.w) : "l"(p), "r"((uint32_t)on) : "memory");
  return v;
}
DEVI void red_release(uint32_t* p) { asm volatile("red.release.gpu.global.add.u32 [%0], 1;" :: "l"(p) : "memory"); }
#define TIGHT 1
DEVI void wait_count_t(const uint32_t* p, uint32_t n, bool tight) {
  for (int i = 0; i < 4000000 && ld_acquire(p) < n; i++) if (!(TIGHT && tight)) __nanosleep(100);
}
DEVI void wait_count(const uint32_t* p, uint32_t n) {
  for (int i = 0; i < 4000000 && ld_acquire(p) < n; i++) __nanosleep(100);
}
DEVI void spin_count(const uint32_t* p, uint32_t n) { for (int i = 0; i < 4000000 && ld_acquire(p) < n; i++) {} }
DEVI void mbar_wait_long(uint32_t bar, uint32_t par) { for (int n = 0; n < 4000000 && !mbar_try(bar, par); n++) {} }
DEVI void ln_row(float (&v)[20], bf16* y, int lane) {
  float s = 0.f;
#pragma unroll
  for (int i = 0; i < 20; i++) s += v[i];
#pragma unroll
  for (int o = 16; o; o >>= 1) s += __shfl_xor_sync(0xffffffffu, s, o);
  const float m = s * (1.0f / DM); float q = 0.f;
#pragma unroll
  for (int i = 0; i < 20; i++) { v[i] -= m; q += v[i] * v[i]; }
#pragma unroll
  for (int o = 16; o; o >>= 1) q += __shfl_xor_sync(0xffffffffu, q, o);
  const float r = rsqrtf(q * (1.0f / DM) + 1e-5f);
#pragma unroll
  for (int i = 0; i < 5; i++) *(uint2*)(y + i * 128 + lane * 4) = make_uint2(pack_bf16(v[4 * i] * r, v[4 * i + 1] * r), pack_bf16(v[4 * i + 2] * r, v[4 * i + 3] * r));
}

DEVI uint32_t mag4(uint32_t m, const uint32_t* f) {
  return __vmaxu2(__vmaxu2(m, __vmaxu2(f[0] & 0x7FFF7FFFu, f[1] & 0x7FFF7FFFu)), __vmaxu2(f[2] & 0x7FFF7FFFu, f[3] & 0x7FFF7FFFu));
}
DEVI void publish_max(uint32_t a, uint32_t m) {
  m = __reduce_max_sync(0xffffffffu, max(m & 0xFFFFu, m >> 16));
  if ((threadIdx.x & 31) == 0) asm volatile("red.shared.max.u32 [%0], %1;" :: "r"(a), "r"(m) : "memory");
}

namespace ch {
constexpr uint32_t WQ = 0;
constexpr uint32_t WOF2 = 81920;
constexpr uint32_t WOF = 106496;
constexpr uint32_t XB = 143360;
constexpr uint32_t MEMB = 184320;
constexpr uint32_t KT = 194560;
constexpr uint32_t VT = 199680;
constexpr uint32_t PK = 204800;
constexpr uint32_t QS = 212992;
constexpr uint32_t KP = 215040;
constexpr uint32_t EX = 217088;
constexpr uint32_t OB = 221184;
constexpr uint32_t SX = 224256;
constexpr uint32_t WOF3 = 226176;
constexpr uint32_t WOSTAGE = 143360;
constexpr uint32_t PB = OB;
constexpr uint32_t WMX = OB + 128;
constexpr uint32_t MISC = 228224;
constexpr uint32_t BAR_XF = MISC + 56;
constexpr uint32_t BAR_WK = MISC + 48, BAR_W1 = MISC, BAR_W2 = MISC + 8, BAR_X0 = MISC + 16, BAR_X1 = MISC + 24, BAR_S = MISC + 32, BAR_O = MISC + 40;
constexpr uint32_t MX = MISC + 64;
constexpr uint32_t INV = MX + 32;
#define PD_ 550
#define XD_ 150
#define X1D_ 0
#define PFW 0
constexpr uint32_t SMEM = 228352;
}

#define TS(e)
#define TSV(e, v)
#define TSX(x)
#define TSD(e, x)

#define SS(e)
#define E1(id, x)
#define PIN(x) asm volatile("" : "+r"(x))
#define PINF(x) asm volatile("" : "+f"(x))
#define PINL(x) asm volatile("" : "+l"(x))

DEVI uint32_t ar_line_off(uint32_t l) { return (l >> 2) * 1024 + (l & 3) * 128; }
DEVI uint32_t ar_tile_off(int T) { return (T >> 1) * 1024 + (T & 1) * 256; }
DEVI uint32_t ar_extra_off(uint32_t T) { return ar_line_off(80 + (T >> 2)) + (T & 3) * 32; }

DEVI void wo_red(const char* p, uint32_t w0, uint32_t w1, bool last) {
  red_f16x2((void*)p, last ? 0x3C00u : w0);
  red_f16x2((void*)(p + 128), last ? 0x3C00u : w1);
}
DEVI void wo_red_extra_p(const char* px, uint32_t w0, uint32_t w1, uint32_t ln) {
  asm volatile("{.reg .pred p; setp.eq.u32 p, %5, 31; @p red.relaxed.gpu.global.add.noftz.v4.f16x2 [%0], {%1,%2,%3,%4};}"
               :: "l"(px), "r"(w0), "r"(w1), "r"(0u), "r"(0x3C00u), "r"(ln) : "memory");
}

#define ARH 2
DEVI void sched_fence(uint32_t zero) {
#pragma unroll 1
  for (uint32_t i = 0; i < zero; i++) asm volatile("nanosleep.u32 0;" ::: "memory");
}
template <int N> DEVI void code_pad(uint32_t zero) {
  if (N > 0) {
#pragma unroll 1
    for (uint32_t i = 0; i < zero; i++) {
#pragma unroll
      for (int k = 0; k < N; k++) asm volatile("nanosleep.u32 0;" ::: "memory");
    }
  }
}
#define PAD1 0
#define PAD0 0
DEVI void loaded(uint32_t x) { asm volatile("{.reg .pred p; setp.eq.u32 p, %0, 0xdeadbeef; @p nanosleep.u32 0;}" :: "r"(x) : "memory"); }
DEVI uint32_t opq(uint32_t x) { asm volatile("" : "+r"(x)); return x; }

DEVI uint32_t ar_read(const char* arb, uint32_t sb, int w, uint32_t lane_, uint32_t zero, uint32_t tref, int dly, int s) {
  const int wg = 2; (void)wg; (void)s;
  const uint32_t lane = opq(lane_);
  const int b0 = (w >> 1) * 10 + (w & 1);
  const uint32_t e = min(lane, 9u), T = 2 * b0 + 4 * (e >> 1) + (e & 1);
  const char* p0 = arb + b0 * 1024 + lane * 16;
  const char* p2 = arb + ar_extra_off(T);
  uint32_t dst = sb + ch::MEMB + b0 * 512 + lane * 16, dst2 = sb + ch::MEMB + (16 * T + 7) * 16 + 12;
  uint32_t v[6][4];
  PINL(p0); PINL(p2); PIN(dst); PIN(dst2);
  while ((int)(clk32() - tref) < dly) {}
#pragma unroll
  for (int i = 0; i < 5; i++) ld_relaxed128(v[i], p0 + i * 2048);
  ld_relaxed128(v[5], p2);
  sched_fence(zero);
  TS(4);
  uint32_t bad = 0;
#pragma unroll
  for (int i = 0; i < 5; i++) bad |= v[i][3] ^ 0x5000u;
  if ((lane & 7) != 7) bad = 0;
  bad |= v[5][3] ^ 0x5000u;
  TSD(5, bad);
  E1(6, bad);
  int n = 0;
  if (__any_sync(0xffffffffu, bad != 0)) {
    if (lane == 0) sts32(sb + ch::MX + 20, 1u);
    while (true) {
      bad = 0;
#pragma unroll
      for (int i = 0; i < 6; i++) if ((i == 5 || (lane & 7) == 7) && v[i][3] != 0x5000u) bad |= 1u << i;
      bad = __reduce_or_sync(0xffffffffu, bad);
      if (!bad || ++n > SPIN_LIMIT) break;
#pragma unroll
      for (int i = 0; i < 6; i++) if (bad >> i & 1) ld_relaxed128(v[i], i < 5 ? p0 + i * 2048 : p2);
    }
  }
  TSV(6, n);
  const uint32_t x0 = f16x2_to_bf16x2(v[5][0]), x1 = f16x2_to_bf16x2(v[5][1]);
#pragma unroll
  for (int i = 0; i < 5; i++) {
    sts128(dst + i * 1024, f16x2_to_bf16x2(v[i][0]), f16x2_to_bf16x2(v[i][1]), f16x2_to_bf16x2(v[i][2]), f16x2_to_bf16x2(v[i][3]));
    if (i == ARH - 1 || i == 4) {
      __syncwarp();
      sts32(dst2, x0); sts32(dst2 + 128, x1);
      if (i < 4) { TS(7); bar_arrive(1, 384); sched_fence(zero); } else { TSX(TS(1)); bar_sync(3, 384); }
    }
  }
  const uint32_t keep = (lane & 7) == 7 ? 0u : 0x7FFF7FFFu;
  uint32_t m = __vmaxu2(v[5][0] & 0x7FFF7FFFu, v[5][1] & 0x7FFF7FFFu);
#pragma unroll
  for (int i = 0; i < 5; i++) m = __vmaxu2(__vmaxu2(m, __vmaxu2(v[i][0] & 0x7FFF7FFFu, v[i][1] & 0x7FFF7FFFu)), __vmaxu2(v[i][2] & 0x7FFF7FFFu, v[i][3] & keep));
  return m;
}

#define VL 0
struct Peers {
  uint32_t a[2];
  DEVI Peers(uint32_t sb, int j) {
#pragma unroll
    for (int r = 0; r < 2; r++) { int peer = j + 1 + r; if (peer >= 3) peer -= 3; a[r] = mapa(sb, peer); }
  }
};
DEVI uint32_t lane_id() { const uint32_t l = threadIdx.x & 31; return __shfl_sync(0xffffffffu, l, l); }
DEVI void score_tile(uint32_t sb, uint32_t qa, const uint32_t (&b0)[4], const uint32_t (&b1)[4], const Peers& pe, uint32_t off, uint32_t lane) {
  float c0[4] = {0.f, 0.f, 0.f, 0.f}, c1[4] = {0.f, 0.f, 0.f, 0.f};
  uint32_t a0[4], a1[4], a2[4], a3[4];
  ldsm4t(a0, qa); ldsm4t(a1, qa + 256); ldsm4t(a2, qa + 512); ldsm4t(a3, qa + 768);
  mma16816(c0, a0, b0[0], b0[1]); mma16816(c1, a1, b0[2], b0[3]);
  mma16816(c0, a2, b1[0], b1[1]); mma16816(c1, a3, b1[2], b1[3]);
  if (!VL) asm volatile("bar.arrive 5, 288;" : "+f"(c0[0]), "+f"(c1[0]) :: "memory");
  const float cs = 0.25f * 0.07216878364870322f * 1.4426950408889634f;
  const float x = ((c0[0] + c0[2]) + (c1[0] + c1[2])) * cs, y = ((c0[1] + c0[3]) + (c1[1] + c1[3])) * cs;
  uint32_t u; asm("cvt.rn.satfinite.f16x2.f32 %0, %1, %2;" : "=r"(u) : "f"(y), "f"(x));
  st_async32(pe.a[0] + off, u, pe.a[0] + ch::BAR_S);
  st_async32(pe.a[1] + off, u, pe.a[1] + ch::BAR_S);
  sts32(sb + off, u);
  __syncwarp();
  if (lane == 0) mbar_arrive(sb + ch::BAR_S);
}
DEVI uint32_t hadd2(uint32_t a, uint32_t b) { uint32_t r; asm("add.rn.f16x2 %0, %1, %2;" : "=r"(r) : "r"(a), "r"(b)); return r; }
DEVI uint32_t hmax2(uint32_t a, uint32_t b) { uint32_t r; asm("max.f16x2 %0, %1, %2;" : "=r"(r) : "r"(a), "r"(b)); return r; }
DEVI uint32_t add_bf16x2(uint32_t a, uint32_t b) { uint32_t r; asm("add.rn.bf16x2 %0, %1, %2;" : "=r"(r) : "r"(a), "r"(b)); return r; }

DEVI uint32_t slab_off(uint32_t base, int w, uint32_t lane) { return base + (16 * w + (lane >> 2)) * 80 + (lane & 3) * 4; }
DEVI void release_x(uint32_t sb, int half, int w, uint32_t lane) {
  if (lane == 0) {
    if (w == 0) mbar_expect(sb + ch::BAR_X0 + half * 8, 20480);
    mbar_arrive_cluster(mapa(sb + ch::BAR_XF, half));
  }
}
#define TSYNC 1
#define KORD 0
#define X0E 0
#define X0D_ 0
#define X1E 1
#define KS2 0
#define SKIPT 0
DEVI void store_slabs(uint32_t sb, int s, int h, int j) {
  bf16* kvp = g_kv + ((size_t)(s * NH + h) * 2 * DH + 64 * j) * NKEY;
  fence_async();
  bulk_store(kvp, sb + ch::KT, SLAB);
  bulk_store(kvp + DH * NKEY, sb + ch::VT, SLAB);
  asm volatile("cp.async.bulk.commit_group;" ::: "memory");
}

template <int MODE>
DEVI void tokens_partial(uint32_t sb, uint32_t dst, const uint32_t* W, uint32_t xdesc, int w, uint32_t lane) {
  float d[16];
#pragma unroll
  for (int i = 0; i < 16; i++) d[i] = 0.f;
  wg_fence();
  if (!((SKIPT >> (MODE == 3 ? 1 : MODE)) & 1)) Unroll<20, 40, 0>::kbulk(d, W - 80, xdesc);
  wg_commit();
  if (MODE == 1) bar_sync(12, 384);
  if (!KS2 && MODE == 2) bar_sync(11, 256);
  wg_wait<0>();
  if (!KS2 && (MODE == 1 || MODE == 3)) release_x(sb, 1, w, lane);
  if (MODE == 1) bar_sync(13, 384);
  if (KS2 && MODE == 2) release_x(sb, 1, w, lane);
  dst += sb + w * 512 + opq(lane) * 16;
#pragma unroll
  for (int i = 0; i < 4; i++)
    sts128(dst + i * 2048, __float_as_uint(d[4 * i]), __float_as_uint(d[4 * i + 1]), __float_as_uint(d[4 * i + 2]), __float_as_uint(d[4 * i + 3]));
  if (KS2 && MODE == 2) bar_arrive(11, 256);
}
#define LSH 0
#define KPK 16
template <bool LOOP>
DEVI void tokens_finish(uint32_t sb, const uint32_t* W, uint32_t xdesc, int w, uint32_t lane, int s = 0, const CUtensorMap* mx = nullptr) {
  const uint32_t ln = opq(lane), t16 = sb + w * 512 + ln * 16, slab = sb + slab_off(16, w, ln);
  float d[16]; uint32_t e[4][4];
#pragma unroll
  for (int i = 0; i < 16; i++) d[i] = 0.f;
  wg_fence();
  if (!(LOOP && (SKIPT & 8))) Unroll<0, 20, 0>::kbulk(d, W + 80, xdesc);
  wg_commit();
  if (!KS2 && !KORD && LOOP) bar_arrive(6, 256);
  if (LOOP && LSH == 2 && s < 0) bar_sync(8, 256);
  if (!LOOP) {
    bar_sync(8, 256);
    if (w == 3 && lane == 0) { mbar_expect(sb + ch::BAR_X1, 20480); tma3d(sb + ch::XB + 20480, mx, 0, SEG, 5, sb + ch::BAR_X1); }
    __syncwarp();
  }
#pragma unroll
  for (int i = 0; i < 4; i++) lds128(e[i], t16 + ch::QS + i * 2048);
  wg_wait<0>();
  uint32_t u[8];
#pragma unroll
  for (int i = 0; i < 4; i++) {
    u[2 * i] = pack_bf16(d[4 * i] + __uint_as_float(e[i][0]), d[4 * i + 1] + __uint_as_float(e[i][1]));
    u[2 * i + 1] = pack_bf16(d[4 * i + 2] + __uint_as_float(e[i][2]), d[4 * i + 3] + __uint_as_float(e[i][3]));
  }
  wg_fence();
  if (!(LOOP && (SKIPT & 16))) Unroll<0, 6, 0>::kbulk(d, W, xdesc);
#pragma unroll
  for (int i = 0; i < 4; i++) { sts32(slab + ch::VT + i * 16, u[2 * i]); sts32(slab + ch::VT + i * 16 + 640, u[2 * i + 1]); }
  if (KS2) {
    if (!(LOOP && (SKIPT & 16))) Unroll<6, KPK>::kbulk(d, W, xdesc);
    if (LOOP) bar_sync(11, 256);
  }
#pragma unroll
  for (int i = 0; i < 4; i++) lds128(e[i], t16 + ch::PK + i * 2048);
  if (!KS2) {
    if (!(LOOP && (SKIPT & 16))) Unroll<6, KPK>::kbulk(d, W, xdesc);
    if (LOOP) asm volatile("bar.arrive 11, 256;" : "+r"(e[0][0]), "+r"(e[1][0]), "+r"(e[2][0]), "+r"(e[3][0]) :: "memory");
  }
  if (!(LOOP && (SKIPT & 16))) Unroll<KPK, 20>::kbulk(d, W, xdesc);
  wg_commit(); wg_wait<0>();
  release_x(sb, 0, w, lane);
  if (LOOP) E1(7, __float_as_uint(d[0]));
#pragma unroll
  for (int i = 0; i < 4; i++) {
    sts32(slab + ch::KT + i * 16, pack_bf16(d[4 * i] + __uint_as_float(e[i][0]), d[4 * i + 1] + __uint_as_float(e[i][1])));
    sts32(slab + ch::KT + i * 16 + 640, pack_bf16(d[4 * i + 2] + __uint_as_float(e[i][2]), d[4 * i + 3] + __uint_as_float(e[i][3])));
  }
}

DEVI uint32_t afrag_off(int w, uint32_t lane) { return ((lane >> 4) * 8 + (lane & 7)) * 128 + (((w * 2 + ((lane >> 3) & 1)) ^ (lane & 7)) << 4); }
#define NF 5
#define WQR 0
DEVI void ldwq(uint32_t (&f)[4], uint32_t a) { if (WQR) lds128(f, a); else ldsm4t(f, a); }
DEVI void proj_stage(uint32_t (&f)[NF][4], uint32_t qa) {
#pragma unroll
  for (int i = 0; i < NF; i++) ldwq(f[i], qa + i * 2048);
}
template <int WG>
DEVI void proj_mem(float (&q)[4], float (&k)[4], float (&v)[4], uint32_t (&f)[NF][4], const uint32_t* W, uint32_t qa, uint32_t ba, uint32_t sb, int w, int s) {
  uint32_t b[2][4];
  const int wg = WG; (void)wg; (void)sb; (void)w; (void)s;
#pragma unroll
  for (int i = 0; i < 4; i++) q[i] = k[i] = v[i] = 0.f;
  bar_sync(1, 384);
  ldsm4t(b[0], ba);
  if (WG == 0) E1(8, b[0][0]);
  if (WG == 1) { TSX(TSD(5, b[0][0])); }
#pragma unroll
  for (int k2 = 0; k2 < 10; k2++) {
    if (WG == 1 && k2 + 1 == 2 * ARH) { TSX(TSD(7, __float_as_uint(v[0]))); }
    if (k2 + 1 == 2 * ARH) bar_sync(3, 384);
    if (k2 < 9) ldsm4t(b[(k2 + 1) & 1], ba + (k2 + 1) * 512);
    if (WG == 1 && k2 + 1 == 2 * ARH) { TSX(TSD(6, b[(k2 + 1) & 1][0])); }
    if (WG == 0 && k2 + 1 == 2 * ARH) { TSX(TSD(7, __float_as_uint(v[0]))); }
    mma16816(q, f[(2 * k2) % NF], b[k2 & 1][0], b[k2 & 1][1]);
    if (2 * k2 + NF < 20) ldwq(f[(2 * k2) % NF], qa + (2 * k2 + NF) * 2048);
    mma16816(k, &W[k2 * 8], b[k2 & 1][0], b[k2 & 1][1]);
    mma16816(v, &W[80 + k2 * 8], b[k2 & 1][0], b[k2 & 1][1]);
    mma16816(q, f[(2 * k2 + 1) % NF], b[k2 & 1][2], b[k2 & 1][3]);
    if (2 * k2 + 1 + NF < 20) ldwq(f[(2 * k2 + 1) % NF], qa + (2 * k2 + 1 + NF) * 2048);
    mma16816(k, &W[k2 * 8 + 4], b[k2 & 1][2], b[k2 & 1][3]);
    mma16816(v, &W[84 + k2 * 8], b[k2 & 1][2], b[k2 & 1][3]);
  }
}

template <bool BAR>
DEVI void wo_tile_smem(uint32_t sb, uint32_t fa, uint32_t ob, int par, const char* p, const char* px, bool last, float& sc) {
  uint32_t f[6][4], b[2][4];
  float c0[4] = {0.f, 0.f, 0.f, 0.f}, c1[4] = {0.f, 0.f, 0.f, 0.f};
#pragma unroll
  for (int k = 0; k < 6; k++) lds128(f[k], fa + k * 512);
  if (BAR) bar_sync(9, 384);
  ldsm4t(b[0], ob); ldsm4t(b[1], ob + 512);
  sc = __uint_as_float(lds32(sb + ch::MX + 16));
  float2 iv = lds64f(sb + ch::INV + (opq(threadIdx.x) & 3) * 8);
  iv.x *= sc; iv.y *= sc;
  mma16816(c0, f[0], b[0][0], b[0][1]); mma16816(c1, f[1], b[0][2], b[0][3]);
  mma16816(c0, f[2], b[1][0], b[1][1]); mma16816(c1, f[3], b[1][2], b[1][3]);
#pragma unroll
  for (int k = 0; k < 4; k++) lds128(f[k], fa + (6 + k) * 512);
  mbar_wait(sb + ch::BAR_O, par);
  ldsm4t(b[0], ob + 1024); ldsm4t(b[1], ob + 1536);
  mma16816(c0, f[4], b[0][0], b[0][1]); mma16816(c1, f[5], b[0][2], b[0][3]);
  lds128(f[4], fa + 10 * 512); lds128(f[5], fa + 11 * 512);
  ldsm4t(b[0], ob + 2048);
  mma16816(c0, f[0], b[1][0], b[1][1]); mma16816(c1, f[1], b[1][2], b[1][3]);
  ldsm4t(b[1], ob + 2560);
  mma16816(c0, f[2], b[0][0], b[0][1]); mma16816(c1, f[3], b[0][2], b[0][3]);
  mma16816(c0, f[4], b[1][0], b[1][1]); mma16816(c1, f[5], b[1][2], b[1][3]);
  const uint32_t w0 = pack_f16((c0[0] + c1[0]) * iv.x, (c0[1] + c1[1]) * iv.y), w1 = pack_f16((c0[2] + c1[2]) * iv.x, (c0[3] + c1[3]) * iv.y);
  wo_red(p, w0, w1, last);
  wo_red_extra_p(px, w0, w1, last ? 31u : 0u);
}

#define LNFIRST 0
DEVI void chain_prepare(const bf16* __restrict__ x) {
  const int t = threadIdx.x, lane = t & 31, r0 = blockIdx.x * 11 + (t >> 5);
  asm volatile("griddepcontrol.wait;" ::: "memory");
  uint2 u[2][5];
#pragma unroll
  for (int i = 0; i < 10; i++) u[i / 5][i % 5] = __ldcg((const uint2*)(x + min(r0 + (i / 5) * 1056, S_LEN - 1) * DM + (i % 5) * 128 + lane * 4));
#pragma unroll
  for (int rr = 0; rr < 2; rr++) {
    float v[20];
#pragma unroll
    for (int i = 0; i < 5; i++) {
      v[4 * i] = __uint_as_float(u[rr][i].x << 16); v[4 * i + 1] = __uint_as_float(u[rr][i].x & 0xFFFF0000u);
      v[4 * i + 2] = __uint_as_float(u[rr][i].y << 16); v[4 * i + 3] = __uint_as_float(u[rr][i].y & 0xFFFF0000u);
    }
    if (r0 + rr * 1056 < S_LEN) ln_row(v, g_xn + (r0 + rr * 1056) * DM, lane);
  }
}
#define LNF 0
#define PWIN 3
#define PWIN1 3
#define LASTG 1
#define PSPL 1
DEVI void load_weights(uint32_t (&W)[160], uint32_t sb, int G, int w, int j, int layer) {
  using namespace ch;
  const uint32_t lane = threadIdx.x & 31;
  const uint32_t wa = sb + G * 40960 + afrag_off(w, lane);
#pragma unroll 1
  for (int i = 0; i < 5; i++) mbar_wait_long(sb + PB + i * 8, 0);
  if (threadIdx.x == 0) PT(0, 10);
#pragma unroll
  for (int kk = 0; kk < 20; kk++) ldsm4t_p(&W[80 + kk * 4], wa + 81920 + kk * 2048);
  uint32_t m = 0;
#pragma unroll
  for (int kk = 0; kk < 20; kk++) m = mag4(m, &W[80 + kk * 4]);
  publish_max(sb + WMX, m);
  bar_sync(8, 256);
  if (threadIdx.x == 0) mbar_arrive(sb + BAR_W1);
#pragma unroll 1
  for (int i = 7; i < 12; i++) mbar_wait_long(sb + PB + i * 8, 0);
  if (threadIdx.x == 0) PT(0, 9);
#pragma unroll
  for (int kk = 0; kk < 20; kk++) ldsm4t_p(&W[kk * 4], wa + kk * 2048);
  loaded(W[79]);
  bar_sync(8, 256);
  if (threadIdx.x == 0) mbar_arrive(sb + BAR_WK);
  m = 0;
  mbar_wait_long(sb + PB + (G == 0 ? 13 : 6) * 8, 0);
  if (threadIdx.x == 0) PT(0, 11);
  const uint32_t src = (G == 0 ? sb + WOF : sb + WOSTAGE + 2 * 24576) + afrag_off(w, lane);
  if (G == 1) {
    for (int kk = 0; kk < 12; kk++) { uint32_t f[4]; ldsm4t(f, src + kk * 2048); m = mag4(m, f); }
    publish_max(sb + WMX + 4, m);
    bar_sync(7, 384);
  }
  if (G == 1 || w < 2) {
    for (int kk = 0; kk < 12; kk++) {
      uint32_t f[4];
      ldsm4t(f, src + ((kk + 4 * j) % 12) * 2048);
      sts128(sb + WOF + ((G == 0 ? 4 + w : w) * 12 + kk) * 512 + lane * 16, f[0], f[1], f[2], f[3]);
      if (G == 0) m = mag4(m, f);
    }
  }
  if (G == 0) { publish_max(sb + WMX + 4, m); bar_sync(7, 384); }
  bar_sync(7, 384);
}
DEVI void arrange_wq(uint32_t sb, int G, int w, int layer) {
  using namespace ch;
  const uint32_t lane = threadIdx.x & 31;
  mbar_wait_long(sb + BAR_W2, 0);
  if (threadIdx.x == 0) PT(0, 15);
  if (WQR) {
    const uint32_t src = sb + WQ + G * 40960 + afrag_off(w, lane), dst = sb + WQ + G * 40960 + w * 512 + lane * 16;
#pragma unroll 1
    for (int r = 0; r < 5; r++) {
      uint32_t f[4][4];
#pragma unroll
      for (int i = 0; i < 4; i++) ldsm4t(f[i], src + (r * 4 + i) * 2048);
      bar_sync(14 + G, 128);
#pragma unroll
      for (int i = 0; i < 4; i++) sts128(dst + (r * 4 + i) * 2048, f[i][0], f[i][1], f[i][2], f[i][3]);
    }
    __syncwarp();
  }
}

namespace tl {
constexpr uint32_t STAGE = 36864, NST = 5, OST = NST * STAGE, FULL = OST + 40960, EMPTY = FULL + 40;
constexpr int RT0 = 13, SL0 = 10;
}
#define TDLY 0
DEVI void tail_load(uint32_t sb, Sync* sy, const CUtensorMap* moa, const CUtensorMap* mwo, int layer) {
  using namespace tl;
  (void)layer;
  const int rt = RT0 + (blockIdx.x >> 5), a = blockIdx.x & 3, b = (blockIdx.x & 31) >> 2;
  const int npre = rt == 15 ? NST : 0;
  for (int c = 0; c < npre; c++) { mbar_expect(sb + FULL + c * 8, STAGE); tma3d(sb + c * STAGE + 16384, mwo, 0, (b * 12 + c) * 64, a * 5, sb + FULL + c * 8); }
  if (TDLY && rt < 15) __nanosleep(TDLY);
  spin_count(&sy->o[rt * 16 + b], 8);
  XT(blockIdx.x, 0);
  fence_flag_to_bulk();
  uint32_t st = 0;
#pragma unroll 1
  for (int c = 0; c < 12; c++) {
    const uint32_t dst = sb + st * STAGE, fb = sb + FULL + st * 8;
    if (c >= npre) {
      if (c >= (int)NST) mbar_wait_long(sb + EMPTY + st * 8, c >= 2 * (int)NST);
      mbar_expect(fb, STAGE);
      tma3d(dst + 16384, mwo, 0, (b * 12 + c) * 64, a * 5, fb);
    }
    tma2d(dst, moa, (b * 12 + c) * 64, rt * 128, fb);
    if (++st == NST) st = 0;
  }
}
DEVI void tail_sum(uint32_t sb, Sync* sy, const bf16* __restrict__ xin, int cw, int w, int layer) {
  using namespace tl;
  (void)layer;
  const int ct = threadIdx.x, lane = ct & 31;
  const int rt = RT0 + (blockIdx.x >> 5), a = blockIdx.x & 3, b = (blockIdx.x & 31) >> 2;
  float d[80];
#pragma unroll
  for (int i = 0; i < 80; i++) d[i] = 0.f;
  bar_sync(14, 288);
  uint32_t st = 0, par = 0;
#pragma unroll 1
  for (int c = 0; c < 12; c++) {
    mbar_wait_long(sb + FULL + st * 8, par);
    if (c == 0 && ct == 0) XT(blockIdx.x, 1);
    const uint64_t da = mkdesc(sb + st * STAGE + cw * 8192, 16, 1024, 1), db = mkdesc(sb + st * STAGE + 16384, 4096, 512, 2);
    wg_fence();
#pragma unroll
    for (int k = 0; k < 4; k++) wgmma_n160_nt(d, da + k * 2, db + k * 64, c | k);
    wg_commit();
    if (c > 0) { wg_wait<1>(); if (lane == 0) mbar_arrive(sb + EMPTY + (st ? st - 1 : NST - 1) * 8); }
    if (++st == NST) { st = 0; par ^= 1; }
  }
  const int rl = b * 16 + (ct >> 4), q = ct & 15, r = rt * 128 + rl, c0 = a * 160 + q * 8;
  uint4 x[2];
#pragma unroll
  for (int i = 0; i < 2; i++) x[i] = ldcg_if(xin + r * DM + c0 + i * 128, i * 16 + q < 20);
  wg_wait<0>();
  const uint32_t orow = w * 16 + (lane & 15), ob = sb + OST + cw * 20480 + orow * 64;
#pragma unroll
  for (int i = 0; i < 10; i++)
    stsm4(ob + (i >> 1) * 4096 + ((((i & 1) * 2 + (lane >> 4)) ^ ((orow >> 1) & 3)) << 4), pack_bf16(d[8 * i], d[8 * i + 1]), pack_bf16(d[8 * i + 2], d[8 * i + 3]),
          pack_bf16(d[8 * i + 4], d[8 * i + 5]), pack_bf16(d[8 * i + 6], d[8 * i + 7]));
  fence_async();
  bar_sync(7 + cw, 128);
  const int sl0 = SL0 + (rt - RT0) * 8;
  if ((ct & 127) == 0) {
    bulk_store(g_sl + (size_t)(((sl0 + b) * 4 + a) * 2 + cw) * 10240, sb + OST + cw * 20480, 20480);
    asm volatile("cp.async.bulk.commit_group; cp.async.bulk.wait_group 0;" ::: "memory");
    XT(blockIdx.x, 2 + cw);
    publish_bulk<WFEN>(&sy->wcnt[(rt * 4 + a) * 2 + cw]);
  }
  if (ct == 32) spin_count(&sy->wcnt[(rt * 4 + a) * 2 + (b >> 2)], 8);
  __syncwarp();
  bar_sync(15, 256);
  const bf16* sl = g_sl + (size_t)((sl0 * 4 + a) * 2 + (rl >> 6)) * 10240 + (q >> 2) * 2048 + (rl & 63) * 32 + (((q & 3) ^ (rl >> 1 & 3)) << 3);
  uint4 u[8][2];
#pragma unroll
  for (int k = 0; k < 16; k++) u[k >> 1][k & 1] = ldcg_if(sl + (size_t)(k >> 1) * 128 * DM + (k & 1) * 8192, (k & 1) * 16 + q < 20);
  sched_fence(layer >> 4);
  float s1 = 0.f, s2 = 0.f;
#pragma unroll
  for (int i = 0; i < 2; i++) {
    float y[8];
#pragma unroll
    for (int e = 0; e < 8; e++) y[e] = 0.f;
#pragma unroll
    for (int k = 0; k < 8; k++) {
      const uint32_t v[4] = {u[k][i].x, u[k][i].y, u[k][i].z, u[k][i].w};
#pragma unroll
      for (int e = 0; e < 4; e++) { y[2 * e] += __uint_as_float(v[e] << 16); y[2 * e + 1] += __uint_as_float(v[e] & 0xFFFF0000u); }
    }
    const uint32_t v[4] = {x[i].x, x[i].y, x[i].z, x[i].w};
    uint32_t z[4];
#pragma unroll
    for (int e = 0; e < 4; e++) {
      z[e] = pack_bf16(__uint_as_float(v[e] << 16) + y[2 * e], __uint_as_float(v[e] & 0xFFFF0000u) + y[2 * e + 1]);
      const float lo = __uint_as_float(z[e] << 16), hi = __uint_as_float(z[e] & 0xFFFF0000u);
      s1 += lo + hi; s2 = fmaf(lo, lo, fmaf(hi, hi, s2));
    }
    asm volatile("{.reg .pred p; setp.ne.u32 p, %5, 0; @p st.global.v4.u32 [%0], {%1,%2,%3,%4};}"
                 :: "l"(g_xa + r * DM + c0 + i * 128), "r"(z[0]), "r"(z[1]), "r"(z[2]), "r"(z[3]), "r"((uint32_t)(i * 16 + q < 20)) : "memory");
  }
#pragma unroll
  for (int o = 1; o < 16; o <<= 1) { s1 += __shfl_xor_sync(0xffffffffu, s1, o); s2 += __shfl_xor_sync(0xffffffffu, s2, o); }
  asm volatile("{.reg .pred p; setp.ne.u32 p, %3, 0; @p red.relaxed.gpu.global.add.v2.f32 [%0], {%1,%2};}"
               :: "l"(&sy->rstat[r]), "f"(s1), "f"(s2), "r"((uint32_t)(q == 0)) : "memory");
  bar_sync(15, 256);
  if (ct == 0) { red_release(&sy->pro[1 + rt - RT0]); if (rt == 15) XT(128 + (blockIdx.x & 31), 0); }
  __syncwarp();
}

__global__ void __cluster_dims__(3, 1, 1) __launch_bounds__(384, 1)
chain_kernel(const __grid_constant__ CUtensorMap mq, const __grid_constant__ CUtensorMap mk, const __grid_constant__ CUtensorMap mv,
             const __grid_constant__ CUtensorMap mo, const __grid_constant__ CUtensorMap mx, const bf16* __restrict__ mem0, const bf16* __restrict__ xin, uint32_t zero, int layer
             , const __grid_constant__ CUtensorMap moa, const __grid_constant__ CUtensorMap mwo
             ) {
  using namespace ch;
  extern __shared__ __align__(1024) uint8_t smraw[];
  const uint32_t sb = smem_u32(smraw);
  const int tid = threadIdx.x;
  const int wg = __shfl_sync(0xffffffffu, tid >> 7, 0), w = __shfl_sync(0xffffffffu, (tid >> 5) & 3, 0);
  int h, j;
  asm("mov.u32 %0, %%clusterid.x;" : "=r"(h));
  asm("mov.u32 %0, %%cluster_ctarank;" : "=r"(j));
  h = __shfl_sync(0xffffffffu, h, 0); j = __shfl_sync(0xffffffffu, j, 0);
  const int T0 = j == 0 ? 0 : (j == 1 ? 14 : 27), NT = j == 0 ? 14 : 13;
  const uint32_t PD = PD_, XD = XD_, X1D = X1D_;
  constexpr uint32_t CS = 0, UP = 0, DMIN = 0, FL = 0, SD = 0;

  if (tid == 0) {
    mbar_init(sb + BAR_W1, 1); mbar_init(sb + BAR_W2, 1); mbar_init(sb + BAR_X0, 1); mbar_init(sb + BAR_X1, 1);
    mbar_init(sb + BAR_S, 6); mbar_init(sb + BAR_O, 1); mbar_init(sb + BAR_WK, 1); mbar_init(sb + BAR_XF, 12);
    for (int i = 0; i < 14; i++) mbar_init(sb + PB + i * 8, 1);
    sts64(sb + WMX, 0, 0);
    asm volatile("fence.mbarrier_init.release.cluster;" ::: "memory");
    mbar_expect(sb + BAR_W2, 81920);
    mbar_expect(sb + BAR_S, 1280); mbar_expect(sb + BAR_O, 2048);
  }
  asm volatile("griddepcontrol.launch_dependents;");
  GT(0, 0);
  __syncthreads();
  asm volatile("barrier.cluster.arrive.relaxed.aligned;" ::: "memory");
  asm volatile("barrier.cluster.wait.aligned;" ::: "memory");
  if (tid == 0) PT(0, 0);
  const char* arb = (const char*)g_ar;
  const uint32_t xdesc = desc_lo(sb + XB, 16);

  if (wg < 2) {
    asm volatile("setmaxnreg.inc.sync.aligned.u32 208;");
    chain_prepare(xin);
    bar_arrive(9, 352);
    uint32_t W[160];
    load_weights(W, sb, wg, w, j, layer);
    float inv_sc = 1.0f;
    if (wg == 0) {
      const uint32_t lane = lane_id();
      code_pad<PAD0>(zero);
      mbar_wait_long(sb + BAR_X0, 0);
      if (tid == 0) PT(0, 12);
      if (LSH == 1) bar_sync(8, 256);
      if (!LSH) {
        tokens_finish<false>(sb, W, xdesc, w, lane, 0, &mx);
        if (tid == 0) PT(0, 13);
        if (!KS2) bar_arrive(8, 256);
        arrange_wq(sb, 0, w, layer);
      }
#pragma unroll 1
      for (int s = LSH ? -1 : 0; s < NSEG; s++) {
        float sc = 1.0f;
        if (!LSH || s >= 0) {
        uint32_t A0[2];
        {
          float q[4], k[4], v[4];
          const uint32_t ln = opq(lane), t16 = w * 512 + ln * 16;
          uint32_t f[NF][4], wq = sb + WQ + (WQR ? t16 : afrag_off(w, ln)), ba = sb + MEMB + ln * 16;
          proj_stage(f, wq);
          PIN(ba);
          proj_mem<0>(q, k, v, f, W, wq, ba, sb, w, s);
          const uint32_t qd = sb + QS + w * 256 + ln * 4;
          sts32(qd, pack_bf16(q[0] * inv_sc, q[1] * inv_sc)); sts32(qd + 128, pack_bf16(q[2] * inv_sc, q[3] * inv_sc));
          sts32(qd + 2048, pack_bf16(k[0] * inv_sc, k[1] * inv_sc)); sts32(qd + 2048 + 128, pack_bf16(k[2] * inv_sc, k[3] * inv_sc));
          sts128(sb + EX + t16, __float_as_uint(k[0]), __float_as_uint(k[1]), __float_as_uint(k[2]), __float_as_uint(k[3]));
          E1(1, __float_as_uint(v[0]) ^ __float_as_uint(q[0]));
          uint32_t qa = sb + QS + ((ln >> 3) & 1) * 1024 + ((ln >> 4) * 8 + (ln & 7)) * 16;
          PIN(qa);
          TS(0);
          bar_sync(2, 384);
          if (w == 3 && s < NSEG - 1) {
            uint32_t b0[4], b1[4], c0[4], c1[4];
            const uint32_t ka = sb + KP + ln * 16;
            ldsm4t(b0, ka); ldsm4t(c0, ka + 1024); ldsm4t(b1, ka + 512); ldsm4t(c1, ka + 1536);
#pragma unroll
            for (int i = 0; i < 4; i++) { b0[i] = add_bf16x2(b0[i], c0[i]); b1[i] = add_bf16x2(b1[i], c1[i]); }
            score_tile(sb, qa, b0, b1, Peers(sb, j), SX + j * 640 + ln * 4, ln);
          }
          uint32_t e[4];
          lds128(e, sb + EX + 2048 + t16);
          A0[0] = pack_bf16((v[0] + __uint_as_float(e[0])) * inv_sc, (v[1] + __uint_as_float(e[1])) * inv_sc);
          A0[1] = pack_bf16((v[2] + __uint_as_float(e[2])) * inv_sc, (v[3] + __uint_as_float(e[3])) * inv_sc);
          const uint32_t slab = slab_off(VT, w, ln);
          sts32(sb + slab, A0[0]); sts32(sb + slab + 640, A0[1]);
          bar_arrive(12, 384);
        }
        if (s == NSEG - 1) break;
        {
          const uint32_t ln = opq(lane);
          const uint32_t va = sb + VT + (16 * w + (ln & 15)) * 80 + 16 + (ln >> 4) * 16;
          const uint32_t sa = sb + SX + ln * 4, off = OB + w * 256 + ln * 4;
          const Peers pe(sb, j);
          uint32_t f1[4], f2[4];
          ldsm4(f1, va); ldsm4(f2, va + 32);
          TSX(TS(1));
          mbar_wait(sb + BAR_S, s & 1);
          TS(2);
          uint32_t u[3][5];
#pragma unroll
          for (int i = 0; i < 15; i++) u[i / 5][i % 5] = lds32(sa + (i % 5) * 128 + (i / 5) * 640);
          E1(2, u[0][0]);
          sched_fence(zero);
          uint32_t hs[5];
#pragma unroll
          for (int i = 0; i < 5; i++) hs[i] = hadd2(hadd2(u[0][i], u[1][i]), u[2][i]);
          uint32_t m2 = hmax2(hmax2(hmax2(hs[0], hs[1]), hmax2(hs[2], hs[3])), hs[4]);
          asm volatile("bar.arrive 13, 384;" : "+r"(m2) :: "memory");
          m2 = hmax2(m2, __byte_perm(m2, 0, 0x1032));
          m2 = hmax2(m2, __shfl_xor_sync(0xffffffffu, m2, 1));
          m2 = hmax2(m2, __shfl_xor_sync(0xffffffffu, m2, 2));
          TSX(TSD(3, m2));
          const float m4 = -4.0f * __low2float(*reinterpret_cast<__half2*>(&m2));
          uint32_t P[5];
#pragma unroll
          for (int i = 0; i < 5; i++) {
            const float2 x = __half22float2(*reinterpret_cast<__half2*>(&hs[i]));
            P[i] = pack_bf16(ex2(fmaf(x.x, 4.0f, m4)), ex2(fmaf(x.y, 4.0f, m4)));
          }
          float o[4] = {0.f, 0.f, 0.f, 0.f}, o2[4] = {0.f, 0.f, 0.f, 0.f}, o3[4] = {0.f, 0.f, 0.f, 0.f};
          mma16816(o2, f1, P[1], P[2]); mma1688(o, A0[0], A0[1], P[0]); mma16816(o3, f2, P[3], P[4]);
          const uint32_t w0 = pack_bf16((o[0] + o2[0]) + o3[0], (o[1] + o2[1]) + o3[1]), w1 = pack_bf16((o[2] + o2[2]) + o3[2], (o[3] + o2[3]) + o3[3]);
#pragma unroll
          for (int r = 0; r < 2; r++) { st_async32(pe.a[r] + off + (2 - r) * 1024, w0, pe.a[r] + BAR_O); st_async32(pe.a[r] + off + (2 - r) * 1024 + 128, w1, pe.a[r] + BAR_O); }
          E1(3, w0 ^ w1);
          sts32(sb + off, w0); sts32(sb + off + 128, w1);
          if (w == 3) {
            float z[4] = {0.f, 0.f, 0.f, 0.f}, z2[4] = {0.f, 0.f, 0.f, 0.f};
            const uint32_t one[4] = {0x3F803F80u, 0x3F803F80u, 0x3F803F80u, 0x3F803F80u};
            mma1688(z, one[0], one[1], P[0]); mma16816(z2, one, P[1], P[2]); mma16816(z, one, P[3], P[4]);
            if (ln < 4) sts64(sb + INV + ln * 8, __float_as_uint(rcp(z[0] + z2[0])), __float_as_uint(rcp(z[1] + z2[1])));
          }
          TS(4);
        }
        if (12 + w < NT) {
          const uint32_t ln = opq(lane);
          const char* pr = arb + ar_tile_off(T0 + 12 + w) + ln * 4; const char* px = arb + ar_extra_off(T0 + 12 + w);
          PINL(pr);
          wo_tile_smem<true>(sb, sb + WOF + (4 + w) * 6144 + ln * 16, sb + OB + ln * 16, s & 1, pr, px, ln == 31, sc);
        } else {
          bar_sync(9, 384);
          sc = __uint_as_float(lds32(sb + MX + 16));
          if (w == 3 && lane == 0) {
            mbar_expect(sb + BAR_S, 1280);
            if (!KS2 && !X1E && j == 1 && s + 2 < NSEG) {
              mbar_wait(sb + BAR_XF, s & 1);
              tma3d_mc(sb + XB + 20480, &mx, 0, (s + 2) * SEG, 5, sb + BAR_X1, 7);
            }
            mbar_wait(sb + BAR_O, s & 1);
            mbar_expect(sb + BAR_O, 2048);
          }
          __syncwarp();
        }
        TSX(TS(5));
        if (w == 1) SS(0);
        mbar_wait(sb + BAR_X0, (s + 1) & 1);
        if (w == 1) SS(1);
        bar_sync(4, 384);
        if (w == 1) SS(2);
        arb += AR_STEP_BYTES;
        }
        tokens_finish<true>(sb, W, xdesc, w, lane, s);
        TS(6);
        if (LSH && s < 0) {
          if (tid == 0) PT(0, 13);
          arrange_wq(sb, 0, w, layer);
        }
        inv_sc = __uint_as_float(0x7F000000u - __float_as_uint(sc));
      }
    } else {
      const uint32_t lane = lane_id();
      static_assert(!X0E && !KS2, "prologue");
      code_pad<PAD1>(zero);
#pragma unroll 1
      for (int pass = 0; pass < (LSH ? 1 : 2); pass++) {
        mbar_wait_long(sb + BAR_X1, pass);
        if (pass) bar_sync(8, 256);
        tokens_partial<0>(sb, PK, W, xdesc, w, lane);
        if (pass) break;
        mbar_wait(sb + BAR_X1, 0);
        tokens_partial<0>(sb, QS, W + 80, xdesc, w, lane);
        bar_sync(8, 256);
      }
      if (LSH) {
        if (w == 3 && lane == 0) { mbar_expect(sb + BAR_X1, 20480); tma3d(sb + XB + 20480, &mx, 0, SEG, 5, sb + BAR_X1); }
        __syncwarp();
      } else {
        if (tid == 128) PT(0, 14);
        arrange_wq(sb, 1, w, layer);
      }
#pragma unroll 1
      for (int s = LSH ? -1 : 0; s < NSEG; s++) {
        float sc = 1.0f;
        if (!LSH || s >= 0) {
        {
          float q[4], k[4], v[4];
          const uint32_t ln = opq(lane), t16 = w * 512 + ln * 16;
          uint32_t f[NF][4], wq = sb + WQ + 40960 + (WQR ? t16 : afrag_off(w, ln)), ba = sb + MEMB + 5120 + ln * 16;
          proj_stage(f, wq);
          PIN(ba);
          proj_mem<1>(q, k, v, f, W, wq, ba, sb, w, s);
          const uint32_t qd = sb + QS + 1024 + w * 256 + ln * 4;
          sts32(qd, pack_bf16(q[0] * inv_sc, q[1] * inv_sc)); sts32(qd + 128, pack_bf16(q[2] * inv_sc, q[3] * inv_sc));
          sts32(qd + 2048, pack_bf16(k[0] * inv_sc, k[1] * inv_sc)); sts32(qd + 2048 + 128, pack_bf16(k[2] * inv_sc, k[3] * inv_sc));
          sts128(sb + EX + 2048 + t16, __float_as_uint(v[0]), __float_as_uint(v[1]), __float_as_uint(v[2]), __float_as_uint(v[3]));
          TSX(TS(0));
          bar_sync(2, 384);
          uint32_t e[4];
          lds128(e, sb + EX + t16);
          const uint32_t slab = slab_off(KT, w, ln);
          sts32(sb + slab, pack_bf16((k[0] + __uint_as_float(e[0])) * inv_sc, (k[1] + __uint_as_float(e[1])) * inv_sc));
          sts32(sb + slab + 640, pack_bf16((k[2] + __uint_as_float(e[2])) * inv_sc, (k[3] + __uint_as_float(e[3])) * inv_sc));
        }
        if (s == NSEG - 1) { bar_arrive(12, 384); break; }
        if (w == 1) SS(3);
        if (KS2) mbar_wait(sb + BAR_X1, (s + 1) & 1);
        if (w == 1) SS(4);
        if (VL) {
          bar_arrive(12, 384); bar_arrive(13, 384);
          bar_sync(9, 384);
          tokens_partial<3>(sb, QS, W + 80, xdesc, w, lane);
        } else {
          bar_sync(5, 288);
          TSX(TS(1));
          tokens_partial<1>(sb, QS, W + 80, xdesc, w, lane);
        }
        if (!KS2 && X1E && j == 1 && w == 3 && s + 2 < NSEG) {
          if (opq(lane) == 0) {
            mbar_wait(sb + BAR_XF, s & 1);
            tma3d_mc(sb + XB + 20480, &mx, 0, (s + 2) * SEG, 5, sb + BAR_X1, 7);
          }
          __syncwarp();
        }
        TS(2);
        {
          const uint32_t ln = opq(lane);
          const char* pr = arb + ar_tile_off(T0 + 8 + w) + ln * 4; const char* px = arb + ar_extra_off(T0 + 8 + w);
          PINL(pr);
          wo_tile_smem<!VL>(sb, sb + WOF + w * 6144 + ln * 16, sb + OB + ln * 16, s & 1, pr, px, ln == 31, sc);
        }
        if (KS2) bar_sync(4, 384);
        else if (KORD) {
          if (s + 2 < NSEG) mbar_wait(sb + BAR_X1, s & 1);
          bar_sync(4, 384);
        } else {
          bar_arrive(4, 384);
        }
        arb += AR_STEP_BYTES;
        }
        if (!KS2 && !KORD) {
          if (s + 2 < NSEG) { if (LSH && s < 0) mbar_wait_long(sb + BAR_X1, 1); else mbar_wait(sb + BAR_X1, s & 1); }
          bar_sync(6, 256);
        }
        tokens_partial<2>(sb, PK, W, xdesc, w, lane);
        if (LSH && s < 0) {
          if (tid == 128) PT(0, 14);
          arrange_wq(sb, 1, w, layer);
        }
        if (X0E && j == 0 && w == 2 && s + 2 < NSEG) {
          if (opq(lane) == 0) {
            mbar_wait(sb + BAR_XF, (s + 1) & 1);
            const uint32_t t9 = clk32();
            while (clk32() - t9 < X0D_) {}
            tma3d_mc(sb + XB, &mx, 0, (s + 2) * SEG, 0, sb + BAR_X0, 7);
          }
          __syncwarp();
        }
        if (KS2 && j == 1 && w == 0 && s + 2 < NSEG) {
          if (opq(lane) == 0) {
            mbar_wait(sb + BAR_XF, s & 1);
            tma3d_mc(sb + XB + 20480, &mx, 0, (s + 2) * SEG, 5, sb + BAR_X1, 7);
          }
          __syncwarp();
        }
        TS(4);
        inv_sc = __uint_as_float(0x7F000000u - __float_as_uint(sc));
      }
    }
    asm volatile("barrier.cluster.arrive.relaxed.aligned;" ::: "memory");
    tail_sum(sb, &g_sync[layer], xin, wg, w, layer);
  } else {
    asm volatile("setmaxnreg.dec.sync.aligned.u32 88;");
    const uint32_t lane = lane_id();
    uint32_t W[44];
    if (tid - 256 < 80) asm volatile("prefetch.global.L2 [%0];" :: "l"(mem0 + (tid - 256) * 64) : "memory");
    if (w == 3) {
      if (layer && LNF == 1) bar_sync(10, 64);
      const int win = layer ? PWIN1 : PWIN;
#pragma unroll
      for (int part = 0; part < 2; part++) {
        if (lane == 0) {
#pragma unroll
          for (int i = part ? 2 : 0; i < (part ? 14 : 2); i++) {
            const uint32_t bar = sb + PB + i * 8;
            if (i >= win) mbar_wait_long(bar - win * 8, 0);
            if (i == 12) mbar_wait_long(sb + BAR_W1, 0);
            if (i < 5 || (i >= 7 && i < 12)) {
              mbar_expect(bar, 16384);
              if (i < 5) tma2d(sb + 81920 + i * 16384, &mv, h * DH + 64 * j, i * 128, bar);
              else tma2d(sb + (i - 7) * 16384, &mk, h * DH + 64 * j, (i - 7) * 128, bar);
            } else {
              const int bx = i < 7 ? i - 4 : (i - 12) * 3;
              mbar_expect(bar, 24576);
              tma2d(bx < 3 ? sb + WOSTAGE + bx * 24576 : sb + WOF, &mo, T0 * 16 + 64 * bx, h * DH, bar);
            }
          }
        }
        __syncwarp();
        if (part == 0 && layer && LNF == 2) bar_sync(10, 64);
      }
      if (lane == 0) {
        mbar_wait_long(sb + BAR_WK, 0);
        for (int i = 0; i < 2; i++) tma2d(sb + WQ + i * 16384, &mq, h * DH + 64 * j, i * 128, sb + BAR_W2);
      }
      __syncwarp();
    } else {
      chain_prepare(xin);
      for (int i = blockIdx.x * 96 + tid - 256; i < (NSEG - 1) * 24 * 32; i += 96 * 96) ((uint4*)g_ar)[(i >> 5) * 64 + (i & 31)] = make_uint4(0, 0, 0, 0);
      bar_sync(9, 352);
    }
    PT(0, 1);
    if (w == 0) {
      if (lane == 0) {
        if (layer) sts32(sb + MX + 24, __ldcg(&g_kw));
        red_release(&g_sync[layer].pro[0]);
      }
      PT(0, 2);
      __syncwarp();
      if (layer && LNF) bar_arrive(10, 64);
    }
    if (!(PSPL && layer) && tid == 256) spin_count(&g_sync[layer].pro[0], 96);
    __syncwarp();
    PT(0, 3);
    mbar_wait_long(sb + PB + 5 * 8, 0); mbar_wait_long(sb + PB + 12 * 8, 0);
    PT(0, 4);
    {
      const int i = lane >> 3, r = lane & 7;
      uint32_t m = 0;
#pragma unroll
      for (int kk = 0; kk < 12; kk++)
#pragma unroll
        for (int tt = 0; tt < 2; tt++) {
          const int tl = 2 * w + tt;
          const uint32_t src = sb + WOSTAGE + (tl >> 2) * 24576 + (((kk + 4 * j) % 12) * 16 + (i >> 1) * 8 + r) * 128 + ((((tl & 3) * 2 + (i & 1)) ^ r) << 4);
          const int q = kk * 2 + tt;
          if (q >= 13) { ldsm4t_p(&W[(q - 13) * 4], src); m = mag4(m, &W[(q - 13) * 4]); }
          else { uint32_t f[4]; ldsm4t(f, src); sts128(sb + (q < 12 ? WOF2 + (w * 12 + q) * 512 : WOF3 + w * 512) + lane * 16, f[0], f[1], f[2], f[3]); m = mag4(m, f); }
        }
      publish_max(sb + WMX + 4, m);
    }
    bar_sync(7, 384);
    PT(0, 5);
    if (tid == 256 && !layer) {
      const float2 mm = lds64f(sb + WMX);
      asm volatile("st.relaxed.gpu.global.u32 [%0], %1;" :: "l"(&g_sync[layer].wmax[blockIdx.x]), "r"(0x10000u | (__float_as_uint(mm.x) >> 7 << 8) | (__float_as_uint(mm.y) >> 7)) : "memory");
    }
    uint32_t m0[3][8];
#pragma unroll
    for (int i = 0; i < 24; i++) m0[i >> 3][i & 7] = __ldg((const uint32_t*)(mem0 + (i & 7) * DM) + min(tid - 256 + (i >> 3) * 128, DM / 2 - 1));
    if (tid == 352) {
      if (PSPL && layer) spin_count(&g_sync[layer].pro[0], 96);
      if (XFEN == 0) asm volatile("fence.proxy.async;" ::: "memory");
      if (XFEN == 1) asm volatile("fence.proxy.async.global;" ::: "memory");
      mbar_expect(sb + BAR_X1, 20480); tma3d(sb + XB + 20480, &mx, 0, 0, 5, sb + BAR_X1);
      mbar_expect(sb + BAR_X0, 20480); tma3d(sb + XB, &mx, 0, 0, 0, sb + BAR_X0);
      for (int i = 2; i < 5; i++) tma2d(sb + WQ + i * 16384, &mq, h * DH + 64 * j, i * 128, sb + BAR_W2);
    }
    __syncwarp();
    bar_sync(7, 384);
    PT(0, 6);
    uint32_t wv[3];
    if (w == 0 && !layer)
#pragma unroll
      for (int i = 0; i < 3; i++) asm volatile("ld.relaxed.gpu.global.u32 %0, [%1];" : "=r"(wv[i]) : "l"(&g_sync[layer].wmax[lane + i * 32]) : "memory");
    {
      int em;
      uint32_t m = 0;
#pragma unroll
      for (int i = 0; i < 3; i++) {
        const int p = tid - 256 + i * 128;
        if (p < DM / 2) {
          uint32_t lo[4], hi[4];
#pragma unroll
          for (int q = 0; q < 4; q++) { lo[q] = __byte_perm(m0[i][2 * q], m0[i][2 * q + 1], 0x5410); hi[q] = __byte_perm(m0[i][2 * q], m0[i][2 * q + 1], 0x7632); }
          sts128(sb + MEMB + p * 32, lo[0], lo[1], lo[2], lo[3]); sts128(sb + MEMB + p * 32 + 16, hi[0], hi[1], hi[2], hi[3]);
        }
#pragma unroll
        for (int q = 0; q < 8; q++) m = __vmaxu2(m, m0[i][q] & 0x7FFF7FFFu);
      }
      em = __reduce_max_sync(0xffffffffu, (int)(max(m & 0xFFFFu, m >> 16) >> 7) - 126);
      if (lane == 0) sts32(sb + MX + w * 4, em);
    }
    PT(0, 7);
    bar_arrive(1, 384);
    bar_sync(3, 384);
    if (w == 0 && !layer) {
      for (int n = 0; n < 4000000 && !__all_sync(0xffffffffu, (wv[0] & wv[1] & wv[2]) >> 16); n++) {
#pragma unroll
        for (int i = 0; i < 3; i++) asm volatile("ld.relaxed.gpu.global.u32 %0, [%1];" : "=r"(wv[i]) : "l"(&g_sync[layer].wmax[lane + i * 32]) : "memory");
      }
      const int ev = __reduce_max_sync(0xffffffffu, max(max(wv[0] >> 8 & 255, wv[1] >> 8 & 255), wv[2] >> 8 & 255));
      const int eo = __reduce_max_sync(0xffffffffu, max(max(wv[0] & 255, wv[1] & 255), wv[2] & 255));
      if (lane == 0) {
        sts32(sb + MX + 24, 245 - ev - eo);
        if (blockIdx.x == 0) g_kw = 245 - ev - eo;
      }
      __syncwarp();
    }
    int dly = PD;
    PT(0, 8);
    for (int s = 0; s < NSEG; s++) {
      const uint32_t t0 = clk32();
      TS(0);
      {
        uint32_t b0[4], b1[4];
        const uint32_t ln = opq(lane);
        const uint32_t ka = sb + KT + ln * 80 + (1 + w) * 16;
        ldsm4t(b0, ka); ldsm4t(b1, ka + 2560);
        if (w == 0 && ln == 0 && s + 1 < NSEG) {
          if (!X0E && j == 0) {
            mbar_wait(sb + BAR_XF, s & 1);
            while (clk32() - t0 < XD) {}
            tma3d_mc(sb + XB, &mx, 0, (s + 1) * SEG, 0, sb + BAR_X0, 7);
          }
          if (s + 2 < NSEG - 1 && !(FL & 2)) asm volatile("prefetch.global.L2 [%0];" :: "l"(arb + 2 * AR_STEP_BYTES + ar_line_off(h * 3 + j)) : "memory");
          if (PFW && layer == 0 && s >= PFW && s < PFW + 10) tma2d_prefetch(s & 1 ? &mk : &mv, h * DH + 64 * j, ((s - PFW) >> 1) * 128);
          if (j == 2 && h == (s & 31) && s + 3 < NSEG) { tma3d_prefetch(&mx, 0, (s + 3) * SEG, 0); tma3d_prefetch(&mx, 0, (s + 3) * SEG, 5); }
        }
        __syncwarp();
        uint32_t qa = sb + QS + ((ln >> 3) & 1) * 1024 + ((ln >> 4) * 8 + (ln & 7)) * 16, off = SX + j * 640 + (1 + w) * 128 + ln * 4;
        PIN(qa); PIN(off);
        bar_sync(2, 384);
        if (s == NSEG - 1) break;
        score_tile(sb, qa, b0, b1, Peers(sb, j), off, ln);
        bar_sync(12, 384);
        if (SD) bar_sync(13, 384);
        if (w == 1 && ln == 0 && !(FL & 1)) {
          store_slabs(sb, s, h, j);
        }

        __syncwarp();
      }
      if (w == 0) {
        uint32_t v[4]; lds128(v, sb + MX);
        const int kw = lds32(sb + MX + 24);
        const int em = max(max(max((int)v[0], (int)v[1]), max((int)v[2], (int)v[3])), 1);
        const int e = min(max(kw - em, -120), 120);
        if (opq(lane) == 0) { sts32(sb + MX + 16, (uint32_t)(e + 127) << 23); sts32(sb + MX + 20, 0u); }
      }
      if (!SD) bar_sync(13, 384);
      uint32_t tref;
      {
        float c0[4] = {0.f, 0.f, 0.f, 0.f}, c1[4] = {0.f, 0.f, 0.f, 0.f}, d0[4] = {0.f, 0.f, 0.f, 0.f}, d1[4] = {0.f, 0.f, 0.f, 0.f};
        uint32_t f[4][4], b[2][4];
        const uint32_t ln = opq(lane);
        const uint32_t fa = sb + WOF2 + w * 6144 + ln * 16, ob = sb + OB + ln * 16;
#pragma unroll
        for (int i = 0; i < 4; i++) lds128(f[i], fa + i * 512);
        if (w == 1) SS(5);
        asm volatile("cp.async.bulk.wait_group.read 0;" ::: "memory");
        if (w == 1) SS(6);
        bar_sync(9, 384);
        ldsm4t(b[0], ob); ldsm4t(b[1], ob + 512);
        mma16816(c0, f[0], b[0][0], b[0][1]); mma16816(c1, f[1], b[0][0], b[0][1]);
        lds128(f[0], fa + 2048); lds128(f[1], fa + 2560);
        mma16816(d0, f[2], b[0][2], b[0][3]); mma16816(d1, f[3], b[0][2], b[0][3]);
        lds128(f[2], fa + 3072); lds128(f[3], fa + 3584);
        mma16816(c0, f[0], b[1][0], b[1][1]); mma16816(c1, f[1], b[1][0], b[1][1]);
        mma16816(d0, f[2], b[1][2], b[1][3]); mma16816(d1, f[3], b[1][2], b[1][3]);
#pragma unroll
        for (int i = 0; i < 4; i++) lds128(f[i], fa + (8 + i) * 512);
        mbar_wait(sb + BAR_O, s & 1);
        ldsm4t(b[0], ob + 1024);
        E1(4, b[0][0]);
        mma16816(c0, f[0], b[0][0], b[0][1]); mma16816(c1, f[1], b[0][0], b[0][1]);
        mma16816(d0, f[2], b[0][2], b[0][3]); mma16816(d1, f[3], b[0][2], b[0][3]);
        ldsm4t(b[0], ob + 1536); lds128(f[0], sb + WOF3 + w * 512 + ln * 16); ldsm4t(f[1], ob + 2048); ldsm4t(f[2], ob + 2560);
        float2 iv = lds64f(sb + INV + (ln & 3) * 8);
        const float sc = __uint_as_float(lds32(sb + MX + 16));
        sched_fence(zero);
        mma16816(c1, &W[0], b[0][0], b[0][1]); mma16816(d0, &W[4], b[0][2], b[0][3]); mma16816(d1, &W[8], b[0][2], b[0][3]);
        mma16816(c0, f[0], b[0][0], b[0][1]);
        const char* pr = arb + ar_tile_off(T0 + 2 * w) + ln * 4;
        PINL(pr);
        iv.x *= sc; iv.y *= sc;
        mma16816(c1, &W[16], f[1][0], f[1][1]); mma16816(d0, &W[20], f[1][2], f[1][3]); mma16816(d1, &W[24], f[1][2], f[1][3]);
        mma16816(c0, &W[12], f[1][0], f[1][1]);
        mma16816(c1, &W[32], f[2][0], f[2][1]); mma16816(d0, &W[36], f[2][2], f[2][3]); mma16816(d1, &W[40], f[2][2], f[2][3]);
        mma16816(c0, &W[28], f[2][0], f[2][1]);
        const uint32_t w2 = pack_f16((c1[0] + d1[0]) * iv.x, (c1[1] + d1[1]) * iv.y), w3 = pack_f16((c1[2] + d1[2]) * iv.x, (c1[3] + d1[3]) * iv.y);
        wo_red(pr + ((T0 & 1) ? 768 : 256), w2, w3, ln == 31);
        const uint32_t w0 = pack_f16((c0[0] + d0[0]) * iv.x, (c0[1] + d0[1]) * iv.y), w1 = pack_f16((c0[2] + d0[2]) * iv.x, (c0[3] + d0[3]) * iv.y);
        E1(5, w0 ^ w2);
        wo_red(pr, w0, w1, ln == 31);
        wo_red_extra_p(arb + ar_extra_off(T0 + 2 * w + 1), w2, w3, ln);
        wo_red_extra_p(arb + ar_extra_off(T0 + 2 * w), w0, w1, ln);
        if (TSYNC) bar_sync(4, 384); else bar_arrive(4, 384);
        tref = clk32();
      }
      TSV(2, tref); TS(3);
      if (w == 1 && opq(lane) == 0) {
        asm volatile("cp.async.bulk.wait_group 0;" ::: "memory");
        publish_bulk<0>(&g_sync[layer].kv[s * NH + h]);
      }
      __syncwarp();
      {
        const uint32_t m = ar_read(arb, sb, w, lane, zero, tref, dly, s);
        dly = lds32(sb + MX + 20) ? dly + (int)UP : max(dly - (int)CS, (int)DMIN);
        if (w == 3) TSV(1, dly);
        const int em = __reduce_max_sync(0xffffffffu, (int)(max(m & 0xFFFFu, m >> 16) >> 10) - 13 + 127 - (int)(lds32(sb + MX + 16) >> 23));
        if (opq(lane) == 0) sts32(sb + MX + w * 4, em);
      }
      arb += AR_STEP_BYTES;
    }
    asm volatile("barrier.cluster.arrive.relaxed.aligned;" ::: "memory");
    if (w == 3) {
      if (lane == 0) {
        asm volatile("prefetch.tensormap [%0];" :: "l"(&mwo) : "memory"); asm volatile("prefetch.tensormap [%0];" :: "l"(&moa) : "memory");
        for (int i = 0; i < (int)tl::NST; i++) { mbar_init(sb + tl::FULL + i * 8, 1); mbar_init(sb + tl::EMPTY + i * 8, 8); }
        asm volatile("fence.mbarrier_init.release.cluster;" ::: "memory");
      }
      __syncwarp();
      bar_arrive(14, 288);
    }
    bar_sync(12, 384);
    if (LASTG) {
      bf16* kvp = g_kv + ((size_t)((NSEG - 1) * NH + h) * 2 * DH + 64 * j) * NKEY;
#pragma unroll
      for (int k = 0; k < 5; k++) {
        const int u = k * 128 + tid - 256;
        uint32_t v[4];
        lds128(v, sb + KT + u * 16);
        __stcg((uint4*)(kvp + (u < 320 ? u * 8 : DH * NKEY + (u - 320) * 8)), make_uint4(v[0], v[1], v[2], v[3]));
      }
      bar_sync(10, 128);
      if (tid == 256 + 32) {
        asm volatile("cp.async.bulk.wait_group 0;" ::: "memory");
        red_release(&g_sync[layer].kv[(NSEG - 1) * NH + h]);
        GT(0, 1);
        tail_load(sb, &g_sync[layer], &moa, &mwo, layer);
      }
      __syncwarp();
    } else if (tid == 256 + 32) {
      store_slabs(sb, NSEG - 1, h, j);
      asm volatile("cp.async.bulk.wait_group 0;" ::: "memory");
      publish_bulk<WFEN>(&g_sync[layer].kv[(NSEG - 1) * NH + h]);
    }
  }
  asm volatile("barrier.cluster.wait.aligned;" ::: "memory");
}

DEVI void bulk_load(uint32_t dst, const void* g, uint32_t bytes, uint32_t bar) {
  if (EVF & 2) asm volatile("cp.async.bulk.shared::cluster.global.mbarrier::complete_tx::bytes.L2::cache_hint [%0], [%1], %2, [%3], %4;" :: "r"(dst), "l"(g), "r"(bytes), "r"(bar), "l"(stream_policy()) : "memory");
  else asm volatile("cp.async.bulk.shared::cluster.global.mbarrier::complete_tx::bytes [%0], [%1], %2, [%3];" :: "r"(dst), "l"(g), "r"(bytes), "r"(bar) : "memory");
}
DEVI void bulk_load_plain(uint32_t dst, const void* g, uint32_t bytes, uint32_t bar) {
  asm volatile("cp.async.bulk.shared::cluster.global.mbarrier::complete_tx::bytes [%0], [%1], %2, [%3];" :: "r"(dst), "l"(g), "r"(bytes), "r"(bar) : "memory");
}
DEVI void tma3d_store(const CUtensorMap* m, uint32_t src, int c0, int c1, int c2) {
  if (EVF & 4) asm volatile("cp.async.bulk.tensor.3d.global.shared::cta.bulk_group.L2::cache_hint [%0, {%2, %3, %4}], [%1], %5;" :: "l"(m), "r"(src), "r"(c0), "r"(c1), "r"(c2), "l"(stream_policy()) : "memory");
  else asm volatile("cp.async.bulk.tensor.3d.global.shared::cta.bulk_group [%0, {%2, %3, %4}], [%1];" :: "l"(m), "r"(src), "r"(c0), "r"(c1), "r"(c2) : "memory");
}
namespace wk {
constexpr uint32_t STAGE = 40960, NST = 4, OST = NST * STAGE;
constexpr uint32_t MISC = OST + 49152;
constexpr uint32_t FULL = MISC, EMPTY = MISC + 32, TFULL = MISC + 64, TEMPTY = MISC + 80, TASK = MISC + 96;
constexpr uint32_t DONE = MISC + 104, FREE = MISC + 120, DTASK = MISC + 136, FIN = MISC + 144, DSLOT = MISC + 152;
constexpr uint32_t CGO = MISC + 160;
constexpr uint32_t LBAR = MISC + 168, TL = MISC + 176;
constexpr uint32_t SMEM = TL + 5136;
#define NP2 10
constexpr int NZ = 16, NP = NZ + 80 + NP2, NQ = 512;
#define S15 8
#define SPLITS rt < RT_SPLIT ? 1 : rt < 11 ? 2 : rt < 13 ? 4 : rt < 15 ? 8 : S15
__host__ __device__ constexpr int split(int rt) { return SPLITS; }
__host__ __device__ constexpr int count_w(int rt) { return rt < 0 ? 0 : 4 * split(rt) + count_w(rt - 1); }
constexpr int NW = count_w(15);
__host__ __device__ constexpr int first_slice(int rt) { return rt <= RT_SPLIT ? 0 : first_slice(rt - 1) + split(rt - 1); }
static_assert(first_slice(16) <= NSL, "slice buffer");
DEVI int slice_of(int rt) {
  constexpr int f9 = first_slice(9), f10 = first_slice(10), f11 = first_slice(11), f12 = first_slice(12), f13 = first_slice(13), f14 = first_slice(14), f15 = first_slice(15);
  return rt < 9 ? 0 : rt == 9 ? f9 : rt == 10 ? f10 : rt == 11 ? f11 : rt == 12 ? f12 : rt == 13 ? f13 : rt == 14 ? f14 : f15;
}
static_assert(RT_SPLIT >= 8, "slice_of");
enum { T_Q, T_W, T_P, T_END, T_G, T_F };
#define RG0 14
#define RG1 13
#define BKVZ (CTAIL ? 12 : 14)
#define PFB 0
#define WLD 1
#define FLATE 10
#define WGRID 0
#define PFRONT 0
#define PTAIL 0
#define WPRE 0
#define PFF (CTAIL ? 12 : 14)
#define PFACC 0
#define P2LATE 0
#define LAGK0 16
#define LAGK1 16
#define DEFW0 13
#define DEFW1 13
#define NWE0 0
#define NWE1 0
#define SLATE0 1
#define SLATE1 1
#define SLATE 1
#define FLAG 3
#define FWARM 0
#define SLEV 1
#define SLC 1
#define LFAST 1
#define SCOUT0 13
#define SCOUT1 13
#define NSCOUT 0
#define FVOL 1
#define FXT 10
#define FCGO 0
#define P1M 1
#define TMPF 1
#define ZPRE 1
#define CLQ 8
#define CLW 3
struct Task { int type, rt, a, b; };
DEVI int wtasks(int rt) { return 4 * split(rt); }
DEVI int lsplit(int rt) { return 31 - __clz(split(rt)); }
DEVI Task decode(int id) { return {id >> 24, (id >> 16) & 255, id & 255, (id >> 8) & 255}; }
struct __align__(16) TaskList { int n, tail0, late0, pad; uint32_t t[1280]; };
constexpr void add_w(TaskList& l, int rt, int i0 = 0, int i1 = 64) {
  for (int b = 0; b < split(rt); b++) for (int a = 0; a < 4; a++) if (b * 4 + a >= i0 && b * 4 + a < i1) l.t[l.n++] = (T_W << 24) | (rt << 16) | (b << 8) | a;
}
constexpr void add_f(TaskList& l, int rt, int i0 = 0, int i1 = 64) {
  if (rt >= 0 && split(rt) > 1) for (int a = 0; a < 4; a++) for (int b = 0; b < 128 / FROWS; b++)
    if (a * (128 / FROWS) + b >= i0 && a * (128 / FROWS) + b < i1) l.t[l.n++] = (T_F << 24) | (rt << 16) | (b << 8) | a;
}
constexpr TaskList make_list(int layer) {
  TaskList l = {};
  const int rg = layer == 0 ? RG0 : RG1, lagk = layer == 0 ? LAGK0 : LAGK1, defw = layer == 0 ? DEFW0 : DEFW1, nwe = layer == 0 ? NWE0 : NWE1;
  if (layer == 0) for (int i = NZ; i < (P2LATE ? NZ + 80 : NP) - PTAIL && i < NZ + PFRONT; i++) l.t[l.n++] = (T_P << 24) | i;
  for (int rt = 15; rt >= rg; rt--) for (int h = 0; h < NH; h++) l.t[l.n++] = (T_G << 24) | (rt << 16) | h;
  if (layer == 0) for (int i = NZ + PFRONT; i < (P2LATE ? NZ + 80 : NP) - PTAIL; i++) l.t[l.n++] = (T_P << 24) | i;
  for (int i = 0; i < NZ; i++) l.t[l.n++] = (T_P << 24) | i;
  if (layer == 0 && P2LATE) for (int i = NZ + 80; i < NP; i++) l.t[l.n++] = (T_P << 24) | i;
  for (int rt = 0; rt < 16; rt++) {
    if (rt == 15) l.tail0 = l.n;
    for (int h = 0; h < NH; h++) l.t[l.n++] = (T_Q << 24) | (rt << 16) | ((rt >= rg) << 8) | h;
    if (rt > 0 && rt - 1 < lagk && rt - 1 < defw) add_w(l, rt - 1);
    if (rt >= lagk && rt < defw) add_w(l, rt);
    if (rt == 14 && defw < 14) add_w(l, defw, 0, nwe);
    if (rt == (layer ? SCOUT1 : SCOUT0)) for (int i = 0; i < NSCOUT; i++) l.t[l.n++] = (T_END << 24) | 1;
    if (FWARM && rt - FLAG + 1 == RT_SPLIT) add_f(l, RT_SPLIT, 0, 1);
    if (rt - FLAG < FLATE) add_f(l, rt - FLAG, FWARM && rt - FLAG == RT_SPLIT ? 1 : 0);
  }
  if (layer == 0) for (int i = NP - PTAIL; i < NP; i++) l.t[l.n++] = (T_P << 24) | i;
  if (CTAIL) {
    l.late0 = 1 << 20;
    for (int rt = FLATE; rt < tl::RT0; rt++) add_f(l, rt);
    return l;
  }
  constexpr int W15E = 4 * S15 - 32;
  if (SLATE) add_w(l, 15, 0, W15E);
  if (SLATE && (layer ? SLATE1 : SLATE0) == 2) {
    l.late0 = l.n;
    add_w(l, 14); add_w(l, 15, W15E); add_f(l, 10); add_f(l, 11);
    for (int rt = 12; rt < 16; rt++) add_f(l, rt);
    return l;
  } else if (SLATE) {
    l.late0 = l.n;
    add_w(l, 13); add_w(l, 14); add_w(l, 15, W15E);
  } else {
    for (int rt = defw; rt < 16; rt++) add_w(l, rt, rt == defw && defw < 14 ? nwe : 0);
  }
  for (int rt = FLATE; rt < 16; rt++) add_f(l, rt);
  return l;
}
__device__ const TaskList d_tasks[2] = {make_list(0), make_list(1)};
__host__ __device__ constexpr uint32_t first_task(int layer, int b) {
  if (layer == 0 && PTAIL < NP - NZ) { if (b < PFRONT) return (T_P << 24) | (NZ + b); b -= PFRONT; }
  return (T_G << 24) | ((15 - (b >> 5)) << 16) | (b & 31);
}
constexpr int NLATE = SLATE && !CTAIL ? 96 : 0;
static_assert(!CTAIL || (first_slice(tl::RT0) == tl::SL0 && DEFW0 == tl::RT0 && DEFW1 == tl::RT0 && S15 == 8 && FROWS == 16 && BSL && SLC && LASTG), "tail of the recurrence kernel");
__host__ __device__ constexpr uint32_t late_task(int layer, int i) {
  if ((layer ? SLATE1 : SLATE0) == 2) return i < 64 ? (T_W << 24) | ((14 + (i >> 5)) << 16) | ((((i & 31) >> 2) + (i >> 5) * (S15 - 8)) << 8) | (i & 3)
                                                    : (T_F << 24) | ((6 + (i >> 4)) << 16) | ((i & 3) << 8) | ((i & 15) >> 2);
  return (T_W << 24) | ((13 + (i >> 5)) << 16) | ((((i & 31) >> 2) + (i >> 6) * (S15 - 8)) << 8) | (i & 3);
}
constexpr bool check_first() {
  for (int layer = 0; layer < 2; layer++) {
    const TaskList l = make_list(layer);
    for (int b = 0; b < 64; b++) if (l.t[b] != first_task(layer, b)) return false;
    for (int b = 0; b < NLATE; b++) if (l.t[l.late0 + b] != late_task(layer, b)) return false;
  }
  return true;
}
static_assert(check_first(), "first_task does not match the list");
}

DEVI void pass_stage(uint32_t sb, uint32_t it, int lane) {
  mbar_wait_long(sb + wk::FULL + (it % wk::NST) * 8, (it / wk::NST) & 1);
  if (lane == 0) mbar_arrive(sb + wk::EMPTY + (it % wk::NST) * 8);
}
#define AT(i, x)
template <int NT>
DEVI void attend(uint32_t sb, const uint32_t (&q)[48], int cw, int w, int lane, uint32_t itk, uint32_t itv, uint32_t mid, uint32_t nd) {
  using namespace wk;
  const int g = lane >> 2, t = lane & 3;
  AT(0, q[0]);
  float sc[NT][4];
#pragma unroll
  for (int i = 0; i < NT * 4; i++) sc[i >> 2][i & 3] = 0.f;
  const uint32_t ka = sb + (itk % NST) * STAGE + (w >> 1) * 15360 + lane * 80;
#pragma unroll
  for (int k2 = 0; k2 < 6; k2++) {
    uint32_t b[NT][4];
#pragma unroll
    for (int n = 0; n < NT; n++) ldsm4t(b[n], ka + k2 * 2560 + n * 16);
#pragma unroll
    for (int n = 0; n < NT; n++) mma16816(sc[n], &q[k2 * 8], b[n][0], b[n][1]);
#pragma unroll
    for (int n = 0; n < NT; n++) mma16816(sc[n], &q[k2 * 8 + 4], b[n][2], b[n][3]);
  }
  AT(1, __float_as_uint(sc[NT - 1][0]) ^ __float_as_uint(sc[0][0]));
  __syncwarp();
  if (lane == 0) mbar_arrive(sb + EMPTY + (itk % NST) * 8);
  const float cs = 0.07216878364870322f * 1.4426950408889634f;
  const int r0 = NMEM + (NT == 5 ? 16 : 0) + g;
  float m0 = -INFINITY, m1 = -INFINITY;
#pragma unroll
  for (int n = 0; n < NT; n++)
#pragma unroll
    for (int e = 0; e < 2; e++) {
      const int key = n * 8 + 2 * t + e;
      sc[n][e] = (n < NT - 2 || key <= r0) ? sc[n][e] * cs : -INFINITY; sc[n][2 + e] = (n < NT - 1 || key <= r0 + 8) ? sc[n][2 + e] * cs : -INFINITY;
      m0 = fmaxf(m0, sc[n][e]); m1 = fmaxf(m1, sc[n][2 + e]);
    }
  m0 = fmaxf(m0, __shfl_xor_sync(0xffffffffu, m0, 1)); m1 = fmaxf(m1, __shfl_xor_sync(0xffffffffu, m1, 1));
  m0 = fmaxf(m0, __shfl_xor_sync(0xffffffffu, m0, 2)); m1 = fmaxf(m1, __shfl_xor_sync(0xffffffffu, m1, 2));
  uint32_t P[2 * NT]; float s0 = 0.f, s1 = 0.f;
#pragma unroll
  for (int n = 0; n < NT; n++) {
    const float a = ex2(sc[n][0] - m0), b = ex2(sc[n][1] - m0), c = ex2(sc[n][2] - m1), e = ex2(sc[n][3] - m1);
    s0 += a + b; s1 += c + e; P[2 * n] = pack_bf16(a, b); P[2 * n + 1] = pack_bf16(c, e);
  }
  s0 += __shfl_xor_sync(0xffffffffu, s0, 1); s1 += __shfl_xor_sync(0xffffffffu, s1, 1);
  s0 += __shfl_xor_sync(0xffffffffu, s0, 2); s1 += __shfl_xor_sync(0xffffffffu, s1, 2);
  const float i0 = rcp(s0), i1 = rcp(s1);
  AT(2, __float_as_uint(i0) ^ __float_as_uint(i1));
  mbar_wait_long(sb + FREE + cw * 8, (nd & 1) ^ 1);
  AT(3, 0);
  if (mid != 0xFFFFFFFFu) pass_stage(sb, mid, lane);
  mbar_wait_long(sb + FULL + (itv % NST) * 8, (itv / NST) & 1);
  AT(4, 0);
  const uint32_t vb = sb + (itv % NST) * STAGE + (w >> 1) * 15360;
  const uint32_t va = vb + (lane & 7) * 80 + (lane >> 3) * 16, vc = vb + lane * 80 + 64;
  const uint32_t orow = w * 16 + (lane & 15), ob = sb + OST + cw * 24576 + orow * 128;
#pragma unroll
  for (int n8 = 0; n8 < 3; n8++) {
    uint32_t b[8][4], c[2][4];
    float o[8][4];
#pragma unroll
    for (int i = 0; i < 8; i++) { ldsm4(b[i], va + (n8 * 8 + i) * 640); o[i][0] = o[i][1] = o[i][2] = o[i][3] = 0.f; }
    if (NT == 5) { ldsm4(c[0], vc + n8 * 5120); ldsm4(c[1], vc + n8 * 5120 + 2560); }
#pragma unroll
    for (int i = 0; i < 8; i++) mma16816(o[i], &P[0], b[i][0], b[i][1]);
#pragma unroll
    for (int i = 0; i < 8; i++) { if (NT == 5) mma16816(o[i], &P[4], b[i][2], b[i][3]); else mma1688(o[i], P[4], P[5], b[i][2]); }
    if (NT == 5)
#pragma unroll
      for (int i = 0; i < 8; i++) mma1688(o[i], P[2 * NT - 2], P[2 * NT - 1], c[i >> 2][i & 3]);
#pragma unroll
    for (int i = 0; i < 4; i++)
      stsm4(ob + n8 * 8192 + (((i * 2 + (lane >> 4)) ^ (orow & 7)) << 4), pack_bf16(o[2 * i][0] * i0, o[2 * i][1] * i0), pack_bf16(o[2 * i][2] * i1, o[2 * i][3] * i1),
            pack_bf16(o[2 * i + 1][0] * i0, o[2 * i + 1][1] * i0), pack_bf16(o[2 * i + 1][2] * i1, o[2 * i + 1][3] * i1));
  }
  __syncwarp();
  AT(5, 0);
  if (lane == 0) mbar_arrive(sb + EMPTY + (itv % NST) * 8);
}

__global__ void __launch_bounds__(384, 1)
worker_kernel(int layer, Sync* sy, const bf16* __restrict__ xin, const bf16* __restrict__ wphi, const bf16* __restrict__ wo2,
              const __grid_constant__ CUtensorMap mx, const __grid_constant__ CUtensorMap mq, const __grid_constant__ CUtensorMap moa,
              const __grid_constant__ CUtensorMap mos, const __grid_constant__ CUtensorMap mwo, const __grid_constant__ CUtensorMap mxa,
              const __grid_constant__ CUtensorMap macc, const __grid_constant__ CUtensorMap mwb) {
  using namespace wk;
  extern __shared__ __align__(1024) uint8_t smraw[];
  const uint32_t sb = smem_u32(smraw);
  const int tid = threadIdx.x, lane = tid & 31;
  const int wg = __shfl_sync(0xffffffffu, tid >> 7, 0), w = __shfl_sync(0xffffffffu, (tid >> 5) & 3, 0);
  constexpr int WF = 0;
  if (!WLD) asm volatile("griddepcontrol.launch_dependents;");
  GT(1, 0);
  const int nstat = WGRID ? 0 : min(max((int)gridDim.x - (CTAIL ? 0 : 96), 0), 64);
  int idx0 = 0;
  const int nl = min((int)gridDim.x - nstat, NLATE);
  if (tid == 96 && (int)blockIdx.x >= nstat + nl) idx0 = atomicAdd(&sy->head, 1);
  int id0 = -1;
  uint32_t flag0 = 0;
  if (LFAST && tid == 0 && (int)blockIdx.x >= nstat && (int)blockIdx.x < nstat + nl) {
    if (TMPF) { asm volatile("prefetch.tensormap [%0];" :: "l"(&mwo) : "memory"); asm volatile("prefetch.tensormap [%0];" :: "l"(&moa) : "memory"); }
    id0 = late_task(layer, blockIdx.x - nstat);
    flag0 = ld_acquire(&sy->o[(id0 >> 16 & 255) * 16 + (id0 >> 8 & 255)]);
  }
  if (tid == 0) {
    sts64(sb + FIN, 0, 0);
    for (int i = 0; i < NST; i++) { mbar_init(sb + FULL + i * 8, 1); mbar_init(sb + EMPTY + i * 8, 8); }
    for (int i = 0; i < 2; i++) { mbar_init(sb + TFULL + i * 8, 1); mbar_init(sb + TEMPTY + i * 8, 9); mbar_init(sb + DONE + i * 8, 128); mbar_init(sb + FREE + i * 8, 1); }
    mbar_init(sb + CGO, 1); mbar_init(sb + LBAR, 1);
    asm volatile("fence.mbarrier_init.release.cluster;" ::: "memory");
    mbar_expect(sb + LBAR, sizeof(TaskList));
    bulk_load_plain(sb + TL, &d_tasks[layer], sizeof(TaskList), sb + LBAR);
  }
  uint32_t early = 0;
  if (wg == 0) {
    asm volatile("setmaxnreg.dec.sync.aligned.u32 40;");
    if (LFAST && w == 0) bar_arrive(0, 384); else bar_sync(0, 384);
    if (tid == 96) {
      uint32_t nres = 0;
      bool tail = false;
      int ntask = 0, tail0 = 0, late0 = 0;
      for (uint32_t nt = 0;; nt++) {
        mbar_wait_long(sb + TEMPTY + (nt & 1) * 8, ((nt >> 1) & 1) ^ 1);
        if (nt) mbar_wait_long(sb + CGO, (nt - 1) & 1);
        if (tail) for (int i = 0; i < 4000000 && (lds32(sb + FIN) < nres || lds32(sb + FIN + 4) < nres); i++) {}
        int id;
        if (nt == 0 && (int)blockIdx.x < nstat) id = first_task(layer, blockIdx.x);
        else if (nt == 0 && (int)blockIdx.x < nstat + nl) { id = late_task(layer, blockIdx.x - nstat); tail = true; }
        else {
          const int idx = nstat + (nt ? atomicAdd(&sy->head, 1) : idx0);
          if (!ntask) { mbar_wait_long(sb + LBAR, 0); ntask = lds32(sb + TL); tail0 = lds32(sb + TL + 4); late0 = lds32(sb + TL + 8); }
          const int e = !SLATE || idx < late0 ? idx : idx + nl;
          id = e < ntask ? lds32(sb + TL + 16 + e * 4) : T_END << 24;
          tail = idx >= tail0;
        }
        sts32(sb + TASK + (nt & 1) * 4, id);
        mbar_arrive(sb + TFULL + (nt & 1) * 8);
        if (WLD == 1 && (id >> 24) == T_F && (id >> 16 & 255) >= FLATE) asm volatile("griddepcontrol.launch_dependents;");
        if ((id >> 24) == T_END) {
          if (WLD) asm volatile("griddepcontrol.launch_dependents;");
          early = id & 1;
          break;
        }
        nres += (id >> 24) < T_P;
      }
    } else if (tid == 0) {
      uint32_t it = 0;
      bool have_xn = false, have_zero = false;
      if (TMPF && !LFAST && (int)blockIdx.x >= nstat) {
        asm volatile("prefetch.tensormap [%0];" :: "l"(&mwo) : "memory");
        asm volatile("prefetch.tensormap [%0];" :: "l"(&moa) : "memory");
      }
      if (!BSL && ZPRE && (int)blockIdx.x >= nstat) have_zero = ld_acquire(&sy->zeroed) >= NZ;
      for (uint32_t nt = 0;; nt++) {
        int id = id0;
        if (nt || id0 < 0) {
          mbar_wait_long(sb + TFULL + (nt & 1) * 8, (nt >> 1) & 1);
          id = lds32(sb + TASK + (nt & 1) * 4);
        }
        const Task tk = decode(id);
        if (nt == 0) WS(1, tk.type);
        mbar_arrive(sb + TEMPTY + (nt & 1) * 8);
        if (tk.type == T_END) {
          if (PFB && blockIdx.x < 128) {
            asm volatile("cp.async.bulk.prefetch.L2.global [%0], 19200;" :: "l"((const char*)g_wb1 + blockIdx.x * 19200) : "memory");
            asm volatile("cp.async.bulk.prefetch.L2.global [%0], 6400;" :: "l"((const char*)g_wb2 + blockIdx.x * 6400) : "memory");
          }
          early = id & 1;
          GT(1, 1); break;
        }
        if (tk.type == T_Q && tk.b) {
          for (int c = 0; c < 4; c++, it++) {
            const uint32_t st = it % NST, a = sb + st * STAGE, fb = sb + FULL + st * 8;
            if (!(c & 1)) {
              wait_count_t(&sy->kv[(tk.rt * 4 + c + 1) * NH + tk.a], 3, tk.rt == 15 && c == 2); fence_flag_to_bulk();
              if (LASTG && tk.rt == 15 && c == 2) asm volatile("fence.proxy.async.global;" ::: "memory");
            }
            if (c == 2) mbar_arrive(sb + CGO);
            mbar_wait_long(sb + EMPTY + st * 8, ((it / NST) & 1) ^ 1);
            mbar_expect(fb, 30720);
            const bf16* src = g_kv + ((size_t)((tk.rt * 4 + (c & 2)) * NH + tk.a) * 2 + (c & 1)) * DH * NKEY;
            bulk_load(a, src, 15360, fb);
            bulk_load(a + 15360, src + (size_t)NH * 2 * DH * NKEY, 15360, fb);
          }
        } else if (tk.type == T_G) {
          if (!have_xn) { spin_count(&sy->pro[0], 96); asm volatile("fence.proxy.async;" ::: "memory"); have_xn = true; }
          for (int c = 0; c < 10; c++, it++) {
            const uint32_t st = it % NST, a = sb + st * STAGE, fb = sb + FULL + st * 8;
            if (c == CLQ) mbar_arrive(sb + CGO);
            mbar_wait_long(sb + EMPTY + st * 8, ((it / NST) & 1) ^ 1);
            mbar_expect(fb, 40960);
            tma2d(a, &mx, c * 64, tk.rt * 128, fb);
            tma3d(a + 16384, &mq, 0, c * 64, tk.a * 3, fb);
          }
        } else if (tk.type == T_Q) {
          if (!have_xn) { spin_count(&sy->pro[0], 96); asm volatile("fence.proxy.async;" ::: "memory"); have_xn = true; }
          bool have_kv = false;
          for (int c = (WF & 2) ? 8 : 0; c < 14; c++, it++) {
            const uint32_t st = it % NST, a = sb + st * STAGE, fb = sb + FULL + st * 8;
            if (c == CLQ) mbar_arrive(sb + CGO);
            if (c >= 4 && !have_kv) {
              const uint32_t* fl = &sy->kv[(tk.rt * 4 + 3) * NH + tk.a];
              if (c == 10) wait_count(fl, 3);
              if (c == 10 || ld_acquire(fl) >= 3) { have_kv = true; fence_flag_to_bulk(); }
            }
            mbar_wait_long(sb + EMPTY + st * 8, ((it / NST) & 1) ^ 1);
            if (c < 10) {
              mbar_expect(fb, 40960);
              tma2d(a, &mx, c * 64, tk.rt * 128, fb);
              tma3d(a + 16384, &mq, 0, c * 64, tk.a * 3, fb);
            } else {
              mbar_expect(fb, 30720);
              const bf16* src = g_kv + ((size_t)((tk.rt * 4 + (c & 1) * 2) * NH + tk.a) * 2 + ((c - 10) >> 1)) * DH * NKEY;
              bulk_load(a, src, 15360, fb);
              bulk_load(a + 15360, src + (size_t)NH * 2 * DH * NKEY, 15360, fb);
            }
          }
        } else if (tk.type == T_W) {
          const int nc = (WF & 1) ? 2 : 96 >> lsplit(tk.rt), c0 = tk.b * nc;
          if (!BSL && tk.rt >= RT_SPLIT && !have_zero) { wait_count(&sy->zeroed, NZ); have_zero = true; }
          const int npre = WPRE ? min(nc, (int)NST) : 0;
          for (int c = 0; c < npre; c++) {
            const uint32_t st = (it + c) % NST, fb = sb + FULL + st * 8;
            mbar_wait_long(sb + EMPTY + st * 8, (((it + c) / NST) & 1) ^ 1);
            mbar_expect(fb, 36864);
            tma3d(sb + st * STAGE + 16384, &mwo, 0, (c0 + c) * 64, tk.a * 5, fb);
          }
          if (nt || flag0 < (64u >> lsplit(tk.rt))) wait_count_t(&sy->o[tk.rt * 16 + tk.b], 64 >> lsplit(tk.rt), tk.rt == 15);
          if (tk.rt >= 13) XT((tk.rt - 13) * 32 + (tk.b >> (tk.rt == 15 && S15 == 16) & 7) * 4 + tk.a, 0);
          fence_flag_to_bulk();
          if (tk.rt >= 13) XT((tk.rt - 13) * 32 + (tk.b >> (tk.rt == 15 && S15 == 16) & 7) * 4 + tk.a, 1);
          for (int c = 0; c < nc; c++, it++) {
            const uint32_t st = it % NST, a = sb + st * STAGE, fb = sb + FULL + st * 8;
            if (c == max(nc - CLW, 0)) mbar_arrive(sb + CGO);
            if (c >= npre) {
              mbar_wait_long(sb + EMPTY + st * 8, ((it / NST) & 1) ^ 1);
              mbar_expect(fb, 36864);
              tma3d(a + 16384, &mwo, 0, (c0 + c) * 64, tk.a * 5, fb);
            }
            tma2d(a, &moa, (c0 + c) * 64, tk.rt * 128, fb);
          }
        } else if (tk.type == T_P && tk.a >= NZ && tk.a < NZ + 80) {
          const uint32_t st = it % NST, a = sb + st * STAGE, fb = sb + FULL + st * 8;
          const int gq = (tk.a - NZ) / 10, k0 = (tk.a - NZ) % 10 * 64;
          mbar_arrive(sb + CGO);
          mbar_wait_long(sb + EMPTY + st * 8, ((it / NST) & 1) ^ 1);
          mbar_expect(fb, 30720 + 3200);
          for (int p = 0; p < 3; p++) tma2d(a + p * 10240, &mwb, p * DM + gq * 80, k0, fb);
          bulk_load_plain(a + 30720, wphi + gq * 4 * BDH * BDH, 3200, fb);
          it++;
        } else if (tk.type != T_F) mbar_arrive(sb + CGO);
      }
    } else if (tid == 32 || tid == 64) {
      const int cw = (tid >> 5) - 1;
      for (uint32_t n = 0;; n++) {
        mbar_wait_long(sb + DONE + cw * 8, n & 1);
        const Task tk = decode(lds32(sb + DTASK + cw * 4));
        if (tk.type == T_END) { early = tk.a; break; }
        if (tk.type == T_W && tk.rt == FXT) XT(128 + (tk.b & 1) * 4 + tk.a, cw);
        if (tk.type == T_Q) tma3d_store(&mos, sb + OST + cw * 24576, 0, tk.rt * 128 + cw * 64, tk.a * 3);
        else if (split(tk.rt) == 1) tma3d_store(&mxa, sb + OST + cw * 24576, 0, tk.rt * 128 + cw * 64, tk.a * 5);
        else if (BSL && SLC) {
          bf16* dst = g_sl + (size_t)(((slice_of(tk.rt) + tk.b) * 4 + tk.a) * 2 + cw) * 10240;
          if (SLEV) bulk_store(dst, sb + OST + cw * 24576, 20480);
          else asm volatile("cp.async.bulk.global.shared::cta.bulk_group [%0], [%1], 20480;" :: "l"(dst), "r"(sb + OST + cw * 24576) : "memory");
        }
        else if (BSL) tma3d_store(&macc, sb + OST + cw * 24576, 0, (slice_of(tk.rt) + tk.b) * 128 + cw * 64, tk.a * 5);
        else {
          const uint32_t slot = lds32(sb + DSLOT + cw * 4);
            asm volatile("cp.reduce.async.bulk.tensor.3d.global.shared::cta.add.tile.bulk_group [%0, {%2, %3, %4}], [%1];"
                         :: "l"(&macc), "r"(sb + slot * STAGE), "r"(0), "r"(layer * ACC_ROWS + (tk.rt - RT_SPLIT) * 128 + cw * 64), "r"(tk.a * 5) : "memory");
          asm volatile("cp.async.bulk.commit_group; cp.async.bulk.wait_group.read 0;" ::: "memory");
          asm volatile("mbarrier.arrive.shared::cta.b64 _, [%0], 8;" :: "r"(sb + EMPTY + slot * 8) : "memory");
        }
        asm volatile("cp.async.bulk.commit_group; cp.async.bulk.wait_group.read 0;" ::: "memory");
        mbar_arrive(sb + FREE + cw * 8);
        if (tk.type == T_Q && tk.rt == 15) XT(96 + tk.a, cw);
        asm volatile("cp.async.bulk.wait_group 0;" ::: "memory");
        if (tk.type == T_Q && tk.rt == 15) XT(96 + tk.a, 2 + cw);
        if (tk.type == T_W && tk.rt >= 13) XT((tk.rt - 13) * 32 + (tk.b >> (tk.rt == 15 && S15 == 16) & 7) * 4 + tk.a, 2 + cw);
        if (tk.type == T_W && tk.rt == FXT) XT(128 + (tk.b & 1) * 4 + tk.a, 2 + cw);
        if (tk.type == T_Q) {
          const int sl = tk.rt * 16 + (tk.a >> (5 - lsplit(tk.rt)));
          publish_bulk<WFEN>(&sy->o[sl]);
        } else if (split(tk.rt) > 1) {
          publish_bulk<WFEN>(&sy->wcnt[(tk.rt * 4 + tk.a) * 2 + cw]);
        }
        sts32(sb + FIN + cw * 4, n + 1);
      }
    }
  } else {
    asm volatile("setmaxnreg.inc.sync.aligned.u32 232;");
    bar_sync(0, 384);
    const int cw = wg - 1, g = lane >> 2, t = lane & 3, ct = tid - 128;
    uint32_t it = 0, nd = 0;
    for (uint32_t nt = 0;; nt++) {
      mbar_wait_long(sb + TFULL + (nt & 1) * 8, (nt >> 1) & 1);
      const int tid_ = __shfl_sync(0xffffffffu, (int)lds32(sb + TASK + (nt & 1) * 4), 0);
      const Task tk = decode(tid_);
      if (nt == 0 && ct == 0) WS(2, tid_);
      __syncwarp();
      if (lane == 0) mbar_arrive(sb + TEMPTY + (nt & 1) * 8);
      if (tk.type == T_END) {
        mbar_wait_long(sb + FREE + cw * 8, (nd & 1) ^ 1);
        if (ct == cw * 128) sts32(sb + DTASK + cw * 4, tid_);
        mbar_arrive(sb + DONE + cw * 8);
        early = tid_ & 1;
        break;
      }
      if (tk.type == T_Q || tk.type == T_G) {
        if (PFACC && tk.type == T_Q && tk.rt >= RT_SPLIT && ct == 32)
          asm volatile("cp.async.bulk.prefetch.L2.global [%0], 10240;" :: "l"(g_acc + (size_t)(layer * ACC_ROWS + (tk.rt - RT_SPLIT) * 128 + tk.a * 4) * DM) : "memory");
        uint32_t q[48];
        uint4* qf = g_qf + (size_t)(tk.rt * NH + tk.a) * 12 * 256 + ct;
        if (tk.type == T_Q && tk.b) {
          if ((ct & 127) == 0) wait_count(&sy->gst[tk.rt * NH + tk.a], 2);
          bar_sync(1 + cw, 128);
#pragma unroll
          for (int i = 0; i < 12; i++) { const uint4 u = __ldcg(qf + i * 256); q[4 * i] = u.x; q[4 * i + 1] = u.y; q[4 * i + 2] = u.z; q[4 * i + 3] = u.w; }
        } else {
          float d[96];
#pragma unroll
          for (int i = 0; i < 96; i++) d[i] = 0.f;
          for (int c = 0; c < ((WF & 2) ? 2 : 10); c++, it++) {
            const uint32_t st = it % NST, a = sb + st * STAGE;
            mbar_wait_long(sb + FULL + st * 8, (it / NST) & 1);
            if (c == 0) TM(0);
            const uint64_t da = mkdesc(a + cw * 8192, 16, 1024, 1), db = mkdesc(a + 16384, 8192, 1024, 1);
            wg_fence();
#pragma unroll
            for (int k = 0; k < 4; k++) wgmma_n192_nt(d, da + k * 2, db + k * 128, c | k);
            wg_commit();
            if (c > 0) { wg_wait<1>(); if (lane == 0) mbar_arrive(sb + EMPTY + ((it - 1) % NST) * 8); }
          }
          wg_wait<0>();
          if (lane == 0) mbar_arrive(sb + EMPTY + ((it - 1) % NST) * 8);
#pragma unroll
          for (int i = 0; i < 48; i++) q[i] = pack_bf16(d[2 * i], d[2 * i + 1]);
        }
        TM(1);
        if (tk.type == T_G) {
#pragma unroll
          for (int i = 0; i < 12; i++) __stcg(qf + i * 256, make_uint4(q[4 * i], q[4 * i + 1], q[4 * i + 2], q[4 * i + 3]));
          bar_sync(1 + cw, 128);
          if ((ct & 127) == 0) red_release(&sy->gst[tk.rt * NH + tk.a]);
          __syncwarp();
          TM(2); TM(3);
          continue;
        }
        const uint32_t itk = tk.b ? it + 2 * cw : it + cw, itv = tk.b ? itk + 1 : it + 2 + cw;
        if (cw == 1) { pass_stage(sb, it, lane); if (tk.b) pass_stage(sb, it + 1, lane); }
        mbar_wait_long(sb + FULL + (itk % NST) * 8, (itk / NST) & 1);
        TM(2);
        const uint32_t mid = tk.b ? 0xFFFFFFFFu : itk + 1;
        if (w & 1) attend<5>(sb, q, cw, w, lane, itk, itv, mid, nd); else attend<3>(sb, q, cw, w, lane, itk, itv, mid, nd);
        if (cw == 0) { if (tk.b) pass_stage(sb, it + 2, lane); pass_stage(sb, it + 3, lane); }
        it += 4;
        if (ct == cw * 128) sts32(sb + DTASK + cw * 4, tid_);
        fence_async();
        mbar_arrive(sb + DONE + cw * 8);
        nd++;
        TM(3);
      } else if (tk.type == T_W) {
        float d[80];
#pragma unroll
        for (int i = 0; i < 80; i++) d[i] = 0.f;
        const int nc = (WF & 1) ? 2 : 96 >> lsplit(tk.rt);
        const int off = (tk.rt * 128 + cw * 64 + w * 16 + g) * DM + tk.a * 160 + 2 * t;
        const bool whole = BSL || split(tk.rt) == 1;
        uint32_t res[40];
#pragma unroll
        for (int i = 0; i < 40; i++) res[i] = split(tk.rt) == 1 ? *(const uint32_t*)(xin + off + (i >> 1) * 8 + (i & 1) * 8 * DM) : 0u;
        for (int c = 0; c < nc; c++, it++) {
          const uint32_t st = it % NST, a = sb + st * STAGE;
          mbar_wait_long(sb + FULL + st * 8, (it / NST) & 1);
          if (c == 0) TM(0);
          const uint64_t da = mkdesc(a + cw * 8192, 16, 1024, 1), db = mkdesc(a + 16384, 4096, 512, 2);
          wg_fence();
#pragma unroll
          for (int k = 0; k < 4; k++) wgmma_n160_nt(d, da + k * 2, db + k * 64, c | k);
          wg_commit();
          if (c > 0) { wg_wait<1>(); if (lane == 0 && (whole || c < nc - 1)) mbar_arrive(sb + EMPTY + ((it - 1) % NST) * 8); }
        }
        wg_wait<0>();
        if (lane == 0 && whole) mbar_arrive(sb + EMPTY + ((it - 1) % NST) * 8);
        TM(1);
        mbar_wait_long(sb + FREE + cw * 8, (nd & 1) ^ 1);
        TM(2);
        if (whole) {
          const uint32_t orow = w * 16 + (lane & 15), ob = sb + OST + cw * 24576 + orow * 64;
          float s1[2] = {0.f, 0.f}, s2[2] = {0.f, 0.f};
#pragma unroll
          for (int i2 = 0; i2 < 10; i2++) {
            uint32_t u[4];
#pragma unroll
            for (int e = 0; e < 4; e++) {
              const int i = 2 * i2 + (e >> 1);
              const uint32_t x = res[4 * i2 + e];
              u[e] = pack_bf16(d[4 * i + (e & 1) * 2] + __uint_as_float(x << 16), d[4 * i + (e & 1) * 2 + 1] + __uint_as_float(x & 0xFFFF0000u));
              const float lo = __uint_as_float(u[e] << 16), hi = __uint_as_float(u[e] & 0xFFFF0000u);
              s1[e & 1] += lo + hi; s2[e & 1] = fmaf(lo, lo, fmaf(hi, hi, s2[e & 1]));
            }
            stsm4(ob + (i2 >> 1) * 4096 + ((((i2 & 1) * 2 + (lane >> 4)) ^ ((orow >> 1) & 3)) << 4), u[0], u[1], u[2], u[3]);
          }
          fence_async();
          if (split(tk.rt) == 1)
#pragma unroll
          for (int e = 0; e < 2; e++) {
            s1[e] += __shfl_xor_sync(0xffffffffu, s1[e], 1); s2[e] += __shfl_xor_sync(0xffffffffu, s2[e], 1);
            s1[e] += __shfl_xor_sync(0xffffffffu, s1[e], 2); s2[e] += __shfl_xor_sync(0xffffffffu, s2[e], 2);
            if (t == 0) red_add2(&sy->rstat[tk.rt * 128 + cw * 64 + w * 16 + g + 8 * e], s1[e], s2[e]);
          }
        } else {
          bar_sync(3, 256);
          const uint32_t slot = (it - 2 + cw) % NST, a = sb + slot * STAGE + (w * 16 + g) * 128 + (t & 1) * 8;
#pragma unroll
          for (int i = 0; i < 20; i++) {
            const uint32_t o = a + (i >> 2) * 8192 + ((((i & 3) * 2 + (t >> 1)) ^ g) << 4);
            sts64(o, __float_as_uint(d[4 * i]), __float_as_uint(d[4 * i + 1])); sts64(o + 1024, __float_as_uint(d[4 * i + 2]), __float_as_uint(d[4 * i + 3]));
          }
          if (ct == cw * 128) sts32(sb + DSLOT + cw * 4, slot);
          fence_async();
        }
        if (ct == cw * 128) sts32(sb + DTASK + cw * 4, tid_);
        mbar_arrive(sb + DONE + cw * 8);
        nd++;
        TM(3);
      } else if (BSL && tk.type == T_F) {
        if (tk.rt == BKVZ && tk.b < 2) for (int i = ct; i < NH * BF * 6 / 8; i += 256) ((uint4*)g_bkv)[(tk.a * 2 + tk.b) * (NH * BF * 6 / 8) + i] = make_uint4(0, 0, 0, 0);
        if (PFF && tk.rt == PFF && tk.b < 2 && ct == 32) {
          const int q = tk.a * 2 + tk.b;
          for (int i = 0; i < 20; i++) asm volatile("cp.async.bulk.prefetch.L2.global [%0], 15360;" :: "l"((const char*)g_wb1 + (q * 20 + i) * 15360) : "memory");
          for (int i = 0; i < 8; i++) asm volatile("cp.async.bulk.prefetch.L2.global [%0], 12800;" :: "l"((const char*)g_wb2 + (q * 8 + i) * 12800) : "memory");
          asm volatile("cp.async.bulk.prefetch.L2.global [%0], 9600;" :: "l"((const char*)g_cs + q * 9600) : "memory");
        }
        constexpr int LPR = 256 / FROWS, NU = (20 + LPR - 1) / LPR;
        const int cq = opq(ct), rl = tk.b * FROWS + cq / LPR, q = cq % LPR, r = tk.rt * 128 + rl, c0 = tk.a * 160 + q * 8;
        if (ct == 0) { wait_count_t(&sy->wcnt[(tk.rt * 4 + tk.a) * 2 + tk.b * FROWS / 64], split(tk.rt), TIGHT == 1 && tk.rt >= 13); if (!FCGO) mbar_arrive(sb + CGO); }
        if (ct == 0 && tk.rt == FXT) XT(136 + tk.a * 4 + tk.b, 1);
        uint4 x[NU];
#pragma unroll
        for (int i = 0; i < NU; i++) x[i] = ldcg_if(xin + r * DM + c0 + i * LPR * 8, i * LPR + q < 20);
        bar_sync(3, 256);
        float a[NU][8];
#pragma unroll
        for (int i = 0; i < NU; i++) {
          a[i][0] = __uint_as_float(x[i].x << 16); a[i][1] = __uint_as_float(x[i].x & 0xFFFF0000u); a[i][2] = __uint_as_float(x[i].y << 16); a[i][3] = __uint_as_float(x[i].y & 0xFFFF0000u);
          a[i][4] = __uint_as_float(x[i].z << 16); a[i][5] = __uint_as_float(x[i].z & 0xFFFF0000u); a[i][6] = __uint_as_float(x[i].w << 16); a[i][7] = __uint_as_float(x[i].w & 0xFFFF0000u);
        }
        float y[NU][8];
#pragma unroll
        for (int i = 0; i < NU * 8; i++) y[i >> 3][i & 7] = 0.f;
        const bf16* sl = SLC ? g_sl + (size_t)((slice_of(tk.rt) * 4 + tk.a) * 2 + (rl >> 6)) * 10240 + (q >> 2) * 2048 + (rl & 63) * 32 + (((q & 3) ^ (rl >> 1 & 3)) << 3)
                             : g_sl + (size_t)(slice_of(tk.rt) * 128 + rl) * DM + c0;
        constexpr int US = SLC ? LPR / 4 * 2048 : LPR * 8;
        constexpr int SB = FROWS == 64 ? 4 : 8;
        for (int b0 = 0; b0 < split(tk.rt); b0 += SB) {
          uint4 u[SB][NU];
#pragma unroll
          for (int b = 0; b < SB; b++)
#pragma unroll
            for (int i = 0; i < NU; i++)
              if (FVOL) u[b][i] = ldcg_if(sl + (size_t)(b0 + b) * 128 * DM + i * US, b0 + b < split(tk.rt) && i * LPR + q < 20);
              else u[b][i] = b0 + b < split(tk.rt) && i * LPR + q < 20 ? __ldcg((const uint4*)(sl + (size_t)(b0 + b) * 128 * DM + i * US)) : make_uint4(0, 0, 0, 0);
          if (FVOL) sched_fence(layer >> 4);
#pragma unroll
          for (int b = 0; b < SB; b++)
#pragma unroll
            for (int i = 0; i < NU; i++) {
              y[i][0] += __uint_as_float(u[b][i].x << 16); y[i][1] += __uint_as_float(u[b][i].x & 0xFFFF0000u); y[i][2] += __uint_as_float(u[b][i].y << 16); y[i][3] += __uint_as_float(u[b][i].y & 0xFFFF0000u);
              y[i][4] += __uint_as_float(u[b][i].z << 16); y[i][5] += __uint_as_float(u[b][i].z & 0xFFFF0000u); y[i][6] += __uint_as_float(u[b][i].w << 16); y[i][7] += __uint_as_float(u[b][i].w & 0xFFFF0000u);
            }
        }
        if (FCGO && ct == 0) { loaded(__float_as_uint(y[0][0])); mbar_arrive(sb + CGO); }
        float s1 = 0.f, s2 = 0.f;
#pragma unroll
        for (int i = 0; i < NU; i++) {
          uint32_t z[4];
#pragma unroll
          for (int e = 0; e < 4; e++) {
            z[e] = pack_bf16(a[i][2 * e] + y[i][2 * e], a[i][2 * e + 1] + y[i][2 * e + 1]);
            const float lo = __uint_as_float(z[e] << 16), hi = __uint_as_float(z[e] & 0xFFFF0000u);
            s1 += lo + hi; s2 = fmaf(lo, lo, fmaf(hi, hi, s2));
          }
          asm volatile("{.reg .pred p; setp.ne.u32 p, %5, 0; @p st.global.v4.u32 [%0], {%1,%2,%3,%4};}"
                       :: "l"(g_xa + r * DM + c0 + i * LPR * 8), "r"(z[0]), "r"(z[1]), "r"(z[2]), "r"(z[3]), "r"((uint32_t)(i * LPR + q < 20)) : "memory");
        }
#pragma unroll
        for (int o = 1; o < LPR; o <<= 1) { s1 += __shfl_xor_sync(0xffffffffu, s1, o); s2 += __shfl_xor_sync(0xffffffffu, s2, o); }
        asm volatile("{.reg .pred p; setp.ne.u32 p, %3, 0; @p red.relaxed.gpu.global.add.v2.f32 [%0], {%1,%2};}"
                     :: "l"(&sy->rstat[r]), "f"(s1), "f"(s2), "r"((uint32_t)(q == 0)) : "memory");
        if (ct == 0 && tk.rt == FXT) XT(136 + tk.a * 4 + tk.b, 2);
        TM(0); TM(1); TM(2); TM(3);
      } else if (tk.type == T_F) {
        if (tk.rt == BKVZ) for (int i = ct; i < NH * BF * 6 / 8; i += 256) ((uint4*)g_bkv)[(tk.a * 2 + tk.b) * (NH * BF * 6 / 8) + i] = make_uint4(0, 0, 0, 0);
        if (PFF && tk.rt == PFF && ct == 32) {
          const int q = tk.a * 2 + tk.b;
          for (int i = 0; i < 20; i++) asm volatile("cp.async.bulk.prefetch.L2.global [%0], 15360;" :: "l"((const char*)g_wb1 + (q * 20 + i) * 15360) : "memory");
          for (int i = 0; i < 8; i++) asm volatile("cp.async.bulk.prefetch.L2.global [%0], 12800;" :: "l"((const char*)g_wb2 + (q * 8 + i) * 12800) : "memory");
          asm volatile("cp.async.bulk.prefetch.L2.global [%0], 9600;" :: "l"((const char*)g_cs + q * 9600) : "memory");
        }
        if (ct == 0) { wait_count(&sy->wcnt[(tk.rt * 4 + tk.a) * 2 + tk.b], split(tk.rt)); mbar_arrive(sb + CGO); }
        const int r = tk.rt * 128 + tk.b * 64 + (ct >> 2), c0 = tk.a * 160 + (ct & 3) * 4;
        uint2 x[10];
#pragma unroll
        for (int i = 0; i < 10; i++) x[i] = __ldg((const uint2*)(xin + r * DM + c0 + i * 16));
        bar_sync(3, 256);
        float4 a[10];
#pragma unroll
        for (int i = 0; i < 10; i++) a[i] = __ldcg((const float4*)(g_acc + (layer * ACC_ROWS + r - RT_SPLIT * 128) * DM + c0 + i * 16));
        float s1 = 0.f, s2 = 0.f;
#pragma unroll
        for (int i = 0; i < 10; i++) {
          const uint2 z = make_uint2(pack_bf16(a[i].x + __uint_as_float(x[i].x << 16), a[i].y + __uint_as_float(x[i].x & 0xFFFF0000u)),
                                     pack_bf16(a[i].z + __uint_as_float(x[i].y << 16), a[i].w + __uint_as_float(x[i].y & 0xFFFF0000u)));
          *(uint2*)(g_xa + r * DM + c0 + i * 16) = z;
          const float v0 = __uint_as_float(z.x << 16), v1 = __uint_as_float(z.x & 0xFFFF0000u), v2 = __uint_as_float(z.y << 16), v3 = __uint_as_float(z.y & 0xFFFF0000u);
          s1 += (v0 + v1) + (v2 + v3); s2 = fmaf(v0, v0, fmaf(v1, v1, fmaf(v2, v2, fmaf(v3, v3, s2))));
        }
        s1 += __shfl_xor_sync(0xffffffffu, s1, 1); s2 += __shfl_xor_sync(0xffffffffu, s2, 1);
        s1 += __shfl_xor_sync(0xffffffffu, s1, 2); s2 += __shfl_xor_sync(0xffffffffu, s2, 2);
        if ((ct & 3) == 0) red_add2(&sy->rstat[r], s1, s2);
        TM(0); TM(1); TM(2); TM(3);
      } else if (tk.a < NZ) {
        if (!BSL) for (int i = ct; i < ACC_ROWS * DM / 4 / NZ; i += 256) ((uint4*)(g_acc + layer * ACC_ROWS * DM))[tk.a * (ACC_ROWS * DM / 4 / NZ) + i] = make_uint4(0, 0, 0, 0);
        if (layer == 1) {
          if (ct == 0) wait_count(&sy->pro[0], 96);
          bar_sync(3, 256);
        }
        for (int i = tk.a * 256 + ct; i < (int)(sizeof(Sync) / 16); i += NZ * 256) ((uint4*)&g_sync[layer ^ 1])[i] = make_uint4(0, 0, 0, 0);
        bar_sync(3, 256);
        if (ct == 0) red_release(&sy->zeroed);
        __syncwarp();
      } else if (tk.a >= NZ + 80) {
        const int c = tk.a - NZ - 80, cq = opq(ct);
        uint4 u[20];
#pragma unroll
        for (int i = 0; i < 20; i++) u[i] = __ldg((const uint4*)(wo2 + c * 64 * DM) + i * 256 + cq);
#pragma unroll
        for (int i = 0; i < 20; i++) {
          const int p = i * 256 + cq, kr = p / 80, n8 = p % 80, gq = n8 / 10;
          g_wb2[(gq * 10 + c) * 640 + (n8 % 10 >> 1) * 128 + kr * 2 + ((n8 & 1) ^ (kr >> 2 & 1))] = u[i];
        }
      } else if (P1M) {
        const int gq = (tk.a - NZ) / 10, k0 = (tk.a - NZ) % 10 * 64;
        const uint32_t ln = opq(lane), gg = ln >> 2, tt = ln & 3, wi = opq(ct >> 5);
        const uint32_t T = sb + OST, stg = sb + (it % NST) * STAGE;
        mbar_wait_long(sb + FULL + (it % NST) * 8, (it / NST) & 1);
        uint32_t a0[4], a1[4], a0k[2], a1k;
        {
          const uint32_t pa = stg + 30720 + w * 800 + tt * 80 + gg * 2;
          auto pr = [&](int d, int f) { uint32_t lo, hi;
            asm volatile("ld.shared.u16 %0, [%1];" : "=r"(lo) : "r"(pa + d * 40 + f * 2) : "memory");
            asm volatile("ld.shared.u16 %0, [%1];" : "=r"(hi) : "r"(pa + d * 40 + 40 + f * 2) : "memory");
            return lo | hi << 16; };
          a0[0] = pr(0, 0); a0[1] = pr(0, 8); a0[2] = pr(8, 0); a0[3] = pr(8, 8);
          const int d2 = tt < 2 ? 16 : 0, f2 = gg < 4 ? 16 : 0;
          a0k[0] = pr(d2, 0); a0k[1] = pr(d2, 8);
          a1[0] = pr(0, f2); a1[2] = pr(8, f2); a1k = pr(d2, f2);
          a1[1] = a1[3] = 0;
          if (tt >= 2) a0k[0] = a0k[1] = a1k = 0;
          if (gg >= 4) a1[0] = a1[2] = a1k = 0;
        }
        float c[8][2][4];
        const uint32_t pb = stg + cw * 10240 + gg * 160 + w * 40 + tt * 4;
#pragma unroll
        for (int nt = 0; nt < 8; nt++) {
          const uint32_t b0 = lds32(pb + nt * 1280), b1 = lds32(pb + nt * 1280 + 16);
          uint32_t b2 = lds32(pb + nt * 1280 + (tt < 2 ? 32 : 0));
          if (tt >= 2) b2 = 0;
#pragma unroll
          for (int i = 0; i < 8; i++) c[nt][i >> 2][i & 3] = 0.f;
          mma16816(c[nt][0], a0, b0, b1); mma16816(c[nt][1], a1, b0, b1);
          mma1688(c[nt][0], a0k[0], a0k[1], b2); mma1688(c[nt][1], a1k, 0u, b2);
        }
        uint32_t v[3][4];
        const uint32_t pv = stg + 20480 + (wi * 8 + (ln & 7)) * 160 + (ln >> 3) * 16;
        ldsm4t(v[0], pv); ldsm4t(v[1], pv + 64); ldsm4t(v[2], pv + (ln >> 4 ? 96 : 128));
        mbar_wait_long(sb + FREE + cw * 8, (nd & 1) ^ 1);
        loaded(v[2][3]);
        bar_sync(3, 256);
        if (lane == 0) mbar_arrive(sb + EMPTY + (it % NST) * 8);
        it++;
        {
          const uint32_t n0 = cw * 80 + w * 2 + (gg >> 1) * 8 + (gg & 1);
#pragma unroll
          for (int q = 0; q < 3; q++) {
            const uint32_t n = n0 + q * 32, ro = T + n * 128 + tt * 4, sw = (n >> 3 & 3) * 2 + (n & 1);
            if (q < 2 || gg < 4)
#pragma unroll
              for (int nt = 0; nt < 8; nt++) sts32(ro + ((nt ^ sw) << 4), pack_bf16(c[nt][q >> 1][(q & 1) * 2], c[nt][q >> 1][(q & 1) * 2 + 1]));
          }
#pragma unroll
          for (int i = 0; i < 10; i++) sts32(T + (160 + i * 8 + gg) * 128 + ((wi ^ gg) << 4) + tt * 4, v[i >> 2][i & 3]);
        }
        bar_sync(3, 256);
        const int cq = opq(ct);
        for (int i = cq; i < 240 * 8; i += 256) {
          const uint32_t n = i >> 3, sw = n < 160 ? (n >> 3 & 3) * 2 + (n & 1) : n & 7;
          uint32_t u[4]; lds128(u, T + n * 128 + (((i & 7) ^ sw) << 4));
          *(uint4*)(g_wb1 + (gq * 240 + n) * DM + k0 + (i & 7) * 8) = make_uint4(u[0], u[1], u[2], u[3]);
        }
        if (cq < 240) {
          float cs = 0.f;
#pragma unroll
          for (int i = 0; i < 8; i++) {
            uint32_t u[4]; lds128(u, T + cq * 128 + (((i + cq) & 7) << 4));
#pragma unroll
            for (int e = 0; e < 4; e++) cs += __uint_as_float(u[e] << 16) + __uint_as_float(u[e] & 0xFFFF0000u);
          }
          g_cs[(k0 >> 6) * 3 * DM + gq * 240 + cq] = cs;
        }
        bar_sync(3, 256);
      } else {
        const int gq = (tk.a - NZ) / 10, k0 = (tk.a - NZ) % 10 * 64, r = ct & 63, hh = ct >> 6;
        bf16* T = (bf16*)(smraw + OST);
        float* ph = (float*)(smraw + OST + 30720);
        const uint32_t stg = sb + (it % NST) * STAGE;
        mbar_wait_long(sb + FULL + (it % NST) * 8, (it / NST) & 1);
        uint2 u[3][5];
#pragma unroll
        for (int i = 0; i < 15; i++) { const float2 v = lds64f(stg + (i / 5) * 10240 + r * 160 + hh * 40 + (i % 5) * 8); u[i / 5][i % 5] = make_uint2(__float_as_uint(v.x), __float_as_uint(v.y)); }
        uint32_t pv[4];
#pragma unroll
        for (int i = 0; i < 4; i++) pv[i] = lds32(stg + 30720 + min(ct + i * 256, 799) * 4);
        mbar_wait_long(sb + FREE + cw * 8, (nd & 1) ^ 1);
        loaded(u[2][4].x); loaded(pv[3]);
        bar_sync(3, 256);
        if (lane == 0) mbar_arrive(sb + EMPTY + (it % NST) * 8);
        it++;
#pragma unroll
        for (int i = 0; i < 4; i++) if (ct + i * 256 < 800) *(float2*)(ph + (ct + i * 256) * 2) = make_float2(__uint_as_float(pv[i] << 16), __uint_as_float(pv[i] & 0xFFFF0000u));
        bar_sync(3, 256);
#pragma unroll
        for (int part = 0; part < 2; part++) {
          float a[BDH];
#pragma unroll
          for (int i = 0; i < 5; i++) {
            a[4 * i] = __uint_as_float(u[part][i].x << 16); a[4 * i + 1] = __uint_as_float(u[part][i].x & 0xFFFF0000u);
            a[4 * i + 2] = __uint_as_float(u[part][i].y << 16); a[4 * i + 3] = __uint_as_float(u[part][i].y & 0xFFFF0000u);
          }
#pragma unroll 1
          for (int f4 = 0; f4 < 5; f4++) {
            float4 q = make_float4(0.f, 0.f, 0.f, 0.f);
#pragma unroll
            for (int dd = 0; dd < BDH; dd++) {
              const float4 p = *(const float4*)(ph + (hh * BDH + dd) * BDH + f4 * 4);
              q.x = fmaf(a[dd], p.x, q.x); q.y = fmaf(a[dd], p.y, q.y); q.z = fmaf(a[dd], p.z, q.z); q.w = fmaf(a[dd], p.w, q.w);
            }
            bf16* dst = T + (part * 80 + f4 * 16 + hh * 2) * 64 + r;
            dst[0] = __float2bfloat16(q.x); dst[64] = __float2bfloat16(q.y); dst[8 * 64] = __float2bfloat16(q.z); dst[9 * 64] = __float2bfloat16(q.w);
          }
        }
#pragma unroll
        for (int i = 0; i < 5; i++) {
          uint16_t* dst = (uint16_t*)T + (160 + hh * BDH + i * 4) * 64 + r;
          dst[0] = (uint16_t)u[2][i].x; dst[64] = (uint16_t)(u[2][i].x >> 16); dst[128] = (uint16_t)u[2][i].y; dst[192] = (uint16_t)(u[2][i].y >> 16);
        }
        bar_sync(3, 256);
        for (int i = ct; i < 240 * 8; i += 256) *(uint4*)(g_wb1 + (gq * 240 + (i >> 3)) * DM + k0 + (i & 7) * 8) = *(const uint4*)(T + i * 8);
        if (ct < 240) {
          float cs = 0.f;
#pragma unroll
          for (int i = 0; i < 8; i++) {
            const uint4 v = *(const uint4*)(T + ct * 64 + ((i + ct) & 7) * 8);
            const uint32_t vv[4] = {v.x, v.y, v.z, v.w};
#pragma unroll
            for (int e = 0; e < 4; e++) cs += __uint_as_float(vv[e] << 16) + __uint_as_float(vv[e] & 0xFFFF0000u);
          }
          g_cs[(k0 >> 6) * 3 * DM + gq * 240 + ct] = cs;
        }
        bar_sync(3, 256);
      }
    }
  }
  __syncwarp();
  if (!CTAIL && !__shfl_sync(0xffffffffu, early, 0)) asm volatile("griddepcontrol.wait;" ::: "memory");
}

#define KVREL 0
#define KVF 0
#define PFA_N 2
#define PFA_DELAY 500
#define PFA_LIMIT 30000
#define PFB_DELAY 2000
#define PFA_ORD 0x0312
#define PFA_SLEEP 0
#define BTPF 0
#define BHALF 0
#define LDL8 3
#define W2E 1
#define PREFETCH_A 0
namespace bk {
constexpr uint32_t STAGE = 47104, NST = 4;
constexpr uint32_t W2 = 0, A2 = 102400;
constexpr uint32_t PHI = 102400, VS = PHI + 128 * 336, KVS = PHI;
constexpr uint32_t OS = A2 + 65536;
constexpr uint32_t PHQ = NST * STAGE;
constexpr uint32_t CS = PHQ;
constexpr uint32_t MISC = PHQ + 128 * 336;
constexpr int NST2 = 7;
constexpr uint32_t FULL = MISC, EMPTY = MISC + 32, EMPTY2 = MISC + 64, BW2 = MISC + 128, BOK = MISC + 136, BKR = MISC + 144, BKV = MISC + 152, FULL2 = MISC + 160;
constexpr uint32_t SMEM = MISC + 256;
}
DEVI void feature_map(const float* d, uint32_t dst) {
#pragma unroll
  for (int r = 0; r < 2; r++) {
    const float l2e = 1.4426950408889634f;
    float mx = d[2 * r], mn = d[2 * r];
#pragma unroll
    for (int i = 1; i < 20; i++) { const float x = d[(i >> 1) * 4 + 2 * r + (i & 1)]; mx = fmaxf(mx, x); mn = fminf(mn, x); }
    mx *= l2e; mn *= l2e;
    float p[20], n[20], sp = 0.f, sn = 0.f;
#pragma unroll
    for (int i = 0; i < 20; i++) {
      const float x = d[(i >> 1) * 4 + 2 * r + (i & 1)];
      p[i] = ex2(fmaf(x, l2e, -mx)); n[i] = ex2(fmaf(x, -l2e, mn)); sp += p[i]; sn += n[i];
    }
    sp = rcp(sp); sn = rcp(sn);
#pragma unroll
    for (int i = 0; i < 5; i++)
      sts128(dst + r * 8 * 336 + i * 16, pack_bf16(p[4 * i] * sp, n[4 * i] * sn), pack_bf16(p[4 * i + 1] * sp, n[4 * i + 1] * sn),
             pack_bf16(p[4 * i + 2] * sp, n[4 * i + 2] * sn), pack_bf16(p[4 * i + 3] * sp, n[4 * i + 3] * sn));
  }
}

__global__ void __launch_bounds__(384, 1)
layerb_kernel(int layer, Sync* sy, const bf16* __restrict__ xin, bf16* __restrict__ out, const void* wa0, const void* wa1, const void* wa2, const void* wa3,
              const __grid_constant__ CUtensorMap mx, const __grid_constant__ CUtensorMap mw1, const __grid_constant__ CUtensorMap mo,
              const __grid_constant__ CUtensorMap mos) {
  using namespace bk;
  extern __shared__ __align__(1024) uint8_t smraw[];
  const uint32_t sb = smem_u32(smraw);
  const int tid = threadIdx.x, lane = tid & 31;
  const int wg = __shfl_sync(0xffffffffu, tid >> 7, 0), w = __shfl_sync(0xffffffffu, (tid >> 5) & 3, 0);
  const int rt = CTAIL ? 15 - (blockIdx.x >> 3) : blockIdx.x >> 3, gq = blockIdx.x & 7;
  if (blockIdx.x >= 128) {
    asm volatile("griddepcontrol.launch_dependents;");
    if (tid == 0) {
      asm volatile("griddepcontrol.wait;" ::: "memory");
      const uint32_t t0 = clk32();
      __nanosleep(PFA_DELAY);
      const int nc = gridDim.x - 128;
      for (int i = blockIdx.x - 128; i < PFA_N * 480 && clk32() - t0 < PFA_LIMIT; i += nc) {
        const int m = PFA_ORD >> (i / 480 * 4) & 3;
        const char* p = (const char*)(m == 0 ? wa0 : m == 1 ? wa1 : m == 2 ? wa2 : wa3) + (size_t)(i % 480) * 16384;
        asm volatile("cp.async.bulk.prefetch.L2.global [%0], 16384;" :: "l"(p) : "memory");
        if (PFA_SLEEP) __nanosleep(PFA_SLEEP);
      }
    }
    return;
  }
  if (tid == 0) {
    for (int i = 0; i < NST; i++) { mbar_init(sb + FULL + i * 8, 1); mbar_init(sb + EMPTY + i * 8, 8); }
    for (int i = 0; i < NST2; i++) { mbar_init(sb + FULL2 + i * 8, 1); mbar_init(sb + EMPTY2 + i * 8, 8); }
    mbar_init(sb + BW2, 1); mbar_init(sb + BOK, 256); mbar_init(sb + BKV, 1); mbar_init(sb + BKR, 1);
    asm volatile("fence.mbarrier_init.release.cluster;" ::: "memory");
  }
  if (!LDL8) asm volatile("griddepcontrol.launch_dependents;");
  if (wg == 0) {
    asm volatile("setmaxnreg.dec.sync.aligned.u32 40;");
    bar_sync(0, 384);
    if (tid == 32 && layer == 0 && PREFETCH_A) {
      asm volatile("griddepcontrol.wait;" ::: "memory");
      __nanosleep(PFB_DELAY);
      for (int i = 0; i < 32; i++) {
        const char* p = (const char*)((i & 1) ? wa0 : wa3) + (size_t)blockIdx.x * 61440 + (i >> 1) * 3840;
        asm volatile("cp.async.bulk.prefetch.L2.global [%0], 3840;" :: "l"(p) : "memory");
        __nanosleep(PREFETCH_A);
      }
    }
    if (w == 2) {
      bar_sync(4, 288);
      if (lane == 0) {
        if (KVREL) red_release(&sy->bkv_cnt[gq]);
        spin_count(&sy->bkv_cnt[gq], 16);
        mbar_arrive(sb + BKR);
      }
    }
    if (tid == 0) {
      if (BTPF) {
        asm volatile("prefetch.tensormap [%0];" :: "l"(&mx) : "memory"); asm volatile("prefetch.tensormap [%0];" :: "l"(&mw1) : "memory");
        asm volatile("prefetch.tensormap [%0];" :: "l"(&mos) : "memory"); asm volatile("prefetch.tensormap [%0];" :: "l"(&mo) : "memory");
      }
      asm volatile("griddepcontrol.wait;" ::: "memory");
      GT(2, 0);
      const int npre = CTAIL && rt >= tl::RT0 ? NST : 0;
      if (npre) {
#pragma unroll 1
        for (int c = 0; c < (int)NST; c++) { mbar_expect(sb + FULL + c * 8, STAGE); tma2d(sb + c * STAGE + 16384, &mw1, c * 64, gq * 240, sb + FULL + c * 8); }
        spin_count(&sy->pro[1 + rt - tl::RT0], 32);
        asm volatile("fence.proxy.async.global;" ::: "memory");
      }
#pragma unroll 1
      for (int c = 0; c < 10; c++) {
        const uint32_t st = c % NST, a = sb + st * STAGE, fb = sb + FULL + st * 8;
        if (c >= npre) {
          mbar_wait_long(sb + EMPTY + st * 8, ((c / NST) & 1) ^ 1);
          mbar_expect(fb, STAGE - (BHALF & 1) * 8192);
        }
        tma2d(a, &mx, c * 64, rt * 128, fb);
        if (c >= npre) tma2d(a + 16384, &mw1, c * 64, gq * 240, fb);
      }
      mbar_wait_long(sb + BKV, 0);
      mbar_expect(sb + BW2, 102400);
      PT(1, 0);
      for (int c = 0; c < 2; c++) bulk_load_plain(sb + W2 + c * 51200, g_wb2 + gq * 6400 + c * 3200, 51200, sb + BW2);
      mbar_wait_long(sb + BOK, 0);
      asm volatile("cp.async.bulk.tensor.2d.global.shared::cta.bulk_group [%0, {%2, %3}], [%1];" :: "l"(&mos), "r"(sb + OS), "r"(gq * 80), "r"(rt * 128) : "memory");
      asm volatile("cp.async.bulk.commit_group; cp.async.bulk.wait_group 0;" ::: "memory");
      publish_bulk<WFEN>(&sy->bo_cnt[rt]);
      spin_count(&sy->bo_cnt[rt], 8);
      fence_flag_to_bulk();
#pragma unroll 1
      for (int c = 0; c < 10; c++) {
        const uint32_t st = c < NST2 ? c : c - NST2, fb = sb + FULL2 + st * 8;
        if (c >= NST2) mbar_wait_long(sb + EMPTY2 + st * 8, 0);
        mbar_expect(fb, 16384 - (BHALF >> 1 & 1) * 8192);
        tma2d(sb + A2 + st * 16384, &mo, c * 64, rt * 128, fb);
      }
    }
  } else {
    asm volatile("setmaxnreg.inc.sync.aligned.u32 232;");
    bar_sync(0, 384);
    asm volatile("griddepcontrol.wait;" ::: "memory");
    const int cw = wg - 1, g = lane >> 2, t = lane & 3, ct = tid - 128;
    const int row = cw * 64 + w * 16 + g;
    float rs[2], ms[2];
    {
      float cs = 0.f;
      if (ct < 240) {
#pragma unroll
        for (int i = 0; i < 10; i++) cs += __ldcg(g_cs + i * 3 * DM + gq * 240 + ct);
      }
      if (!CTAIL)
#pragma unroll
      for (int e = 0; e < 2; e++) {
        const float2 st = __ldcg(&sy->rstat[rt * 128 + row + 8 * e]);
        const float m = st.x * (1.0f / DM);
        rs[e] = rsqrtf(fmaxf(st.y * (1.0f / DM) - m * m, 0.f) + 1e-5f);
        ms[e] = -m * rs[e];
      }
      if (ct < 240) sts32(sb + CS + ct * 4, __float_as_uint(cs));
      bar_sync(3, 256);
      if (CTAIL) {
        mbar_wait_long(sb + FULL, 0);
#pragma unroll
        for (int e = 0; e < 2; e++) asm volatile("ld.global.cg.v2.f32 {%0,%1}, [%2];" : "=f"(ms[e]), "=f"(rs[e]) : "l"(&sy->rstat[rt * 128 + row + 8 * e]) : "memory");
      }
    }
    uint32_t res[20];
    const int off = (rt * 128 + row) * DM + gq * 80 + 2 * t;
    {
      float d[120];
#pragma unroll
      for (int i = 0; i < 120; i++) d[i] = 0.f;
      for (int c = 0; c < 10; c++) {
        const uint32_t st = c % NST, a = sb + st * STAGE;
        mbar_wait_long(sb + FULL + st * 8, (c / NST) & 1);
        if (c == 0 && ct == 0) PT(1, 15);
        const uint64_t da = mkdesc(a + cw * 8192, 16, 1024, 1), db = mkdesc(a + 16384, 16, 1024, 1);
        wg_fence();
#pragma unroll
        for (int k = 0; k < 4; k++) wgmma_n240_nn(d, da + k * 2, db + k * 2, c | k);
        wg_commit();
        if (c > 0) { wg_wait<1>(); if (lane == 0) mbar_arrive(sb + EMPTY + ((c - 1) % NST) * 8); }
      }
      wg_wait<0>();
      if (lane == 0) mbar_arrive(sb + EMPTY + (9 % NST) * 8);
      if (ct == 0) PT(1, 2);
      if (CTAIL)
#pragma unroll
      for (int e = 0; e < 2; e++) {
        const float m = ms[e] * (1.0f / DM);
        rs[e] = rsqrtf(fmaxf(rs[e] * (1.0f / DM) - m * m, 0.f) + 1e-5f);
        ms[e] = -m * rs[e];
      }
#pragma unroll
      for (int i = 0; i < 30; i++) {
        const float2 c = lds64f(sb + CS + (8 * i + 2 * t) * 4);
        d[4 * i] = fmaf(c.x, ms[0], d[4 * i] * rs[0]); d[4 * i + 1] = fmaf(c.y, ms[0], d[4 * i + 1] * rs[0]);
        d[4 * i + 2] = fmaf(c.x, ms[1], d[4 * i + 2] * rs[1]); d[4 * i + 3] = fmaf(c.y, ms[1], d[4 * i + 3] * rs[1]);
      }
      if (ct == 0) PT(1, 11);
      bar_sync(3, 256);
      if (W2E && ct == 0) mbar_arrive(sb + BKV);
      feature_map(&d[40], sb + PHI + row * 336 + t * 80);
      if (ct == 0) PT(1, 12);
#pragma unroll
      for (int i = 0; i < 10; i++) {
        const int c = i * 8 + 2 * t;
        const uint32_t a = sb + VS + row * 208 + (c / 20) * 48 + (c % 20) * 2;
        sts32(a, pack_bf16(d[80 + 4 * i], d[81 + 4 * i])); sts32(a + 8 * 208, pack_bf16(d[82 + 4 * i], d[83 + 4 * i]));
      }
      { const uint32_t a = sb + VS + row * 208 + t * 48 + 40; sts64(a, 0x3F80u, 0u); sts64(a + 8 * 208, 0x3F80u, 0u); }
      bar_sync(3, 256);
      if (ct == 0) PT(1, 13);
      {
        float kv[5][4];
#pragma unroll
        for (int i = 0; i < 20; i++) kv[i >> 2][i & 3] = 0.f;
        const uint32_t pa = sb + PHI + ((lane >> 4) * 8 + (lane & 7)) * 336 + w * 80 + ((lane >> 3) & 1) * 16;
        const uint32_t va = sb + VS + lane * 208 + w * 48;
#pragma unroll
        for (int k2 = 0; k2 < 4; k2++) {
          uint32_t b[3][4];
#pragma unroll
          for (int n = 0; n < 3; n++) ldsm4t(b[n], va + k2 * 32 * 208 + n * 16);
#pragma unroll
          for (int kk = 0; kk < 2; kk++) {
            uint32_t a[4], a2[4];
            ldsm4t(a, pa + (k2 * 32 + kk * 16) * 336 + cw * 32);
            ldsm4t(a2, pa + (k2 * 32 + kk * 16) * 336 + 64);
#pragma unroll
            for (int n = 0; n < 3; n++) mma16816(kv[n], a, b[n][2 * kk], b[n][2 * kk + 1]);
            if (cw == 0) { mma16816(kv[3], a2, b[0][2 * kk], b[0][2 * kk + 1]); mma16816(kv[4], a2, b[1][2 * kk], b[1][2 * kk + 1]); }
            else mma16816(kv[3], a2, b[2][2 * kk], b[2][2 * kk + 1]);
          }
        }
        float* p = g_bkv + ((gq * 4 + w) * BF + g) * 24 + 2 * t;
        PINF(kv[0][0]); PINF(kv[3][0]);
        if (ct == 0) PT(1, 14);
#pragma unroll
        for (int n = 0; n < 3; n++) {
          asm volatile("red.relaxed.gpu.global.add.v2.f32 [%0], {%1,%2};" :: "l"(p + cw * 16 * 24 + n * 8), "f"(kv[n][0]), "f"(kv[n][1]) : "memory");
          asm volatile("red.relaxed.gpu.global.add.v2.f32 [%0], {%1,%2};" :: "l"(p + (cw * 16 + 8) * 24 + n * 8), "f"(kv[n][2]), "f"(kv[n][3]) : "memory");
        }
        asm volatile("red.relaxed.gpu.global.add.v2.f32 [%0], {%1,%2};" :: "l"(p + 32 * 24 + cw * 16), "f"(kv[3][0]), "f"(kv[3][1]) : "memory");
        if (cw == 0) asm volatile("red.relaxed.gpu.global.add.v2.f32 [%0], {%1,%2};" :: "l"(p + 32 * 24 + 8), "f"(kv[4][0]), "f"(kv[4][1]) : "memory");
      }
      if (ct == 0) PT(1, 3);
      if (LDL8 == 4) asm volatile("griddepcontrol.launch_dependents;");
      if (KVF == 1) __threadfence();
      bar_sync(4, 288);
      if (!KVREL) { if (ct == 0) red_release(&sy->bkv_cnt[gq]); __syncwarp(); }
      if (ct == 0) PT(1, 9);
      if (!W2E && ct == 0) mbar_arrive(sb + BKV);
      feature_map(&d[0], sb + PHQ + row * 336 + t * 80);
    }
    if (ct == 0) PT(1, 4);
#pragma unroll
    for (int i = 0; i < 10; i++) { res[2 * i] = __ldcg((const uint32_t*)(g_xa + off + i * 8)); res[2 * i + 1] = __ldcg((const uint32_t*)(g_xa + off + i * 8 + 8 * DM)); }
    mbar_wait_long(sb + BKR, 0);
    if (LDL8 == 1) asm volatile("griddepcontrol.launch_dependents;");
    if (KVF == 2) __threadfence();
    if (KVF == 3) __nanosleep(1500);
    if (ct == 0) PT(1, 5);
    {
      float4 a[4];
#pragma unroll
      for (int i = 0; i < 4; i++) a[i] = __ldcg((const float4*)(g_bkv + gq * 4 * BF * 24) + min(ct + i * 256, 4 * BF * 6 - 1));
#pragma unroll
      for (int i = 0; i < 4; i++) if (ct + i * 256 < 4 * BF * 6) sts64(sb + KVS + (ct + i * 256) * 8, pack_bf16(a[i].x, a[i].y), pack_bf16(a[i].z, a[i].w));
    }
    bar_sync(3, 256);
    {
      float o[4][3][4];
#pragma unroll
      for (int hh = 0; hh < 4; hh++) {
        uint32_t a0[4], a1[4], a2[2], c[4];
        const uint32_t qa = sb + PHQ + (cw * 64 + w * 16 + (lane & 15)) * 336 + hh * 80;
        ldsm4(a0, qa + (lane >> 4) * 16); ldsm4(a1, qa + 32 + (lane >> 4) * 16); ldsm2(a2, qa + 64);
        ldsm4t(c, sb + KVS + hh * 1920 + (32 + (lane & 7)) * 48 + min(lane >> 3, 2) * 16);
#pragma unroll
        for (int n = 0; n < 3; n++) {
          uint32_t b[4];
          ldsm4t(b, sb + KVS + hh * 1920 + lane * 48 + n * 16);
          o[hh][n][0] = o[hh][n][1] = o[hh][n][2] = o[hh][n][3] = 0.f;
          mma16816(o[hh][n], a0, b[0], b[1]); mma16816(o[hh][n], a1, b[2], b[3]); mma1688(o[hh][n], a2[0], a2[1], c[n]);
        }
      }
      const uint32_t oa = sb + OS + row * 160 + t * 4;
#pragma unroll
      for (int hh = 0; hh < 4; hh++) {
        const float i0 = __fdividef(1.0f, __shfl_sync(0xffffffffu, o[hh][2][0], (lane & 28) + 2) + 1e-6f);
        const float i1 = __fdividef(1.0f, __shfl_sync(0xffffffffu, o[hh][2][2], (lane & 28) + 2) + 1e-6f);
#pragma unroll
        for (int n = 0; n < 3; n++)
          if (n < 2 || t < 2) {
            sts32(oa + hh * 40 + n * 16, pack_bf16(o[hh][n][0] * i0, o[hh][n][1] * i0));
            sts32(oa + hh * 40 + n * 16 + 8 * 160, pack_bf16(o[hh][n][2] * i1, o[hh][n][3] * i1));
          }
      }
      fence_async();
    }
    if (ct == 0) PT(1, 6);
    mbar_arrive(sb + BOK);
    if (LDL8 == 2) asm volatile("griddepcontrol.launch_dependents;");
    float d[40];
#pragma unroll
    for (int i = 0; i < 40; i++) d[i] = 0.f;
    mbar_wait_long(sb + BW2, 0);
    for (int c = 0; c < 10; c++) {
      const uint32_t st = c % NST2;
      mbar_wait_long(sb + FULL2 + st * 8, c / NST2);
      if (ct == 0 && c == 0) PT(1, 7);
      if (LDL8 == 3 && c == 0) asm volatile("griddepcontrol.launch_dependents;");
      const uint64_t da = mkdesc(sb + A2 + st * 16384 + cw * 8192, 16, 1024, 1), db = mkdesc(sb + W2 + c * 10240, 2048, 256, 3);
      wg_fence();
#pragma unroll
      for (int k = 0; k < 4; k++) wgmma_n80_nt(d, da + k * 2, db + k * 32, c | k);
      wg_commit();
      if (c > 0 && c <= 10 - NST2) { wg_wait<1>(); if (lane == 0) mbar_arrive(sb + EMPTY2 + (c - 1) * 8); }
    }
    wg_wait<0>();
    if (ct == 0) PT(1, 10);
#pragma unroll
    for (int i = 0; i < 10; i++) {
      *(uint32_t*)(out + off + i * 8) = pack_bf16(d[4 * i] + __uint_as_float(res[2 * i] << 16), d[4 * i + 1] + __uint_as_float(res[2 * i] & 0xFFFF0000u));
      *(uint32_t*)(out + off + i * 8 + 8 * DM) = pack_bf16(d[4 * i + 2] + __uint_as_float(res[2 * i + 1] << 16), d[4 * i + 3] + __uint_as_float(res[2 * i + 1] & 0xFFFF0000u));
    }
    if (ct == 0) PT(1, 8);
    if (ct == 0) GT(2, 1);
  }
}

typedef CUresult (*EncodeFn)(CUtensorMap*, CUtensorMapDataType, cuuint32_t, void*, const cuuint64_t*, const cuuint64_t*, const cuuint32_t*,
                             const cuuint32_t*, CUtensorMapInterleave, CUtensorMapSwizzle, CUtensorMapL2promotion, CUtensorMapFloatOOBfill);
static EncodeFn g_enc = nullptr;
static void make_map(CUtensorMap* m, const void* p, uint64_t cols, uint64_t rows, uint32_t bc, uint32_t br, bool swz = true) {
  cuuint64_t dims[2] = {cols, rows}; cuuint64_t strides[1] = {cols * 2}; cuuint32_t box[2] = {bc, br}; cuuint32_t es[2] = {1, 1};
  g_enc(m, CU_TENSOR_MAP_DATA_TYPE_BFLOAT16, 2, (void*)p, dims, strides, box, es, CU_TENSOR_MAP_INTERLEAVE_NONE, swz ? CU_TENSOR_MAP_SWIZZLE_128B : CU_TENSOR_MAP_SWIZZLE_NONE,
        CU_TENSOR_MAP_L2_PROMOTION_L2_256B, CU_TENSOR_MAP_FLOAT_OOB_FILL_NONE);
}
static void make_map3(CUtensorMap* m, const void* p, uint64_t cols, uint64_t rows, uint32_t cw, uint32_t br, uint32_t bch) {
  cuuint64_t dims[3] = {cw, rows, cols / cw}; cuuint64_t strides[2] = {cols * 2, cw * 2}; cuuint32_t box[3] = {cw, br, bch}; cuuint32_t es[3] = {1, 1, 1};
  g_enc(m, CU_TENSOR_MAP_DATA_TYPE_BFLOAT16, 3, (void*)p, dims, strides, box, es, CU_TENSOR_MAP_INTERLEAVE_NONE,
        cw == 64 ? CU_TENSOR_MAP_SWIZZLE_128B : cw == 32 ? CU_TENSOR_MAP_SWIZZLE_64B : CU_TENSOR_MAP_SWIZZLE_32B, CU_TENSOR_MAP_L2_PROMOTION_L2_256B, CU_TENSOR_MAP_FLOAT_OOB_FILL_NONE);
}
template <typename T> static void* sym(T& s) { void* p = nullptr; cudaGetSymbolAddress(&p, s); return p; }
template <typename... KA, typename... A>
static void launch(void (*k)(KA...), int grid, int smem, bool pdl, A... a) {
  cudaLaunchConfig_t cfg = {};
  cfg.gridDim = dim3(grid); cfg.blockDim = dim3(384); cfg.dynamicSmemBytes = smem; cfg.stream = cudaStreamPerThread;
  cudaLaunchAttribute at[1]; at[0].id = cudaLaunchAttributeProgrammaticStreamSerialization; at[0].val.programmaticStreamSerializationAllowed = 1;
  cfg.attrs = at; cfg.numAttrs = pdl ? 1 : 0;
  cudaLaunchKernelEx(&cfg, k, a...);
}

constexpr int dev_layers = 2, dev_pdl = 1;
#define EV(i)
extern "C" void kernel_launch(void* const* d_in, const int* in_sizes, int n_in, void* d_out, int out_size) {
  static int nsm = 0;
  if (!g_enc) {
    void* fn = nullptr; cudaDriverEntryPointQueryResult st;
    cudaGetDriverEntryPoint("cuTensorMapEncodeTiled", &fn, cudaEnableDefault, &st);
    g_enc = (EncodeFn)fn;
    cudaFuncSetAttribute(chain_kernel, cudaFuncAttributeMaxDynamicSharedMemorySize, ch::SMEM);
    cudaFuncSetAttribute(worker_kernel, cudaFuncAttributeMaxDynamicSharedMemorySize, wk::SMEM);
    cudaFuncSetAttribute(layerb_kernel, cudaFuncAttributeMaxDynamicSharedMemorySize, bk::SMEM);
    cudaDeviceGetAttribute(&nsm, cudaDevAttrMultiProcessorCount, 0);
  }
  CUtensorMap mq, mk, mv, mo, mx, wx, wq, woa, wos, wwo, wxa, wacc, wwb, bx, bw1, bo, bos;
  make_map(&mq, d_in[2], HD, DM, 64, 128); make_map(&mk, d_in[3], HD, DM, 64, 128); make_map(&mv, d_in[4], HD, DM, 64, 128);
  make_map(&mo, d_in[5], DM, HD, 64, 192); make_map3(&mx, sym(g_xn), DM, S_LEN, 64, 32, 5);
  make_map(&wx, sym(g_xn), DM, S_LEN, 64, 128); make_map3(&wq, d_in[2], HD, DM, 64, 64, 3);
  make_map(&woa, sym(g_o), HD, S_LEN, 64, 128); make_map3(&wos, sym(g_o), HD, S_LEN, 64, 64, 3); make_map3(&wwo, d_in[5], DM, HD, 32, 64, 5);
  make_map3(&wxa, sym(g_xa), DM, S_LEN, 32, 64, 5);
  if (BSL) make_map3(&wacc, sym(g_sl), DM, NSL * 128, 32, 64, 5);
  else {
    cuuint64_t dims[3] = {32, 2 * ACC_ROWS, DM / 32}, strides[2] = {DM * 4, 128}; cuuint32_t box[3] = {32, 64, 5}, es[3] = {1, 1, 1};
    g_enc(&wacc, CU_TENSOR_MAP_DATA_TYPE_FLOAT32, 3, sym(g_acc), dims, strides, box, es, CU_TENSOR_MAP_INTERLEAVE_NONE, CU_TENSOR_MAP_SWIZZLE_128B,
          CU_TENSOR_MAP_L2_PROMOTION_NONE, CU_TENSOR_MAP_FLOAT_OOB_FILL_NONE);
  }
  make_map(&wwb, d_in[8], 3 * DM, DM, 80, 64, false);
  make_map(&bx, sym(g_xa), DM, S_LEN, 64, (BHALF & 1) ? 64 : 128); make_map(&bw1, sym(g_wb1), DM, 3 * DM, 64, 240);
  make_map(&bo, sym(g_bo), DM, S_LEN, 64, (BHALF & 2) ? 64 : 128); make_map(&bos, sym(g_bo), DM, S_LEN, 80, 128, false);
  cudaStream_t st = cudaStreamPerThread;
  for (int layer = 0; layer < dev_layers; layer++) {
    const bf16* x = layer == 0 ? (const bf16*)d_in[0] : (const bf16*)sym(g_xb);
    Sync* sy = (Sync*)sym(g_sync) + layer;
    EV(layer * 5);
    EV(layer * 5 + 1);
    launch(chain_kernel, 96, ch::SMEM, dev_pdl && layer, mq, mk, mv, mo, mx, (const bf16*)d_in[1], x, 0u, layer, woa, wwo);
    EV(layer * 5 + 2);
    launch(worker_kernel, WGRID ? WGRID : CTAIL ? nsm - 96 : nsm, wk::SMEM, dev_pdl, layer, sy, x, (const bf16*)d_in[9], (const bf16*)d_in[10], wx, wq, woa, wos, wwo, wxa, wacc, wwb);
    EV(layer * 5 + 3);
    launch(layerb_kernel, layer == 0 && PFA_N ? max(128, min(nsm, 132)) : 128, bk::SMEM, dev_pdl, layer, sy, x, layer == 0 ? (bf16*)sym(g_xb) : (bf16*)d_out,
           (const void*)d_in[2], (const void*)d_in[3], (const void*)d_in[4], (const void*)d_in[5], bx, bw1, bo, bos);
    EV(layer * 5 + 4);
  }
}
```

```cpp
#include <cuda_runtime.h>
#include <cuda_bf16.h>
#include <cuda_fp16.h>
#include <cuda.h>
#include <stdint.h>

typedef __nv_bfloat16 bf16;

constexpr int S_LEN = 2048, DM = 640, NH = 32, DH = 192, NMEM = 8, SEG = 32, NSEG = 64;
constexpr int HD = NH * DH;
constexpr int NKEY = NMEM + SEG;
constexpr int SLAB = 64 * NKEY * 2;
constexpr int AR_STEP_BYTES = 24 * 1024;
constexpr int BDH = 20, BF = 40;

__device__ __align__(1024) bf16 g_xn[S_LEN * DM];
__device__ __align__(1024) bf16 g_kv[(size_t)NSEG * NH * 2 * DH * NKEY];
__device__ __align__(1024) bf16 g_o[(size_t)S_LEN * HD];
__device__ __align__(1024) bf16 g_xa[S_LEN * DM];
__device__ __align__(1024) bf16 g_xb[S_LEN * DM];
__device__ __align__(32768) uint32_t g_ar[NSEG * AR_STEP_BYTES / 4];
#define RTS 10
constexpr int RT_SPLIT = RTS;
constexpr int ACC_ROWS = (16 - RT_SPLIT) * 128;
#define BSL 1
#define FROWS 32
__device__ __align__(1024) float g_acc[BSL ? 256 : 2 * ACC_ROWS * DM];
#define BFL 0
#define CTAIL 1
constexpr int NSL = 48;
__device__ __align__(1024) bf16 g_sl[BSL ? NSL * 128 * DM : 512];
__device__ __align__(1024) float g_cs[10 * 3 * DM];
__device__ __align__(1024) bf16 g_wb1[3 * DM * DM];
__device__ __align__(1024) uint4 g_wb2[DM * DM / 8];
__device__ __align__(1024) bf16 g_bo[S_LEN * DM];
__device__ __align__(1024) uint4 g_qf[16 * NH * 12 * 256];
struct __align__(1024) Sync {
  uint32_t kv[NSEG * NH];
  uint32_t o[16 * 16];
  uint32_t bkv_cnt[8], bo_cnt[16];
  uint32_t pro[4];
  uint32_t wmax[96];
  uint32_t pad1[4];
  uint32_t head, pad0[31];
  uint32_t zeroed, pad[31];
  uint32_t gst[16 * NH];
  uint32_t wcnt[16 * 8];
  float2 rstat[S_LEN];
};
__device__ __align__(1024) Sync g_sync[2];
__device__ uint32_t g_kw;
__device__ __align__(1024) float g_bkv[NH * BF * 24];

#define GT(k, e)
#define WS(e_, v_)
#undef TLOG
#undef TM
#undef PT
#undef XT
#define XT(i, e)
#define TLOG(id, ta)
#define TM(i)
#define PT(k, e)
#define DEVI __device__ __forceinline__
constexpr int SPIN_LIMIT = 20000;
DEVI uint32_t smem_u32(const void* p) { return (uint32_t)__cvta_generic_to_shared(p); }
DEVI uint32_t clk32() { uint64_t c; asm volatile("mov.u64 %0, %%clock64;" : "=l"(c)); return (uint32_t)c; }
DEVI uint32_t mapa(uint32_t a, uint32_t r) { uint32_t o; asm("mapa.shared::cluster.u32 %0, %1, %2;" : "=r"(o) : "r"(a), "r"(r)); return o; }
DEVI void mbar_init(uint32_t bar, uint32_t cnt) { asm volatile("mbarrier.init.shared::cta.b64 [%0], %1;" :: "r"(bar), "r"(cnt) : "memory"); }
DEVI void mbar_expect(uint32_t bar, uint32_t bytes) { asm volatile("mbarrier.arrive.expect_tx.shared::cta.b64 _, [%0], %1;" :: "r"(bar), "r"(bytes) : "memory"); }
DEVI void mbar_arrive(uint32_t bar) { asm volatile("mbarrier.arrive.shared::cta.b64 _, [%0];" :: "r"(bar) : "memory"); }
DEVI void mbar_arrive_cluster(uint32_t rbar) { asm volatile("mbarrier.arrive.relaxed.cluster.shared::cluster.b64 _, [%0];" :: "r"(rbar) : "memory"); }
DEVI bool mbar_try(uint32_t bar, uint32_t par) {
  uint32_t ok;
  asm volatile("{.reg .pred p; mbarrier.try_wait.parity.shared::cta.b64 p, [%1], %2; selp.u32 %0, 1, 0, p;}" : "=r"(ok) : "r"(bar), "r"(par) : "memory");
  return ok;
}
DEVI void mbar_wait(uint32_t bar, uint32_t par) {
  int n = 0;
  while (!mbar_try(bar, par) && ++n < SPIN_LIMIT) {}
}
DEVI void bar_sync(int id, int n) { asm volatile("bar.sync %0, %1;" :: "r"(id), "r"(n) : "memory"); }
DEVI void bar_arrive(int id, int n) { asm volatile("bar.arrive %0, %1;" :: "r"(id), "r"(n) : "memory"); }
DEVI void fence_async() { asm volatile("fence.proxy.async.shared::cta;" ::: "memory"); }
#define RFEN 2
#define CEND 1
#define XFEN 1
#define WFEN 2
template <int M> DEVI void publish_bulk(uint32_t* flag) {
  if (M == 1) asm volatile("fence.proxy.async;" ::: "memory");
  if (M == 2) asm volatile("red.release.gpu.global.add.u32 [%0], 1;" :: "l"(flag) : "memory");
  else asm volatile("red.relaxed.gpu.global.add.u32 [%0], 1;" :: "l"(flag) : "memory");
}
DEVI void fence_flag_to_bulk() {
  if (RFEN == 0) asm volatile("fence.proxy.async;" ::: "memory");
  if (RFEN == 1) asm volatile("fence.proxy.async.global;" ::: "memory");
}
DEVI void cluster_sync_full() { asm volatile("barrier.cluster.arrive.release.aligned; barrier.cluster.wait.acquire.aligned;" ::: "memory"); }
DEVI void tma2d(uint32_t dst, const CUtensorMap* m, int c0, int c1, uint32_t bar) {
  asm volatile("cp.async.bulk.tensor.2d.shared::cluster.global.mbarrier::complete_tx::bytes [%0], [%1, {%3, %4}], [%2];"
               :: "r"(dst), "l"(m), "r"(bar), "r"(c0), "r"(c1) : "memory");
}
DEVI void tma3d(uint32_t dst, const CUtensorMap* m, int c0, int c1, int c2, uint32_t bar) {
  asm volatile("cp.async.bulk.tensor.3d.shared::cluster.global.mbarrier::complete_tx::bytes [%0], [%1, {%3, %4, %5}], [%2];"
               :: "r"(dst), "l"(m), "r"(bar), "r"(c0), "r"(c1), "r"(c2) : "memory");
}
DEVI void tma3d_mc(uint32_t dst, const CUtensorMap* m, int c0, int c1, int c2, uint32_t bar, uint16_t mask) {
  asm volatile("cp.async.bulk.tensor.3d.shared::cluster.global.mbarrier::complete_tx::bytes.multicast::cluster [%0], [%1, {%3, %4, %5}], [%2], %6;"
               :: "r"(dst), "l"(m), "r"(bar), "r"(c0), "r"(c1), "r"(c2), "h"(mask) : "memory");
}
DEVI void tma3d_prefetch(const CUtensorMap* m, int c0, int c1, int c2) {
  asm volatile("cp.async.bulk.prefetch.tensor.3d.L2.global [%0, {%1, %2, %3}];" :: "l"(m), "r"(c0), "r"(c1), "r"(c2) : "memory");
}
DEVI void tma2d_prefetch(const CUtensorMap* m, int c0, int c1) {
  asm volatile("cp.async.bulk.prefetch.tensor.2d.L2.global [%0, {%1, %2}];" :: "l"(m), "r"(c0), "r"(c1) : "memory");
}
#define EVF 7
DEVI uint64_t stream_policy() { uint64_t p; asm("createpolicy.fractional.L2::evict_first.b64 %0, 1.0;" : "=l"(p)); return p; }
DEVI void bulk_store(void* g, uint32_t s, uint32_t bytes) {
  if (EVF & 1) asm volatile("cp.async.bulk.global.shared::cta.bulk_group.L2::cache_hint [%0], [%1], %2, %3;" :: "l"(g), "r"(s), "r"(bytes), "l"(stream_policy()) : "memory");
  else asm volatile("cp.async.bulk.global.shared::cta.bulk_group [%0], [%1], %2;" :: "l"(g), "r"(s), "r"(bytes) : "memory");
}
DEVI void ldsm4(uint32_t (&r)[4], uint32_t a) {
  asm volatile("ldmatrix.sync.aligned.m8n8.x4.shared.b16 {%0,%1,%2,%3}, [%4];" : "=r"(r[0]), "=r"(r[1]), "=r"(r[2]), "=r"(r[3]) : "r"(a) : "memory");
}
DEVI void ldsm4t(uint32_t (&r)[4], uint32_t a) {
  asm volatile("ldmatrix.sync.aligned.m8n8.x4.trans.shared.b16 {%0,%1,%2,%3}, [%4];" : "=r"(r[0]), "=r"(r[1]), "=r"(r[2]), "=r"(r[3]) : "r"(a) : "memory");
}
DEVI void ldsm4t_p(uint32_t* r, uint32_t a) {
  asm volatile("ldmatrix.sync.aligned.m8n8.x4.trans.shared.b16 {%0,%1,%2,%3}, [%4];" : "=r"(r[0]), "=r"(r[1]), "=r"(r[2]), "=r"(r[3]) : "r"(a) : "memory");
}
DEVI void ldsm2(uint32_t (&r)[2], uint32_t a) {
  asm volatile("ldmatrix.sync.aligned.m8n8.x2.shared.b16 {%0,%1}, [%2];" : "=r"(r[0]), "=r"(r[1]) : "r"(a) : "memory");
}
DEVI void stsm4(uint32_t a, uint32_t r0, uint32_t r1, uint32_t r2, uint32_t r3) {
  asm volatile("stmatrix.sync.aligned.m8n8.x4.shared.b16 [%0], {%1,%2,%3,%4};" :: "r"(a), "r"(r0), "r"(r1), "r"(r2), "r"(r3) : "memory");
}
DEVI void mma16816(float (&d)[4], const uint32_t* a, uint32_t b0, uint32_t b1) {
  asm volatile("mma.sync.aligned.m16n8k16.row.col.f32.bf16.bf16.f32 {%0,%1,%2,%3}, {%4,%5,%6,%7}, {%8,%9}, {%0,%1,%2,%3};"
               : "+f"(d[0]), "+f"(d[1]), "+f"(d[2]), "+f"(d[3]) : "r"(a[0]), "r"(a[1]), "r"(a[2]), "r"(a[3]), "r"(b0), "r"(b1));
}
DEVI void mma1688(float (&d)[4], uint32_t a0, uint32_t a1, uint32_t b0) {
  asm volatile("mma.sync.aligned.m16n8k8.row.col.f32.bf16.bf16.f32 {%0,%1,%2,%3}, {%4,%5}, {%6}, {%0,%1,%2,%3};"
               : "+f"(d[0]), "+f"(d[1]), "+f"(d[2]), "+f"(d[3]) : "r"(a0), "r"(a1), "r"(b0));
}
DEVI uint32_t pack_bf16(float lo, float hi) { uint32_t r; asm("cvt.rn.bf16x2.f32 %0, %1, %2;" : "=r"(r) : "f"(hi), "f"(lo)); return r; }
DEVI uint32_t pack_f16(float lo, float hi) { uint32_t r; asm("cvt.rn.f16x2.f32 %0, %1, %2;" : "=r"(r) : "f"(hi), "f"(lo)); return r; }
DEVI uint32_t f16x2_to_bf16x2(uint32_t h) { float2 f = __half22float2(*reinterpret_cast<__half2*>(&h)); return pack_bf16(f.x, f.y); }
DEVI void sts32(uint32_t a, uint32_t v) { asm volatile("st.shared.u32 [%0], %1;" :: "r"(a), "r"(v) : "memory"); }
DEVI void sts64(uint32_t a, uint32_t v0, uint32_t v1) { asm volatile("st.shared.v2.u32 [%0], {%1,%2};" :: "r"(a), "r"(v0), "r"(v1) : "memory"); }
DEVI void sts128(uint32_t a, uint32_t v0, uint32_t v1, uint32_t v2, uint32_t v3) { asm volatile("st.shared.v4.u32 [%0], {%1,%2,%3,%4};" :: "r"(a), "r"(v0), "r"(v1), "r"(v2), "r"(v3) : "memory"); }
DEVI uint32_t lds32(uint32_t a) { uint32_t v; asm volatile("ld.shared.u32 %0, [%1];" : "=r"(v) : "r"(a) : "memory"); return v; }
DEVI float2 lds64f(uint32_t a) { float2 v; asm volatile("ld.shared.v2.f32 {%0,%1}, [%2];" : "=f"(v.x), "=f"(v.y) : "r"(a) : "memory"); return v; }
DEVI void lds128(uint32_t (&r)[4], uint32_t a) { asm volatile("ld.shared.v4.u32 {%0,%1,%2,%3}, [%4];" : "=r"(r[0]), "=r"(r[1]), "=r"(r[2]), "=r"(r[3]) : "r"(a) : "memory"); }
DEVI void st_async64(uint32_t a, float x, float y, uint32_t bar) {
  asm volatile("st.async.weak.shared::cluster.mbarrier::complete_tx::bytes.v2.f32 [%0], {%1,%2}, [%3];" :: "r"(a), "f"(x), "f"(y), "r"(bar) : "memory");
}
DEVI void st_async32(uint32_t a, uint32_t x, uint32_t bar) {
  asm volatile("st.async.weak.shared::cluster.mbarrier::complete_tx::bytes.b32 [%0], %1, [%2];" :: "r"(a), "r"(x), "r"(bar) : "memory");
}
DEVI void ld_relaxed128(uint32_t (&r)[4], const void* p) {
  asm volatile("ld.relaxed.gpu.global.v4.u32 {%0,%1,%2,%3}, [%4];" : "=r"(r[0]), "=r"(r[1]), "=r"(r[2]), "=r"(r[3]) : "l"(p) : "memory");
}
DEVI void red_f16x2(void* p, uint32_t v) { asm volatile("red.relaxed.gpu.global.add.noftz.f16x2 [%0], %1;" :: "l"(p), "r"(v) : "memory"); }
DEVI void red_f16x2_v4(void* p, uint32_t a, uint32_t b, uint32_t c, uint32_t d) {
  asm volatile("red.relaxed.gpu.global.add.noftz.v4.f16x2 [%0], {%1,%2,%3,%4};" :: "l"(p), "r"(a), "r"(b), "r"(c), "r"(d) : "memory");
}
DEVI void red_add2(float2* p, float a, float b) { asm volatile("red.relaxed.gpu.global.add.v2.f32 [%0], {%1,%2};" :: "l"(p), "f"(a), "f"(b) : "memory"); }
DEVI float rcp(float x) { float y; asm("rcp.approx.ftz.f32 %0, %1;" : "=f"(y) : "f"(x)); return y; }
DEVI float ex2(float x) { float y; asm("ex2.approx.ftz.f32 %0, %1;" : "=f"(y) : "f"(x)); return y; }
DEVI uint64_t mkdesc(uint32_t addr, uint32_t lbo, uint32_t sbo, uint32_t swz) {
  return (uint64_t)((addr & 0x3FFFF) >> 4) | ((uint64_t)(lbo >> 4) << 16) | ((uint64_t)(sbo >> 4) << 32) | ((uint64_t)swz << 62);
}
DEVI void wg_fence() { asm volatile("wgmma.fence.sync.aligned;" ::: "memory"); }
DEVI void wg_commit() { asm volatile("wgmma.commit_group.sync.aligned;" ::: "memory"); }
template <int N> DEVI void wg_wait() { asm volatile("wgmma.wait_group.sync.aligned %0;" :: "n"(N) : "memory"); }
#define ACC4(d, o) "+f"(d[o]), "+f"(d[o + 1]), "+f"(d[o + 2]), "+f"(d[o + 3])
constexpr uint32_t DHI_SW128 = (1024u >> 4) | (1u << 30);
DEVI uint32_t desc_lo(uint32_t addr, uint32_t lbo) { return ((addr & 0x3FFFF) >> 4) | ((lbo >> 4) << 16); }
template <int OB_, int ACC> DEVI void wgmma_rs_n32(float (&d)[16], const uint32_t* a, uint32_t b) {
  asm volatile("{.reg .b64 db; .reg .b32 tb; add.u32 tb, %20, %21; mov.b64 db, {tb, %22};\n"
               "wgmma.mma_async.sync.aligned.m64n32k16.f32.bf16.bf16 {%0,%1,%2,%3,%4,%5,%6,%7,%8,%9,%10,%11,%12,%13,%14,%15}, {%16,%17,%18,%19}, db, %23, 1, 1, 0;}"
               : ACC4(d, 0), ACC4(d, 4), ACC4(d, 8), ACC4(d, 12) : "r"(a[0]), "r"(a[1]), "r"(a[2]), "r"(a[3]), "r"(b), "n"(OB_ >> 4), "n"(DHI_SW128), "n"(ACC));
}
template <int K0, int K1, int ACC = 1> struct Unroll {
  static DEVI void kbulk(float (&d)[16], const uint32_t* W, uint32_t x) { wgmma_rs_n32<(K0 >> 2) * 4096 + (K0 & 3) * 32, ACC>(d, W + K0 * 4, x); Unroll<K0 + 1, K1>::kbulk(d, W, x); }
};
template <int K1> struct Unroll<K1, K1, 1> {
  static DEVI void kbulk(float (&)[16], const uint32_t*, uint32_t) {}
};

DEVI void wgmma_n192_nt(float (&d)[96], uint64_t a, uint64_t b, int acc) {
  asm volatile("{.reg .pred p; setp.ne.b32 p, %98, 0;\n"
               "wgmma.mma_async.sync.aligned.m64n192k16.f32.bf16.bf16 {%0,%1,%2,%3,%4,%5,%6,%7,%8,%9,%10,%11,%12,%13,%14,%15,%16,%17,%18,%19,%20,%21,%22,%23,%24,%25,%26,%27,%28,%29,%30,%31,%32,%33,%34,%35,%36,%37,%38,%39,%40,%41,%42,%43,%44,%45,%46,%47,%48,%49,%50,%51,%52,%53,%54,%55,%56,%57,%58,%59,%60,%61,%62,%63,%64,%65,%66,%67,%68,%69,%70,%71,%72,%73,%74,%75,%76,%77,%78,%79,%80,%81,%82,%83,%84,%85,%86,%87,%88,%89,%90,%91,%92,%93,%94,%95}, %96, %97, p, 1, 1, 0, 1;}"
               : ACC4(d, 0), ACC4(d, 4), ACC4(d, 8), ACC4(d, 12), ACC4(d, 16), ACC4(d, 20), ACC4(d, 24), ACC4(d, 28), ACC4(d, 32), ACC4(d, 36), ACC4(d, 40), ACC4(d, 44), ACC4(d, 48), ACC4(d, 52), ACC4(d, 56), ACC4(d, 60), ACC4(d, 64), ACC4(d, 68), ACC4(d, 72), ACC4(d, 76), ACC4(d, 80), ACC4(d, 84), ACC4(d, 88), ACC4(d, 92) : "l"(a), "l"(b), "r"(acc));
}
DEVI void wgmma_n160_nt(float (&d)[80], uint64_t a, uint64_t b, int acc) {
  asm volatile("{.reg .pred p; setp.ne.b32 p, %82, 0;\n"
               "wgmma.mma_async.sync.aligned.m64n160k16.f32.bf16.bf16 {%0,%1,%2,%3,%4,%5,%6,%7,%8,%9,%10,%11,%12,%13,%14,%15,%16,%17,%18,%19,%20,%21,%22,%23,%24,%25,%26,%27,%28,%29,%30,%31,%32,%33,%34,%35,%36,%37,%38,%39,%40,%41,%42,%43,%44,%45,%46,%47,%48,%49,%50,%51,%52,%53,%54,%55,%56,%57,%58,%59,%60,%61,%62,%63,%64,%65,%66,%67,%68,%69,%70,%71,%72,%73,%74,%75,%76,%77,%78,%79}, %80, %81, p, 1, 1, 0, 1;}"
               : ACC4(d, 0), ACC4(d, 4), ACC4(d, 8), ACC4(d, 12), ACC4(d, 16), ACC4(d, 20), ACC4(d, 24), ACC4(d, 28), ACC4(d, 32), ACC4(d, 36), ACC4(d, 40), ACC4(d, 44), ACC4(d, 48), ACC4(d, 52), ACC4(d, 56), ACC4(d, 60), ACC4(d, 64), ACC4(d, 68), ACC4(d, 72), ACC4(d, 76) : "l"(a), "l"(b), "r"(acc));
}
DEVI void wgmma_n240_nn(float (&d)[120], uint64_t a, uint64_t b, int acc) {
  asm volatile("{.reg .pred p; setp.ne.b32 p, %122, 0;\n"
               "wgmma.mma_async.sync.aligned.m64n240k16.f32.bf16.bf16 {%0,%1,%2,%3,%4,%5,%6,%7,%8,%9,%10,%11,%12,%13,%14,%15,%16,%17,%18,%19,%20,%21,%22,%23,%24,%25,%26,%27,%28,%29,%30,%31,%32,%33,%34,%35,%36,%37,%38,%39,%40,%41,%42,%43,%44,%45,%46,%47,%48,%49,%50,%51,%52,%53,%54,%55,%56,%57,%58,%59,%60,%61,%62,%63,%64,%65,%66,%67,%68,%69,%70,%71,%72,%73,%74,%75,%76,%77,%78,%79,%80,%81,%82,%83,%84,%85,%86,%87,%88,%89,%90,%91,%92,%93,%94,%95,%96,%97,%98,%99,%100,%101,%102,%103,%104,%105,%106,%107,%108,%109,%110,%111,%112,%113,%114,%115,%116,%117,%118,%119}, %120, %121, p, 1, 1, 0, 0;}"
               : ACC4(d, 0), ACC4(d, 4), ACC4(d, 8), ACC4(d, 12), ACC4(d, 16), ACC4(d, 20), ACC4(d, 24), ACC4(d, 28), ACC4(d, 32), ACC4(d, 36), ACC4(d, 40), ACC4(d, 44), ACC4(d, 48), ACC4(d, 52), ACC4(d, 56), ACC4(d, 60), ACC4(d, 64), ACC4(d, 68), ACC4(d, 72), ACC4(d, 76), ACC4(d, 80), ACC4(d, 84), ACC4(d, 88), ACC4(d, 92), ACC4(d, 96), ACC4(d, 100), ACC4(d, 104), ACC4(d, 108), ACC4(d, 112), ACC4(d, 116) : "l"(a), "l"(b), "r"(acc));
}
DEVI void wgmma_n80_nt(float (&d)[40], uint64_t a, uint64_t b, int acc) {
  asm volatile("{.reg .pred p; setp.ne.b32 p, %42, 0;\n"
               "wgmma.mma_async.sync.aligned.m64n80k16.f32.bf16.bf16 {%0,%1,%2,%3,%4,%5,%6,%7,%8,%9,%10,%11,%12,%13,%14,%15,%16,%17,%18,%19,%20,%21,%22,%23,%24,%25,%26,%27,%28,%29,%30,%31,%32,%33,%34,%35,%36,%37,%38,%39}, %40, %41, p, 1, 1, 0, 1;}"
               : ACC4(d, 0), ACC4(d, 4), ACC4(d, 8), ACC4(d, 12), ACC4(d, 16), ACC4(d, 20), ACC4(d, 24), ACC4(d, 28), ACC4(d, 32), ACC4(d, 36) : "l"(a), "l"(b), "r"(acc));
}

#define ACQ 0
DEVI uint32_t ld_acquire(const uint32_t* p) {
  uint32_t v;
  if (ACQ) asm volatile("ld.acquire.gpu.global.u32 %0, [%1];" : "=r"(v) : "l"(p) : "memory");
  else asm volatile("ld.relaxed.gpu.global.u32 %0, [%1];" : "=r"(v) : "l"(p) : "memory");
  return v;
}
DEVI uint4 ldcg_if(const void* p, bool on) {
  uint4 v;
  asm volatile("{.reg .pred p; setp.ne.u32 p, %5, 0; mov.u32 %0, 0; mov.u32 %1, 0; mov.u32 %2, 0; mov.u32 %3, 0;\n"
               "@p ld.global.cg.v4.u32 {%0,%1,%2,%3}, [%4];}" : "=&r"(v.x), "=&r"(v.y), "=&r"(v.z), "=&r"(v.w) : "l"(p), "r"((uint32_t)on) : "memory");
  return v;
}
DEVI void red_release(uint32_t* p) { asm volatile("red.release.gpu.global.add.u32 [%0], 1;" :: "l"(p) : "memory"); }
#define TIGHT 1
DEVI void wait_count_t(const uint32_t* p, uint32_t n, bool tight) {
  for (int i = 0; i < 4000000 && ld_acquire(p) < n; i++) if (!(TIGHT && tight)) __nanosleep(100);
}
DEVI void wait_count(const uint32_t* p, uint32_t n) {
  for (int i = 0; i < 4000000 && ld_acquire(p) < n; i++) __nanosleep(100);
}
DEVI void spin_count(const uint32_t* p, uint32_t n) { for (int i = 0; i < 4000000 && ld_acquire(p) < n; i++) {} }
DEVI void mbar_wait_long(uint32_t bar, uint32_t par) { for (int n = 0; n < 4000000 && !mbar_try(bar, par); n++) {} }
DEVI void ln_row(float (&v)[20], bf16* y, int lane) {
  float s = 0.f;
#pragma unroll
  for (int i = 0; i < 20; i++) s += v[i];
#pragma unroll
  for (int o = 16; o; o >>= 1) s += __shfl_xor_sync(0xffffffffu, s, o);
  const float m = s * (1.0f / DM); float q = 0.f;
#pragma unroll
  for (int i = 0; i < 20; i++) { v[i] -= m; q += v[i] * v[i]; }
#pragma unroll
  for (int o = 16; o; o >>= 1) q += __shfl_xor_sync(0xffffffffu, q, o);
  const float r = rsqrtf(q * (1.0f / DM) + 1e-5f);
#pragma unroll
  for (int i = 0; i < 5; i++) *(uint2*)(y + i * 128 + lane * 4) = make_uint2(pack_bf16(v[4 * i] * r, v[4 * i + 1] * r), pack_bf16(v[4 * i + 2] * r, v[4 * i + 3] * r));
}

DEVI uint32_t mag4(uint32_t m, const uint32_t* f) {
  return __vmaxu2(__vmaxu2(m, __vmaxu2(f[0] & 0x7FFF7FFFu, f[1] & 0x7FFF7FFFu)), __vmaxu2(f[2] & 0x7FFF7FFFu, f[3] & 0x7FFF7FFFu));
}
DEVI void publish_max(uint32_t a, uint32_t m) {
  m = __reduce_max_sync(0xffffffffu, max(m & 0xFFFFu, m >> 16));
  if ((threadIdx.x & 31) == 0) asm volatile("red.shared.max.u32 [%0], %1;" :: "r"(a), "r"(m) : "memory");
}

namespace ch {
constexpr uint32_t WQ = 0;
constexpr uint32_t WOF2 = 81920;
constexpr uint32_t WOF = 106496;
constexpr uint32_t XB = 143360;
constexpr uint32_t MEMB = 184320;
constexpr uint32_t KT = 194560;
constexpr uint32_t VT = 199680;
constexpr uint32_t PK = 204800;
constexpr uint32_t QS = 212992;
constexpr uint32_t KP = 215040;
constexpr uint32_t EX = 217088;
constexpr uint32_t OB = 221184;
constexpr uint32_t SX = 224256;
constexpr uint32_t WOF3 = 226176;
constexpr uint32_t WOSTAGE = 143360;
constexpr uint32_t PB = OB;
constexpr uint32_t WMX = OB + 128;
constexpr uint32_t MISC = 228224;
constexpr uint32_t BAR_XF = MISC + 56;
constexpr uint32_t BAR_WK = MISC + 48, BAR_W1 = MISC, BAR_W2 = MISC + 8, BAR_X0 = MISC + 16, BAR_X1 = MISC + 24, BAR_S = MISC + 32, BAR_O = MISC + 40;
constexpr uint32_t MX = MISC + 64;
constexpr uint32_t INV = MX + 32;
#define PD_ 550
#define XD_ 150
#define X1D_ 0
#define PFW 0
constexpr uint32_t SMEM = 228352;
}

#define TS(e)
#define TSV(e, v)
#define TSX(x)
#define TSD(e, x)

#define SS(e)
#define E1(id, x)
#define PIN(x) asm volatile("" : "+r"(x))
#define PINF(x) asm volatile("" : "+f"(x))
#define PINL(x) asm volatile("" : "+l"(x))

DEVI uint32_t ar_line_off(uint32_t l) { return (l >> 2) * 1024 + (l & 3) * 128; }
DEVI uint32_t ar_tile_off(int T) { return (T >> 1) * 1024 + (T & 1) * 256; }
DEVI uint32_t ar_extra_off(uint32_t T) { return ar_line_off(80 + (T >> 2)) + (T & 3) * 32; }

DEVI void wo_red(const char* p, uint32_t w0, uint32_t w1, bool last) {
  red_f16x2((void*)p, last ? 0x3C00u : w0);
  red_f16x2((void*)(p + 128), last ? 0x3C00u : w1);
}
DEVI void wo_red_extra_p(const char* px, uint32_t w0, uint32_t w1, uint32_t ln) {
  asm volatile("{.reg .pred p; setp.eq.u32 p, %5, 31; @p red.relaxed.gpu.global.add.noftz.v4.f16x2 [%0], {%1,%2,%3,%4};}"
               :: "l"(px), "r"(w0), "r"(w1), "r"(0u), "r"(0x3C00u), "r"(ln) : "memory");
}

#define ARH 2
DEVI void sched_fence(uint32_t zero) {
#pragma unroll 1
  for (uint32_t i = 0; i < zero; i++) asm volatile("nanosleep.u32 0;" ::: "memory");
}
template <int N> DEVI void code_pad(uint32_t zero) {
  if (N > 0) {
#pragma unroll 1
    for (uint32_t i = 0; i < zero; i++) {
#pragma unroll
      for (int k = 0; k < N; k++) asm volatile("nanosleep.u32 0;" ::: "memory");
    }
  }
}
#define PAD1 0
#define PAD0 0
DEVI void loaded(uint32_t x) { asm volatile("{.reg .pred p; setp.eq.u32 p, %0, 0xdeadbeef; @p nanosleep.u32 0;}" :: "r"(x) : "memory"); }
DEVI uint32_t opq(uint32_t x) { asm volatile("" : "+r"(x)); return x; }

DEVI uint32_t ar_read(const char* arb, uint32_t sb, int w, uint32_t lane_, uint32_t zero, uint32_t tref, int dly, int s) {
  const int wg = 2; (void)wg; (void)s;
  const uint32_t lane = opq(lane_);
  const int b0 = (w >> 1) * 10 + (w & 1);
  const uint32_t e = min(lane, 9u), T = 2 * b0 + 4 * (e >> 1) + (e & 1);
  const char* p0 = arb + b0 * 1024 + lane * 16;
  const char* p2 = arb + ar_extra_off(T);
  uint32_t dst = sb + ch::MEMB + b0 * 512 + lane * 16, dst2 = sb + ch::MEMB + (16 * T + 7) * 16 + 12;
  uint32_t v[6][4];
  PINL(p0); PINL(p2); PIN(dst); PIN(dst2);
  while ((int)(clk32() - tref) < dly) {}
#pragma unroll
  for (int i = 0; i < 5; i++) ld_relaxed128(v[i], p0 + i * 2048);
  ld_relaxed128(v[5], p2);
  sched_fence(zero);
  TS(4);
  uint32_t bad = 0;
#pragma unroll
  for (int i = 0; i < 5; i++) bad |= v[i][3] ^ 0x5000u;
  if ((lane & 7) != 7) bad = 0;
  bad |= v[5][3] ^ 0x5000u;
  TSD(5, bad);
  E1(6, bad);
  int n = 0;
  if (__any_sync(0xffffffffu, bad != 0)) {
    if (lane == 0) sts32(sb + ch::MX + 20, 1u);
    while (true) {
      bad = 0;
#pragma unroll
      for (int i = 0; i < 6; i++) if ((i == 5 || (lane & 7) == 7) && v[i][3] != 0x5000u) bad |= 1u << i;
      bad = __reduce_or_sync(0xffffffffu, bad);
      if (!bad || ++n > SPIN_LIMIT) break;
#pragma unroll
      for (int i = 0; i < 6; i++) if (bad >> i & 1) ld_relaxed128(v[i], i < 5 ? p0 + i * 2048 : p2);
    }
  }
  TSV(6, n);
  const uint32_t x0 = f16x2_to_bf16x2(v[5][0]), x1 = f16x2_to_bf16x2(v[5][1]);
#pragma unroll
  for (int i = 0; i < 5; i++) {
    sts128(dst + i * 1024, f16x2_to_bf16x2(v[i][0]), f16x2_to_bf16x2(v[i][1]), f16x2_to_bf16x2(v[i][2]), f16x2_to_bf16x2(v[i][3]));
    if (i == ARH - 1 || i == 4) {
      __syncwarp();
      sts32(dst2, x0); sts32(dst2 + 128, x1);
      if (i < 4) { TS(7); bar_arrive(1, 384); sched_fence(zero); } else { TSX(TS(1)); bar_sync(3, 384); }
    }
  }
  const uint32_t keep = (lane & 7) == 7 ? 0u : 0x7FFF7FFFu;
  uint32_t m = __vmaxu2(v[5][0] & 0x7FFF7FFFu, v[5][1] & 0x7FFF7FFFu);
#pragma unroll
  for (int i = 0; i < 5; i++) m = __vmaxu2(__vmaxu2(m, __vmaxu2(v[i][0] & 0x7FFF7FFFu, v[i][1] & 0x7FFF7FFFu)), __vmaxu2(v[i][2] & 0x7FFF7FFFu, v[i][3] & keep));
  return m;
}

#define VL 0
struct Peers {
  uint32_t a[2];
  DEVI Peers(uint32_t sb, int j) {
#pragma unroll
    for (int r = 0; r < 2; r++) { int peer = j + 1 + r; if (peer >= 3) peer -= 3; a[r] = mapa(sb, peer); }
  }
};
DEVI uint32_t lane_id() { const uint32_t l = threadIdx.x & 31; return __shfl_sync(0xffffffffu, l, l); }
DEVI void score_tile(uint32_t sb, uint32_t qa, const uint32_t (&b0)[4], const uint32_t (&b1)[4], const Peers& pe, uint32_t off, uint32_t lane) {
  float c0[4] = {0.f, 0.f, 0.f, 0.f}, c1[4] = {0.f, 0.f, 0.f, 0.f};
  uint32_t a0[4], a1[4], a2[4], a3[4];
  ldsm4t(a0, qa); ldsm4t(a1, qa + 256); ldsm4t(a2, qa + 512); ldsm4t(a3, qa + 768);
  mma16816(c0, a0, b0[0], b0[1]); mma16816(c1, a1, b0[2], b0[3]);
  mma16816(c0, a2, b1[0], b1[1]); mma16816(c1, a3, b1[2], b1[3]);
  if (!VL) asm volatile("bar.arrive 5, 288;" : "+f"(c0[0]), "+f"(c1[0]) :: "memory");
  const float cs = 0.25f * 0.07216878364870322f * 1.4426950408889634f;
  const float x = ((c0[0] + c0[2]) + (c1[0] + c1[2])) * cs, y = ((c0[1] + c0[3]) + (c1[1] + c1[3])) * cs;
  uint32_t u; asm("cvt.rn.satfinite.f16x2.f32 %0, %1, %2;" : "=r"(u) : "f"(y), "f"(x));
  st_async32(pe.a[0] + off, u, pe.a[0] + ch::BAR_S);
  st_async32(pe.a[1] + off, u, pe.a[1] + ch::BAR_S);
  sts32(sb + off, u);
  __syncwarp();
  if (lane == 0) mbar_arrive(sb + ch::BAR_S);
}
DEVI uint32_t hadd2(uint32_t a, uint32_t b) { uint32_t r; asm("add.rn.f16x2 %0, %1, %2;" : "=r"(r) : "r"(a), "r"(b)); return r; }
DEVI uint32_t hmax2(uint32_t a, uint32_t b) { uint32_t r; asm("max.f16x2 %0, %1, %2;" : "=r"(r) : "r"(a), "r"(b)); return r; }
DEVI uint32_t add_bf16x2(uint32_t a, uint32_t b) { uint32_t r; asm("add.rn.bf16x2 %0, %1, %2;" : "=r"(r) : "r"(a), "r"(b)); return r; }

DEVI uint32_t slab_off(uint32_t base, int w, uint32_t lane) { return base + (16 * w + (lane >> 2)) * 80 + (lane & 3) * 4; }
DEVI void release_x(uint32_t sb, int half, int w, uint32_t lane) {
  if (lane == 0) {
    if (w == 0) mbar_expect(sb + ch::BAR_X0 + half * 8, 20480);
    mbar_arrive_cluster(mapa(sb + ch::BAR_XF, half));
  }
}
#define TSYNC 1
#define KORD 0
#define X0E 0
#define X0D_ 0
#define X1E 1
#define KS2 0
#define SKIPT 0
DEVI void store_slabs(uint32_t sb, int s, int h, int j) {
  bf16* kvp = g_kv + ((size_t)(s * NH + h) * 2 * DH + 64 * j) * NKEY;
  fence_async();
  bulk_store(kvp, sb + ch::KT, SLAB);
  bulk_store(kvp + DH * NKEY, sb + ch::VT, SLAB);
  asm volatile("cp.async.bulk.commit_group;" ::: "memory");
}

template <int MODE>
DEVI void tokens_partial(uint32_t sb, uint32_t dst, const uint32_t* W, uint32_t xdesc, int w, uint32_t lane) {
  float d[16];
#pragma unroll
  for (int i = 0; i < 16; i++) d[i] = 0.f;
  wg_fence();
  if (!((SKIPT >> (MODE == 3 ? 1 : MODE)) & 1)) Unroll<20, 40, 0>::kbulk(d, W - 80, xdesc);
  wg_commit();
  if (MODE == 1) bar_sync(12, 384);
  if (!KS2 && MODE == 2) bar_sync(11, 256);
  wg_wait<0>();
  if (!KS2 && (MODE == 1 || MODE == 3)) release_x(sb, 1, w, lane);
  if (MODE == 1) bar_sync(13, 384);
  if (KS2 && MODE == 2) release_x(sb, 1, w, lane);
  dst += sb + w * 512 + opq(lane) * 16;
#pragma unroll
  for (int i = 0; i < 4; i++)
    sts128(dst + i * 2048, __float_as_uint(d[4 * i]), __float_as_uint(d[4 * i + 1]), __float_as_uint(d[4 * i + 2]), __float_as_uint(d[4 * i + 3]));
  if (KS2 && MODE == 2) bar_arrive(11, 256);
}
#define LSH 0
#define KPK 16
template <bool LOOP>
DEVI void tokens_finish(uint32_t sb, const uint32_t* W, uint32_t xdesc, int w, uint32_t lane, int s = 0, const CUtensorMap* mx = nullptr) {
  const uint32_t ln = opq(lane), t16 = sb + w * 512 + ln * 16, slab = sb + slab_off(16, w, ln);
  float d[16]; uint32_t e[4][4];
#pragma unroll
  for (int i = 0; i < 16; i++) d[i] = 0.f;
  wg_fence();
  if (!(LOOP && (SKIPT & 8))) Unroll<0, 20, 0>::kbulk(d, W + 80, xdesc);
  wg_commit();
  if (!KS2 && !KORD && LOOP) bar_arrive(6, 256);
  if (LOOP && LSH == 2 && s < 0) bar_sync(8, 256);
  if (!LOOP) {
    bar_sync(8, 256);
    if (w == 3 && lane == 0) { mbar_expect(sb + ch::BAR_X1, 20480); tma3d(sb + ch::XB + 20480, mx, 0, SEG, 5, sb + ch::BAR_X1); }
    __syncwarp();
  }
#pragma unroll
  for (int i = 0; i < 4; i++) lds128(e[i], t16 + ch::QS + i * 2048);
  wg_wait<0>();
  uint32_t u[8];
#pragma unroll
  for (int i = 0; i < 4; i++) {
    u[2 * i] = pack_bf16(d[4 * i] + __uint_as_float(e[i][0]), d[4 * i + 1] + __uint_as_float(e[i][1]));
    u[2 * i + 1] = pack_bf16(d[4 * i + 2] + __uint_as_float(e[i][2]), d[4 * i + 3] + __uint_as_float(e[i][3]));
  }
  wg_fence();
  if (!(LOOP && (SKIPT & 16))) Unroll<0, 6, 0>::kbulk(d, W, xdesc);
#pragma unroll
  for (int i = 0; i < 4; i++) { sts32(slab + ch::VT + i * 16, u[2 * i]); sts32(slab + ch::VT + i * 16 + 640, u[2 * i + 1]); }
  if (KS2) {
    if (!(LOOP && (SKIPT & 16))) Unroll<6, KPK>::kbulk(d, W, xdesc);
    if (LOOP) bar_sync(11, 256);
  }
#pragma unroll
  for (int i = 0; i < 4; i++) lds128(e[i], t16 + ch::PK + i * 2048);
  if (!KS2) {
    if (!(LOOP && (SKIPT & 16))) Unroll<6, KPK>::kbulk(d, W, xdesc);
    if (LOOP) asm volatile("bar.arrive 11, 256;" : "+r"(e[0][0]), "+r"(e[1][0]), "+r"(e[2][0]), "+r"(e[3][0]) :: "memory");
  }
  if (!(LOOP && (SKIPT & 16))) Unroll<KPK, 20>::kbulk(d, W, xdesc);
  wg_commit(); wg_wait<0>();
  release_x(sb, 0, w, lane);
  if (LOOP) E1(7, __float_as_uint(d[0]));
#pragma unroll
  for (int i = 0; i < 4; i++) {
    sts32(slab + ch::KT + i * 16, pack_bf16(d[4 * i] + __uint_as_float(e[i][0]), d[4 * i + 1] + __uint_as_float(e[i][1])));
    sts32(slab + ch::KT + i * 16 + 640, pack_bf16(d[4 * i + 2] + __uint_as_float(e[i][2]), d[4 * i + 3] + __uint_as_float(e[i][3])));
  }
}

DEVI uint32_t afrag_off(int w, uint32_t lane) { return ((lane >> 4) * 8 + (lane & 7)) * 128 + (((w * 2 + ((lane >> 3) & 1)) ^ (lane & 7)) << 4); }
#define NF 5
#define WQR 0
DEVI void ldwq(uint32_t (&f)[4], uint32_t a) { if (WQR) lds128(f, a); else ldsm4t(f, a); }
DEVI void proj_stage(uint32_t (&f)[NF][4], uint32_t qa) {
#pragma unroll
  for (int i = 0; i < NF; i++) ldwq(f[i], qa + i * 2048);
}
template <int WG>
DEVI void proj_mem(float (&q)[4], float (&k)[4], float (&v)[4], uint32_t (&f)[NF][4], const uint32_t* W, uint32_t qa, uint32_t ba, uint32_t sb, int w, int s) {
  uint32_t b[2][4];
  const int wg = WG; (void)wg; (void)sb; (void)w; (void)s;
#pragma unroll
  for (int i = 0; i < 4; i++) q[i] = k[i] = v[i] = 0.f;
  bar_sync(1, 384);
  ldsm4t(b[0], ba);
  if (WG == 0) E1(8, b[0][0]);
  if (WG == 1) { TSX(TSD(5, b[0][0])); }
#pragma unroll
  for (int k2 = 0; k2 < 10; k2++) {
    if (WG == 1 && k2 + 1 == 2 * ARH) { TSX(TSD(7, __float_as_uint(v[0]))); }
    if (k2 + 1 == 2 * ARH) bar_sync(3, 384);
    if (k2 < 9) ldsm4t(b[(k2 + 1) & 1], ba + (k2 + 1) * 512);
    if (WG == 1 && k2 + 1 == 2 * ARH) { TSX(TSD(6, b[(k2 + 1) & 1][0])); }
    if (WG == 0 && k2 + 1 == 2 * ARH) { TSX(TSD(7, __float_as_uint(v[0]))); }
    mma16816(q, f[(2 * k2) % NF], b[k2 & 1][0], b[k2 & 1][1]);
    if (2 * k2 + NF < 20) ldwq(f[(2 * k2) % NF], qa + (2 * k2 + NF) * 2048);
    mma16816(k, &W[k2 * 8], b[k2 & 1][0], b[k2 & 1][1]);
    mma16816(v, &W[80 + k2 * 8], b[k2 & 1][0], b[k2 & 1][1]);
    mma16816(q, f[(2 * k2 + 1) % NF], b[k2 & 1][2], b[k2 & 1][3]);
    if (2 * k2 + 1 + NF < 20) ldwq(f[(2 * k2 + 1) % NF], qa + (2 * k2 + 1 + NF) * 2048);
    mma16816(k, &W[k2 * 8 + 4], b[k2 & 1][2], b[k2 & 1][3]);
    mma16816(v, &W[84 + k2 * 8], b[k2 & 1][2], b[k2 & 1][3]);
  }
}

template <bool BAR>
DEVI void wo_tile_smem(uint32_t sb, uint32_t fa, uint32_t ob, int par, const char* p, const char* px, bool last, float& sc) {
  uint32_t f[6][4], b[2][4];
  float c0[4] = {0.f, 0.f, 0.f, 0.f}, c1[4] = {0.f, 0.f, 0.f, 0.f};
#pragma unroll
  for (int k = 0; k < 6; k++) lds128(f[k], fa + k * 512);
  if (BAR) bar_sync(9, 384);
  ldsm4t(b[0], ob); ldsm4t(b[1], ob + 512);
  sc = __uint_as_float(lds32(sb + ch::MX + 16));
  float2 iv = lds64f(sb + ch::INV + (opq(threadIdx.x) & 3) * 8);
  iv.x *= sc; iv.y *= sc;
  mma16816(c0, f[0], b[0][0], b[0][1]); mma16816(c1, f[1], b[0][2], b[0][3]);
  mma16816(c0, f[2], b[1][0], b[1][1]); mma16816(c1, f[3], b[1][2], b[1][3]);
#pragma unroll
  for (int k = 0; k < 4; k++) lds128(f[k], fa + (6 + k) * 512);
  mbar_wait(sb + ch::BAR_O, par);
  ldsm4t(b[0], ob + 1024); ldsm4t(b[1], ob + 1536);
  mma16816(c0, f[4], b[0][0], b[0][1]); mma16816(c1, f[5], b[0][2], b[0][3]);
  lds128(f[4], fa + 10 * 512); lds128(f[5], fa + 11 * 512);
  ldsm4t(b[0], ob + 2048);
  mma16816(c0, f[0], b[1][0], b[1][1]); mma16816(c1, f[1], b[1][2], b[1][3]);
  ldsm4t(b[1], ob + 2560);
  mma16816(c0, f[2], b[0][0], b[0][1]); mma16816(c1, f[3], b[0][2], b[0][3]);
  mma16816(c0, f[4], b[1][0], b[1][1]); mma16816(c1, f[5], b[1][2], b[1][3]);
  const uint32_t w0 = pack_f16((c0[0] + c1[0]) * iv.x, (c0[1] + c1[1]) * iv.y), w1 = pack_f16((c0[2] + c1[2]) * iv.x, (c0[3] + c1[3]) * iv.y);
  wo_red(p, w0, w1, last);
  wo_red_extra_p(px, w0, w1, last ? 31u : 0u);
}

#define LNFIRST 0
DEVI void chain_prepare(const bf16* __restrict__ x) {
  const int t = threadIdx.x, lane = t & 31, r0 = blockIdx.x * 11 + (t >> 5);
  asm volatile("griddepcontrol.wait;" ::: "memory");
  uint2 u[2][5];
#pragma unroll
  for (int i = 0; i < 10; i++) u[i / 5][i % 5] = __ldcg((const uint2*)(x + min(r0 + (i / 5) * 1056, S_LEN - 1) * DM + (i % 5) * 128 + lane * 4));
#pragma unroll
  for (int rr = 0; rr < 2; rr++) {
    float v[20];
#pragma unroll
    for (int i = 0; i < 5; i++) {
      v[4 * i] = __uint_as_float(u[rr][i].x << 16); v[4 * i + 1] = __uint_as_float(u[rr][i].x & 0xFFFF0000u);
      v[4 * i + 2] = __uint_as_float(u[rr][i].y << 16); v[4 * i + 3] = __uint_as_float(u[rr][i].y & 0xFFFF0000u);
    }
    if (r0 + rr * 1056 < S_LEN) ln_row(v, g_xn + (r0 + rr * 1056) * DM, lane);
  }
}
#define LNF 0
#define PWIN 3
#define PWIN1 3
#define LASTG 1
#define PSPL 1
DEVI void load_weights(uint32_t (&W)[160], uint32_t sb, int G, int w, int j, int layer) {
  using namespace ch;
  const uint32_t lane = threadIdx.x & 31;
  const uint32_t wa = sb + G * 40960 + afrag_off(w, lane);
#pragma unroll 1
  for (int i = 0; i < 5; i++) mbar_wait_long(sb + PB + i * 8, 0);
  if (threadIdx.x == 0) PT(0, 10);
#pragma unroll
  for (int kk = 0; kk < 20; kk++) ldsm4t_p(&W[80 + kk * 4], wa + 81920 + kk * 2048);
  uint32_t m = 0;
#pragma unroll
  for (int kk = 0; kk < 20; kk++) m = mag4(m, &W[80 + kk * 4]);
  publish_max(sb + WMX, m);
  bar_sync(8, 256);
  if (threadIdx.x == 0) mbar_arrive(sb + BAR_W1);
#pragma unroll 1
  for (int i = 7; i < 12; i++) mbar_wait_long(sb + PB + i * 8, 0);
  if (threadIdx.x == 0) PT(0, 9);
#pragma unroll
  for (int kk = 0; kk < 20; kk++) ldsm4t_p(&W[kk * 4], wa + kk * 2048);
  loaded(W[79]);
  bar_sync(8, 256);
  if (threadIdx.x == 0) mbar_arrive(sb + BAR_WK);
  m = 0;
  mbar_wait_long(sb + PB + (G == 0 ? 13 : 6) * 8, 0);
  if (threadIdx.x == 0) PT(0, 11);
  const uint32_t src = (G == 0 ? sb + WOF : sb + WOSTAGE + 2 * 24576) + afrag_off(w, lane);
  if (G == 1) {
    for (int kk = 0; kk < 12; kk++) { uint32_t f[4]; ldsm4t(f, src + kk * 2048); m = mag4(m, f); }
    publish_max(sb + WMX + 4, m);
    bar_sync(7, 384);
  }
  if (G == 1 || w < 2) {
    for (int kk = 0; kk < 12; kk++) {
      uint32_t f[4];
      ldsm4t(f, src + ((kk + 4 * j) % 12) * 2048);
      sts128(sb + WOF + ((G == 0 ? 4 + w : w) * 12 + kk) * 512 + lane * 16, f[0], f[1], f[2], f[3]);
      if (G == 0) m = mag4(m, f);
    }
  }
  if (G == 0) { publish_max(sb + WMX + 4, m); bar_sync(7, 384); }
  bar_sync(7, 384);
}
DEVI void arrange_wq(uint32_t sb, int G, int w, int layer) {
  using namespace ch;
  const uint32_t lane = threadIdx.x & 31;
  mbar_wait_long(sb + BAR_W2, 0);
  if (threadIdx.x == 0) PT(0, 15);
  if (WQR) {
    const uint32_t src = sb + WQ + G * 40960 + afrag_off(w, lane), dst = sb + WQ + G * 40960 + w * 512 + lane * 16;
#pragma unroll 1
    for (int r = 0; r < 5; r++) {
      uint32_t f[4][4];
#pragma unroll
      for (int i = 0; i < 4; i++) ldsm4t(f[i], src + (r * 4 + i) * 2048);
      bar_sync(14 + G, 128);
#pragma unroll
      for (int i = 0; i < 4; i++) sts128(dst + (r * 4 + i) * 2048, f[i][0], f[i][1], f[i][2], f[i][3]);
    }
    __syncwarp();
  }
}

namespace tl {
constexpr uint32_t FULL = 225280, EMPTY = FULL + 56;
#define TSL0 10
constexpr int RT0 = 13, SL0 = TSL0;
}
DEVI uint32_t fresh_tid() { uint32_t t; asm volatile("mov.u32 %0, %%tid.x;" : "=r"(t)); return t; }
DEVI int fresh_cta() { uint32_t t; asm volatile("mov.u32 %0, %%ctaid.x;" : "=r"(t)); const uint32_t h = t * 86 >> 8; return (t - h * 3) * 32 + h; }
DEVI void ldcg128(uint32_t (&r)[4], const void* p) { asm volatile("ld.global.cg.v4.u32 {%0,%1,%2,%3}, [%4];" : "=r"(r[0]), "=r"(r[1]), "=r"(r[2]), "=r"(r[3]) : "l"(p) : "memory"); }
#define TNST 3
#define TCV 0
#define TPOS 2
DEVI void tail_load(uint32_t sb, Sync* sy, const CUtensorMap* moa, const CUtensorMap* mwo, int layer) {
  using namespace tl;
  (void)layer;
  const int i = fresh_cta(), a = i & 3, b = (i & 31) >> 2, rt = RT0 + (i >> 5);
  const bool last = rt == 15;
  const int nst = last ? 7 : TNST, npre = last ? 7 : 0;
  const uint32_t ab = last ? 8192 : 16384, stage = ab + 20480;
#pragma unroll 1
  for (int g = 0; g < npre; g++) { mbar_expect(sb + FULL + g * 8, stage); tma3d(sb + g * stage + ab, mwo, 0, (b * 12 + g) * 64, a * 5, sb + FULL + g * 8); }
  spin_count(&sy->o[rt * 16 + b], last ? 4 : 8);
  if (!last) XT(i, 0);
  fence_flag_to_bulk();
  int st = 0, par = 1;
#pragma unroll 1
  for (int g = 0; g < (last ? 24 : 12); g++) {
    const uint32_t dst = sb + st * stage, fb = sb + FULL + st * 8;
    const int k = (b * 12 + (g < 12 ? g : g < 19 ? g - 7 : g - 19)) * 64;
    if (g == 12) { spin_count(&sy->o[15 * 16 + 8 + b], 4); XT(i, 0); fence_flag_to_bulk(); }
    if (g >= npre) {
      mbar_wait_long(sb + EMPTY + st * 8, par);
      mbar_expect(fb, g >= 12 && g < 19 ? ab : stage);
      if (g < 12 || g >= 19) tma3d(dst + ab, mwo, 0, k, a * 5, fb);
    }
    tma2d(dst, moa, k, rt * 128 + (g >= 12) * 64, fb);
    if (!last) tma2d(dst + 8192, moa, k, rt * 128 + 64, fb);
    if (++st == nst) { st = 0; par ^= 1; }
  }
}
DEVI void tail_sum(uint32_t sb, Sync* sy, const bf16* __restrict__ xin, int layer) {
  using namespace tl;
  const int ct = fresh_tid(), lane = ct & 31, cw = __shfl_sync(0xffffffffu, ct >> 7, 0), w = ct >> 5 & 3;
  const int i = TCV ? __shfl_sync(0xffffffffu, fresh_cta(), 0) : blockIdx.x % 3 * 32 + blockIdx.x / 3, a = i & 3, b = (i & 31) >> 2, rt = RT0 + (i >> 5);
  const bool last = rt == 15;
  const uint32_t nst = last ? 7 : TNST, stage = last ? 28672 : 36864, ao = last ? 0 : cw * 8192, bo = stage - 20480, ost = sb + (last ? 200704 : 184320 + cw * 20480);
  float d[80];
#pragma unroll
  for (int n = 0; n < 80; n++) d[n] = 0.f;
  bar_sync(14, 288);
  if (last && cw) bar_sync(6, 256);
  uint32_t st = last && cw ? 5 : 0, par = last && cw, prev = 0;
#pragma unroll 1
  for (int c = 0; c < 12; c++) {
    mbar_wait_long(sb + FULL + st * 8, par);
    if (c == 0 && ct == 128) XT(i, 1);
    const uint64_t da = mkdesc(sb + st * stage + ao, 16, 1024, 1), db = mkdesc(sb + st * stage + bo, 4096, 512, 2);
    wg_fence();
#pragma unroll
    for (int k = 0; k < 4; k++) wgmma_n160_nt(d, da + k * 2, db + k * 64, c | k);
    wg_commit();
    if (c > 0) { wg_wait<1>(); if (lane == 0) mbar_arrive(prev); }
    prev = sb + EMPTY + st * 8;
    if (++st == nst) { st = 0; par ^= 1; }
  }
  if (last && !cw) bar_arrive(6, 256);
  const int rl = last ? cw * 64 + b * 8 + (ct >> 4 & 7) : b * 16 + (ct >> 4), q = ct & 15, r = rt * 128 + rl;
  const int c0 = r * DM + a * 160 + q * 8, c1 = c0 + 128 - (q & 12) * 8;
  uint32_t u[9][2][4];
  ldcg128(u[8][0], xin + c0); ldcg128(u[8][1], xin + c1);
  if (last && cw) bar_sync(5, 256);
  wg_wait<0>();
  if (lane == 0) mbar_arrive(prev);
  const uint32_t orow = w * 16 + (lane & 15), ob = ost + orow * 64;
#pragma unroll
  for (int n = 0; n < 10; n++)
    stsm4(ob + (n >> 1) * 4096 + ((((n & 1) * 2 + (lane >> 4)) ^ ((orow >> 1) & 3)) << 4), pack_bf16(d[8 * n], d[8 * n + 1]), pack_bf16(d[8 * n + 2], d[8 * n + 3]),
          pack_bf16(d[8 * n + 4], d[8 * n + 5]), pack_bf16(d[8 * n + 6], d[8 * n + 7]));
  fence_async();
  bar_sync(7 + cw, 128);
  const int sl0 = SL0 * 8 + (rt - RT0) * 64 + a * 16;
  if ((ct & 127) == 0) {
    bulk_store(g_sl + (size_t)(sl0 + cw * 8 + b) * 10240, ost, 20480);
    asm volatile("cp.async.bulk.commit_group; cp.async.bulk.wait_group 0;" ::: "memory");
    XT(i, 2 + cw);
    publish_bulk<WFEN>(&sy->wcnt[(rt * 4 + a) * 2 + cw]);
  }
  if ((ct & 127) == 32) spin_count(&sy->wcnt[(rt * 4 + a) * 2 + (rl >> 6)], 8);
  __syncwarp();
  bar_sync(7 + cw, 128);
  const bf16* sl = g_sl + (size_t)(sl0 + (rl >> 6) * 8) * 10240 + (rl & 63) * 32 + (((q & 3) ^ (rl >> 1 & 3)) << 3);
#pragma unroll
  for (int n = 0; n < 8; n++) { ldcg128(u[n][0], sl + n * 10240 + (q >> 2) * 2048); ldcg128(u[n][1], sl + n * 10240 + 8192); }
  if (last && !cw) bar_arrive(5, 256);
  if (ct == 128 && last) XT(128 + (i & 31), 0);
  sched_fence(layer >> 4);
  const uint32_t id = (lane >> 2) == (lane & 3) * 2 ? 0x3F80u : (lane >> 2) == (lane & 3) * 2 + 1 ? 0x3F800000u : 0u;
  float y[4][4], s1 = 0.f, s2 = 0.f;
#pragma unroll
  for (int e = 0; e < 16; e++) y[e >> 2][e & 3] = 0.f;
#pragma unroll
  for (int n = 0; n < 9; n++)
#pragma unroll
    for (int m = 0; m < 2; m++) { mma16816(y[2 * m], u[n][m], id, 0u); mma16816(y[2 * m + 1], u[n][m], 0u, id); }
#pragma unroll
  for (int m = 0; m < 2; m++) {
    const bool on = !m || q < 4;
    uint32_t z[4];
    float t1 = 0.f, t2 = 0.f;
#pragma unroll
    for (int e = 0; e < 4; e++) {
      z[e] = pack_bf16(y[2 * m + (e >> 1)][(e & 1) * 2], y[2 * m + (e >> 1)][(e & 1) * 2 + 1]);
      const float lo = __uint_as_float(z[e] << 16), hi = __uint_as_float(z[e] & 0xFFFF0000u);
      t1 += lo + hi; t2 = fmaf(lo, lo, fmaf(hi, hi, t2));
    }
    if (on) { s1 += t1; s2 += t2; }
    asm volatile("{.reg .pred p; setp.ne.u32 p, %5, 0; @p st.global.v4.u32 [%0], {%1,%2,%3,%4};}"
                 :: "l"(g_xa + (m ? c1 : c0)), "r"(z[0]), "r"(z[1]), "r"(z[2]), "r"(z[3]), "r"((uint32_t)on) : "memory");
  }
#pragma unroll
  for (int o = 1; o < 16; o <<= 1) { s1 += __shfl_xor_sync(0xffffffffu, s1, o); s2 += __shfl_xor_sync(0xffffffffu, s2, o); }
  asm volatile("{.reg .pred p; setp.ne.u32 p, %3, 0; @p red.relaxed.gpu.global.add.v2.f32 [%0], {%1,%2};}"
               :: "l"(&sy->rstat[r]), "f"(s1), "f"(s2), "r"((uint32_t)(q == 0)) : "memory");
  if (ct == 128 && last) XT(128 + (i & 31), 1);
  if (BFL) {
    bar_sync(7 + cw, 128);
    if ((ct & 127) == 0) red_release(&sy->pro[1 + rt - RT0]);
    if (ct == 128 && last) XT(128 + (i & 31), 2);
    __syncwarp();
  }
}

__global__ void __cluster_dims__(3, 1, 1) __launch_bounds__(384, 1)
chain_kernel(const __grid_constant__ CUtensorMap mq, const __grid_constant__ CUtensorMap mk, const __grid_constant__ CUtensorMap mv,
             const __grid_constant__ CUtensorMap mo, const __grid_constant__ CUtensorMap mx, const bf16* __restrict__ mem0, const bf16* __restrict__ xin, uint32_t zero, int layer
             , const __grid_constant__ CUtensorMap moa, const __grid_constant__ CUtensorMap mwo
             ) {
  using namespace ch;
  extern __shared__ __align__(1024) uint8_t smraw[];
  const uint32_t sb = smem_u32(smraw);
  const int tid = threadIdx.x;
  const int wg = __shfl_sync(0xffffffffu, tid >> 7, 0), w = __shfl_sync(0xffffffffu, (tid >> 5) & 3, 0);
  int h, j;
  asm("mov.u32 %0, %%clusterid.x;" : "=r"(h));
  asm("mov.u32 %0, %%cluster_ctarank;" : "=r"(j));
  h = __shfl_sync(0xffffffffu, h, 0); j = __shfl_sync(0xffffffffu, j, 0);
  const int T0 = j == 0 ? 0 : (j == 1 ? 14 : 27), NT = j == 0 ? 14 : 13;
  const uint32_t PD = PD_, XD = XD_, X1D = X1D_;
  constexpr uint32_t CS = 0, UP = 0, DMIN = 0, FL = 0, SD = 0;

  if (tid == 0) {
    mbar_init(sb + BAR_W1, 1); mbar_init(sb + BAR_W2, 1); mbar_init(sb + BAR_X0, 1); mbar_init(sb + BAR_X1, 1);
    mbar_init(sb + BAR_S, 6); mbar_init(sb + BAR_O, 1); mbar_init(sb + BAR_WK, 1); mbar_init(sb + BAR_XF, 12);
    for (int i = 0; i < 14; i++) mbar_init(sb + PB + i * 8, 1);
    sts64(sb + WMX, 0, 0);
    asm volatile("fence.mbarrier_init.release.cluster;" ::: "memory");
    mbar_expect(sb + BAR_W2, 81920);
    mbar_expect(sb + BAR_S, 1280); mbar_expect(sb + BAR_O, 2048);
  }
  asm volatile("griddepcontrol.launch_dependents;");
  GT(0, 0);
  __syncthreads();
  asm volatile("barrier.cluster.arrive.relaxed.aligned;" ::: "memory");
  asm volatile("barrier.cluster.wait.aligned;" ::: "memory");
  if (tid == 0) PT(0, 0);
  const char* arb = (const char*)g_ar;
  const uint32_t xdesc = desc_lo(sb + XB, 16);

  if (wg < 2) {
    asm volatile("setmaxnreg.inc.sync.aligned.u32 208;");
    chain_prepare(xin);
    bar_arrive(9, 352);
    uint32_t W[160];
    load_weights(W, sb, wg, w, j, layer);
    float inv_sc = 1.0f;
    if (wg == 0) {
      const uint32_t lane = lane_id();
      code_pad<PAD0>(zero);
      mbar_wait_long(sb + BAR_X0, 0);
      if (tid == 0) PT(0, 12);
      if (LSH == 1) bar_sync(8, 256);
      if (!LSH) {
        tokens_finish<false>(sb, W, xdesc, w, lane, 0, &mx);
        if (tid == 0) PT(0, 13);
        if (!KS2) bar_arrive(8, 256);
        arrange_wq(sb, 0, w, layer);
      }
#pragma unroll 1
      for (int s = LSH ? -1 : 0; s < NSEG; s++) {
        float sc = 1.0f;
        if (!LSH || s >= 0) {
        uint32_t A0[2];
        {
          float q[4], k[4], v[4];
          const uint32_t ln = opq(lane), t16 = w * 512 + ln * 16;
          uint32_t f[NF][4], wq = sb + WQ + (WQR ? t16 : afrag_off(w, ln)), ba = sb + MEMB + ln * 16;
          proj_stage(f, wq);
          PIN(ba);
          proj_mem<0>(q, k, v, f, W, wq, ba, sb, w, s);
          const uint32_t qd = sb + QS + w * 256 + ln * 4;
          sts32(qd, pack_bf16(q[0] * inv_sc, q[1] * inv_sc)); sts32(qd + 128, pack_bf16(q[2] * inv_sc, q[3] * inv_sc));
          sts32(qd + 2048, pack_bf16(k[0] * inv_sc, k[1] * inv_sc)); sts32(qd + 2048 + 128, pack_bf16(k[2] * inv_sc, k[3] * inv_sc));
          sts128(sb + EX + t16, __float_as_uint(k[0]), __float_as_uint(k[1]), __float_as_uint(k[2]), __float_as_uint(k[3]));
          E1(1, __float_as_uint(v[0]) ^ __float_as_uint(q[0]));
          uint32_t qa = sb + QS + ((ln >> 3) & 1) * 1024 + ((ln >> 4) * 8 + (ln & 7)) * 16;
          PIN(qa);
          TS(0);
          bar_sync(2, 384);
          if (w == 3 && s < NSEG - 1) {
            uint32_t b0[4], b1[4], c0[4], c1[4];
            const uint32_t ka = sb + KP + ln * 16;
            ldsm4t(b0, ka); ldsm4t(c0, ka + 1024); ldsm4t(b1, ka + 512); ldsm4t(c1, ka + 1536);
#pragma unroll
            for (int i = 0; i < 4; i++) { b0[i] = add_bf16x2(b0[i], c0[i]); b1[i] = add_bf16x2(b1[i], c1[i]); }
            score_tile(sb, qa, b0, b1, Peers(sb, j), SX + j * 640 + ln * 4, ln);
          }
          uint32_t e[4];
          lds128(e, sb + EX + 2048 + t16);
          A0[0] = pack_bf16((v[0] + __uint_as_float(e[0])) * inv_sc, (v[1] + __uint_as_float(e[1])) * inv_sc);
          A0[1] = pack_bf16((v[2] + __uint_as_float(e[2])) * inv_sc, (v[3] + __uint_as_float(e[3])) * inv_sc);
          const uint32_t slab = slab_off(VT, w, ln);
          sts32(sb + slab, A0[0]); sts32(sb + slab + 640, A0[1]);
          bar_arrive(12, 384);
        }
        if (s == NSEG - 1) break;
        {
          const uint32_t ln = opq(lane);
          const uint32_t va = sb + VT + (16 * w + (ln & 15)) * 80 + 16 + (ln >> 4) * 16;
          const uint32_t sa = sb + SX + ln * 4, off = OB + w * 256 + ln * 4;
          const Peers pe(sb, j);
          uint32_t f1[4], f2[4];
          ldsm4(f1, va); ldsm4(f2, va + 32);
          TSX(TS(1));
          mbar_wait(sb + BAR_S, s & 1);
          TS(2);
          uint32_t u[3][5];
#pragma unroll
          for (int i = 0; i < 15; i++) u[i / 5][i % 5] = lds32(sa + (i % 5) * 128 + (i / 5) * 640);
          E1(2, u[0][0]);
          sched_fence(zero);
          uint32_t hs[5];
#pragma unroll
          for (int i = 0; i < 5; i++) hs[i] = hadd2(hadd2(u[0][i], u[1][i]), u[2][i]);
          uint32_t m2 = hmax2(hmax2(hmax2(hs[0], hs[1]), hmax2(hs[2], hs[3])), hs[4]);
          asm volatile("bar.arrive 13, 384;" : "+r"(m2) :: "memory");
          m2 = hmax2(m2, __byte_perm(m2, 0, 0x1032));
          m2 = hmax2(m2, __shfl_xor_sync(0xffffffffu, m2, 1));
          m2 = hmax2(m2, __shfl_xor_sync(0xffffffffu, m2, 2));
          TSX(TSD(3, m2));
          const float m4 = -4.0f * __low2float(*reinterpret_cast<__half2*>(&m2));
          uint32_t P[5];
#pragma unroll
          for (int i = 0; i < 5; i++) {
            const float2 x = __half22float2(*reinterpret_cast<__half2*>(&hs[i]));
            P[i] = pack_bf16(ex2(fmaf(x.x, 4.0f, m4)), ex2(fmaf(x.y, 4.0f, m4)));
          }
          float o[4] = {0.f, 0.f, 0.f, 0.f}, o2[4] = {0.f, 0.f, 0.f, 0.f}, o3[4] = {0.f, 0.f, 0.f, 0.f};
          mma16816(o2, f1, P[1], P[2]); mma1688(o, A0[0], A0[1], P[0]); mma16816(o3, f2, P[3], P[4]);
          const uint32_t w0 = pack_bf16((o[0] + o2[0]) + o3[0], (o[1] + o2[1]) + o3[1]), w1 = pack_bf16((o[2] + o2[2]) + o3[2], (o[3] + o2[3]) + o3[3]);
#pragma unroll
          for (int r = 0; r < 2; r++) { st_async32(pe.a[r] + off + (2 - r) * 1024, w0, pe.a[r] + BAR_O); st_async32(pe.a[r] + off + (2 - r) * 1024 + 128, w1, pe.a[r] + BAR_O); }
          E1(3, w0 ^ w1);
          sts32(sb + off, w0); sts32(sb + off + 128, w1);
          if (w == 3) {
            float z[4] = {0.f, 0.f, 0.f, 0.f}, z2[4] = {0.f, 0.f, 0.f, 0.f};
            const uint32_t one[4] = {0x3F803F80u, 0x3F803F80u, 0x3F803F80u, 0x3F803F80u};
            mma1688(z, one[0], one[1], P[0]); mma16816(z2, one, P[1], P[2]); mma16816(z, one, P[3], P[4]);
            if (ln < 4) sts64(sb + INV + ln * 8, __float_as_uint(rcp(z[0] + z2[0])), __float_as_uint(rcp(z[1] + z2[1])));
          }
          TS(4);
        }
        if (12 + w < NT) {
          const uint32_t ln = opq(lane);
          const char* pr = arb + ar_tile_off(T0 + 12 + w) + ln * 4; const char* px = arb + ar_extra_off(T0 + 12 + w);
          PINL(pr);
          wo_tile_smem<true>(sb, sb + WOF + (4 + w) * 6144 + ln * 16, sb + OB + ln * 16, s & 1, pr, px, ln == 31, sc);
        } else {
          bar_sync(9, 384);
          sc = __uint_as_float(lds32(sb + MX + 16));
          if (w == 3 && lane == 0) {
            mbar_expect(sb + BAR_S, 1280);
            if (!KS2 && !X1E && j == 1 && s + 2 < NSEG) {
              mbar_wait(sb + BAR_XF, s & 1);
              tma3d_mc(sb + XB + 20480, &mx, 0, (s + 2) * SEG, 5, sb + BAR_X1, 7);
            }
            mbar_wait(sb + BAR_O, s & 1);
            mbar_expect(sb + BAR_O, 2048);
          }
          __syncwarp();
        }
        TSX(TS(5));
        if (w == 1) SS(0);
        mbar_wait(sb + BAR_X0, (s + 1) & 1);
        if (w == 1) SS(1);
        bar_sync(4, 384);
        if (w == 1) SS(2);
        arb += AR_STEP_BYTES;
        }
        tokens_finish<true>(sb, W, xdesc, w, lane, s);
        TS(6);
        if (LSH && s < 0) {
          if (tid == 0) PT(0, 13);
          arrange_wq(sb, 0, w, layer);
        }
        inv_sc = __uint_as_float(0x7F000000u - __float_as_uint(sc));
      }
    } else {
      const uint32_t lane = lane_id();
      static_assert(!X0E && !KS2, "prologue");
      code_pad<PAD1>(zero);
#pragma unroll 1
      for (int pass = 0; pass < (LSH ? 1 : 2); pass++) {
        mbar_wait_long(sb + BAR_X1, pass);
        if (pass) bar_sync(8, 256);
        tokens_partial<0>(sb, PK, W, xdesc, w, lane);
        if (pass) break;
        mbar_wait(sb + BAR_X1, 0);
        tokens_partial<0>(sb, QS, W + 80, xdesc, w, lane);
        bar_sync(8, 256);
      }
      if (LSH) {
        if (w == 3 && lane == 0) { mbar_expect(sb + BAR_X1, 20480); tma3d(sb + XB + 20480, &mx, 0, SEG, 5, sb + BAR_X1); }
        __syncwarp();
      } else {
        if (tid == 128) PT(0, 14);
        arrange_wq(sb, 1, w, layer);
      }
#pragma unroll 1
      for (int s = LSH ? -1 : 0; s < NSEG; s++) {
        float sc = 1.0f;
        if (!LSH || s >= 0) {
        {
          float q[4], k[4], v[4];
          const uint32_t ln = opq(lane), t16 = w * 512 + ln * 16;
          uint32_t f[NF][4], wq = sb + WQ + 40960 + (WQR ? t16 : afrag_off(w, ln)), ba = sb + MEMB + 5120 + ln * 16;
          proj_stage(f, wq);
          PIN(ba);
          proj_mem<1>(q, k, v, f, W, wq, ba, sb, w, s);
          const uint32_t qd = sb + QS + 1024 + w * 256 + ln * 4;
          sts32(qd, pack_bf16(q[0] * inv_sc, q[1] * inv_sc)); sts32(qd + 128, pack_bf16(q[2] * inv_sc, q[3] * inv_sc));
          sts32(qd + 2048, pack_bf16(k[0] * inv_sc, k[1] * inv_sc)); sts32(qd + 2048 + 128, pack_bf16(k[2] * inv_sc, k[3] * inv_sc));
          sts128(sb + EX + 2048 + t16, __float_as_uint(v[0]), __float_as_uint(v[1]), __float_as_uint(v[2]), __float_as_uint(v[3]));
          TSX(TS(0));
          bar_sync(2, 384);
          uint32_t e[4];
          lds128(e, sb + EX + t16);
          const uint32_t slab = slab_off(KT, w, ln);
          sts32(sb + slab, pack_bf16((k[0] + __uint_as_float(e[0])) * inv_sc, (k[1] + __uint_as_float(e[1])) * inv_sc));
          sts32(sb + slab + 640, pack_bf16((k[2] + __uint_as_float(e[2])) * inv_sc, (k[3] + __uint_as_float(e[3])) * inv_sc));
        }
        if (s == NSEG - 1) { bar_arrive(12, 384); break; }
        if (w == 1) SS(3);
        if (KS2) mbar_wait(sb + BAR_X1, (s + 1) & 1);
        if (w == 1) SS(4);
        if (VL) {
          bar_arrive(12, 384); bar_arrive(13, 384);
          bar_sync(9, 384);
          tokens_partial<3>(sb, QS, W + 80, xdesc, w, lane);
        } else {
          bar_sync(5, 288);
          TSX(TS(1));
          tokens_partial<1>(sb, QS, W + 80, xdesc, w, lane);
        }
        if (!KS2 && X1E && j == 1 && w == 3 && s + 2 < NSEG) {
          if (opq(lane) == 0) {
            mbar_wait(sb + BAR_XF, s & 1);
            tma3d_mc(sb + XB + 20480, &mx, 0, (s + 2) * SEG, 5, sb + BAR_X1, 7);
          }
          __syncwarp();
        }
        TS(2);
        {
          const uint32_t ln = opq(lane);
          const char* pr = arb + ar_tile_off(T0 + 8 + w) + ln * 4; const char* px = arb + ar_extra_off(T0 + 8 + w);
          PINL(pr);
          wo_tile_smem<!VL>(sb, sb + WOF + w * 6144 + ln * 16, sb + OB + ln * 16, s & 1, pr, px, ln == 31, sc);
        }
        if (KS2) bar_sync(4, 384);
        else if (KORD) {
          if (s + 2 < NSEG) mbar_wait(sb + BAR_X1, s & 1);
          bar_sync(4, 384);
        } else {
          bar_arrive(4, 384);
        }
        arb += AR_STEP_BYTES;
        }
        if (!KS2 && !KORD) {
          if (s + 2 < NSEG) { if (LSH && s < 0) mbar_wait_long(sb + BAR_X1, 1); else mbar_wait(sb + BAR_X1, s & 1); }
          bar_sync(6, 256);
        }
        tokens_partial<2>(sb, PK, W, xdesc, w, lane);
        if (LSH && s < 0) {
          if (tid == 128) PT(0, 14);
          arrange_wq(sb, 1, w, layer);
        }
        if (X0E && j == 0 && w == 2 && s + 2 < NSEG) {
          if (opq(lane) == 0) {
            mbar_wait(sb + BAR_XF, (s + 1) & 1);
            const uint32_t t9 = clk32();
            while (clk32() - t9 < X0D_) {}
            tma3d_mc(sb + XB, &mx, 0, (s + 2) * SEG, 0, sb + BAR_X0, 7);
          }
          __syncwarp();
        }
        if (KS2 && j == 1 && w == 0 && s + 2 < NSEG) {
          if (opq(lane) == 0) {
            mbar_wait(sb + BAR_XF, s & 1);
            tma3d_mc(sb + XB + 20480, &mx, 0, (s + 2) * SEG, 5, sb + BAR_X1, 7);
          }
          __syncwarp();
        }
        TS(4);
        inv_sc = __uint_as_float(0x7F000000u - __float_as_uint(sc));
      }
    }
    asm volatile("barrier.cluster.arrive.relaxed.aligned;" ::: "memory");
    tail_sum(sb, &g_sync[layer], xin, layer);
  } else {
    asm volatile("setmaxnreg.dec.sync.aligned.u32 88;");
    const uint32_t lane = lane_id();
    uint32_t W[44];
    if (tid - 256 < 80) asm volatile("prefetch.global.L2 [%0];" :: "l"(mem0 + (tid - 256) * 64) : "memory");
    if (w == 3) {
      if (layer && LNF == 1) bar_sync(10, 64);
      const int win = layer ? PWIN1 : PWIN;
#pragma unroll
      for (int part = 0; part < 2; part++) {
        if (lane == 0) {
#pragma unroll
          for (int i = part ? 2 : 0; i < (part ? 14 : 2); i++) {
            const uint32_t bar = sb + PB + i * 8;
            if (i >= win) mbar_wait_long(bar - win * 8, 0);
            if (i == 12) mbar_wait_long(sb + BAR_W1, 0);
            if (i < 5 || (i >= 7 && i < 12)) {
              mbar_expect(bar, 16384);
              if (i < 5) tma2d(sb + 81920 + i * 16384, &mv, h * DH + 64 * j, i * 128, bar);
              else tma2d(sb + (i - 7) * 16384, &mk, h * DH + 64 * j, (i - 7) * 128, bar);
            } else {
              const int bx = i < 7 ? i - 4 : (i - 12) * 3;
              mbar_expect(bar, 24576);
              tma2d(bx < 3 ? sb + WOSTAGE + bx * 24576 : sb + WOF, &mo, T0 * 16 + 64 * bx, h * DH, bar);
            }
          }
        }
        __syncwarp();
        if (part == 0 && layer && LNF == 2) bar_sync(10, 64);
      }
      if (lane == 0) {
        mbar_wait_long(sb + BAR_WK, 0);
        for (int i = 0; i < 2; i++) tma2d(sb + WQ + i * 16384, &mq, h * DH + 64 * j, i * 128, sb + BAR_W2);
      }
      __syncwarp();
    } else {
      chain_prepare(xin);
      for (int i = blockIdx.x * 96 + tid - 256; i < (NSEG - 1) * 24 * 32; i += 96 * 96) ((uint4*)g_ar)[(i >> 5) * 64 + (i & 31)] = make_uint4(0, 0, 0, 0);
      bar_sync(9, 352);
    }
    PT(0, 1);
    if (w == 0) {
      if (lane == 0) {
        if (layer) sts32(sb + MX + 24, __ldcg(&g_kw));
        red_release(&g_sync[layer].pro[0]);
      }
      PT(0, 2);
      __syncwarp();
      if (layer && LNF) bar_arrive(10, 64);
    }
    if (!(PSPL && layer) && tid == 256) spin_count(&g_sync[layer].pro[0], 96);
    __syncwarp();
    PT(0, 3);
    mbar_wait_long(sb + PB + 5 * 8, 0); mbar_wait_long(sb + PB + 12 * 8, 0);
    PT(0, 4);
    {
      const int i = lane >> 3, r = lane & 7;
      uint32_t m = 0;
#pragma unroll
      for (int kk = 0; kk < 12; kk++)
#pragma unroll
        for (int tt = 0; tt < 2; tt++) {
          const int tl = 2 * w + tt;
          const uint32_t src = sb + WOSTAGE + (tl >> 2) * 24576 + (((kk + 4 * j) % 12) * 16 + (i >> 1) * 8 + r) * 128 + ((((tl & 3) * 2 + (i & 1)) ^ r) << 4);
          const int q = kk * 2 + tt;
          if (q >= 13) { ldsm4t_p(&W[(q - 13) * 4], src); m = mag4(m, &W[(q - 13) * 4]); }
          else { uint32_t f[4]; ldsm4t(f, src); sts128(sb + (q < 12 ? WOF2 + (w * 12 + q) * 512 : WOF3 + w * 512) + lane * 16, f[0], f[1], f[2], f[3]); m = mag4(m, f); }
        }
      publish_max(sb + WMX + 4, m);
    }
    bar_sync(7, 384);
    PT(0, 5);
    if (tid == 256 && !layer) {
      const float2 mm = lds64f(sb + WMX);
      asm volatile("st.relaxed.gpu.global.u32 [%0], %1;" :: "l"(&g_sync[layer].wmax[blockIdx.x]), "r"(0x10000u | (__float_as_uint(mm.x) >> 7 << 8) | (__float_as_uint(mm.y) >> 7)) : "memory");
    }
    uint32_t m0[3][8];
#pragma unroll
    for (int i = 0; i < 24; i++) m0[i >> 3][i & 7] = __ldg((const uint32_t*)(mem0 + (i & 7) * DM) + min(tid - 256 + (i >> 3) * 128, DM / 2 - 1));
    if (tid == 352) {
      if (PSPL && layer) spin_count(&g_sync[layer].pro[0], 96);
      if (XFEN == 0) asm volatile("fence.proxy.async;" ::: "memory");
      if (XFEN == 1) asm volatile("fence.proxy.async.global;" ::: "memory");
      mbar_expect(sb + BAR_X1, 20480); tma3d(sb + XB + 20480, &mx, 0, 0, 5, sb + BAR_X1);
      mbar_expect(sb + BAR_X0, 20480); tma3d(sb + XB, &mx, 0, 0, 0, sb + BAR_X0);
      for (int i = 2; i < 5; i++) tma2d(sb + WQ + i * 16384, &mq, h * DH + 64 * j, i * 128, sb + BAR_W2);
    }
    __syncwarp();
    bar_sync(7, 384);
    PT(0, 6);
    uint32_t wv[3];
    if (w == 0 && !layer)
#pragma unroll
      for (int i = 0; i < 3; i++) asm volatile("ld.relaxed.gpu.global.u32 %0, [%1];" : "=r"(wv[i]) : "l"(&g_sync[layer].wmax[lane + i * 32]) : "memory");
    {
      int em;
      uint32_t m = 0;
#pragma unroll
      for (int i = 0; i < 3; i++) {
        const int p = tid - 256 + i * 128;
        if (p < DM / 2) {
          uint32_t lo[4], hi[4];
#pragma unroll
          for (int q = 0; q < 4; q++) { lo[q] = __byte_perm(m0[i][2 * q], m0[i][2 * q + 1], 0x5410); hi[q] = __byte_perm(m0[i][2 * q], m0[i][2 * q + 1], 0x7632); }
          sts128(sb + MEMB + p * 32, lo[0], lo[1], lo[2], lo[3]); sts128(sb + MEMB + p * 32 + 16, hi[0], hi[1], hi[2], hi[3]);
        }
#pragma unroll
        for (int q = 0; q < 8; q++) m = __vmaxu2(m, m0[i][q] & 0x7FFF7FFFu);
      }
      em = __reduce_max_sync(0xffffffffu, (int)(max(m & 0xFFFFu, m >> 16) >> 7) - 126);
      if (lane == 0) sts32(sb + MX + w * 4, em);
    }
    PT(0, 7);
    bar_arrive(1, 384);
    bar_sync(3, 384);
    if (w == 0 && !layer) {
      for (int n = 0; n < 4000000 && !__all_sync(0xffffffffu, (wv[0] & wv[1] & wv[2]) >> 16); n++) {
#pragma unroll
        for (int i = 0; i < 3; i++) asm volatile("ld.relaxed.gpu.global.u32 %0, [%1];" : "=r"(wv[i]) : "l"(&g_sync[layer].wmax[lane + i * 32]) : "memory");
      }
      const int ev = __reduce_max_sync(0xffffffffu, max(max(wv[0] >> 8 & 255, wv[1] >> 8 & 255), wv[2] >> 8 & 255));
      const int eo = __reduce_max_sync(0xffffffffu, max(max(wv[0] & 255, wv[1] & 255), wv[2] & 255));
      if (lane == 0) {
        sts32(sb + MX + 24, 245 - ev - eo);
        if (blockIdx.x == 0) g_kw = 245 - ev - eo;
      }
      __syncwarp();
    }
    int dly = PD;
    PT(0, 8);
    for (int s = 0; s < NSEG; s++) {
      const uint32_t t0 = clk32();
      TS(0);
      {
        uint32_t b0[4], b1[4];
        const uint32_t ln = opq(lane);
        const uint32_t ka = sb + KT + ln * 80 + (1 + w) * 16;
        ldsm4t(b0, ka); ldsm4t(b1, ka + 2560);
        if (w == 0 && ln == 0 && s + 1 < NSEG) {
          if (!X0E && j == 0) {
            mbar_wait(sb + BAR_XF, s & 1);
            while (clk32() - t0 < XD) {}
            tma3d_mc(sb + XB, &mx, 0, (s + 1) * SEG, 0, sb + BAR_X0, 7);
          }
          if (s + 2 < NSEG - 1 && !(FL & 2)) asm volatile("prefetch.global.L2 [%0];" :: "l"(arb + 2 * AR_STEP_BYTES + ar_line_off(h * 3 + j)) : "memory");
          if (PFW && layer == 0 && s >= PFW && s < PFW + 10) tma2d_prefetch(s & 1 ? &mk : &mv, h * DH + 64 * j, ((s - PFW) >> 1) * 128);
          if (j == 2 && h == (s & 31) && s + 3 < NSEG) { tma3d_prefetch(&mx, 0, (s + 3) * SEG, 0); tma3d_prefetch(&mx, 0, (s + 3) * SEG, 5); }
        }
        __syncwarp();
        uint32_t qa = sb + QS + ((ln >> 3) & 1) * 1024 + ((ln >> 4) * 8 + (ln & 7)) * 16, off = SX + j * 640 + (1 + w) * 128 + ln * 4;
        PIN(qa); PIN(off);
        bar_sync(2, 384);
        if (s == NSEG - 1) break;
        score_tile(sb, qa, b0, b1, Peers(sb, j), off, ln);
        bar_sync(12, 384);
        if (SD) bar_sync(13, 384);
        if (w == 1 && ln == 0 && !(FL & 1)) {
          store_slabs(sb, s, h, j);
        }

        __syncwarp();
      }
      if (w == 0) {
        uint32_t v[4]; lds128(v, sb + MX);
        const int kw = lds32(sb + MX + 24);
        const int em = max(max(max((int)v[0], (int)v[1]), max((int)v[2], (int)v[3])), 1);
        const int e = min(max(kw - em, -120), 120);
        if (opq(lane) == 0) { sts32(sb + MX + 16, (uint32_t)(e + 127) << 23); sts32(sb + MX + 20, 0u); }
      }
      if (!SD) bar_sync(13, 384);
      uint32_t tref;
      {
        float c0[4] = {0.f, 0.f, 0.f, 0.f}, c1[4] = {0.f, 0.f, 0.f, 0.f}, d0[4] = {0.f, 0.f, 0.f, 0.f}, d1[4] = {0.f, 0.f, 0.f, 0.f};
        uint32_t f[4][4], b[2][4];
        const uint32_t ln = opq(lane);
        const uint32_t fa = sb + WOF2 + w * 6144 + ln * 16, ob = sb + OB + ln * 16;
#pragma unroll
        for (int i = 0; i < 4; i++) lds128(f[i], fa + i * 512);
        if (w == 1) SS(5);
        asm volatile("cp.async.bulk.wait_group.read 0;" ::: "memory");
        if (w == 1) SS(6);
        bar_sync(9, 384);
        ldsm4t(b[0], ob); ldsm4t(b[1], ob + 512);
        mma16816(c0, f[0], b[0][0], b[0][1]); mma16816(c1, f[1], b[0][0], b[0][1]);
        lds128(f[0], fa + 2048); lds128(f[1], fa + 2560);
        mma16816(d0, f[2], b[0][2], b[0][3]); mma16816(d1, f[3], b[0][2], b[0][3]);
        lds128(f[2], fa + 3072); lds128(f[3], fa + 3584);
        mma16816(c0, f[0], b[1][0], b[1][1]); mma16816(c1, f[1], b[1][0], b[1][1]);
        mma16816(d0, f[2], b[1][2], b[1][3]); mma16816(d1, f[3], b[1][2], b[1][3]);
#pragma unroll
        for (int i = 0; i < 4; i++) lds128(f[i], fa + (8 + i) * 512);
        mbar_wait(sb + BAR_O, s & 1);
        ldsm4t(b[0], ob + 1024);
        E1(4, b[0][0]);
        mma16816(c0, f[0], b[0][0], b[0][1]); mma16816(c1, f[1], b[0][0], b[0][1]);
        mma16816(d0, f[2], b[0][2], b[0][3]); mma16816(d1, f[3], b[0][2], b[0][3]);
        ldsm4t(b[0], ob + 1536); lds128(f[0], sb + WOF3 + w * 512 + ln * 16); ldsm4t(f[1], ob + 2048); ldsm4t(f[2], ob + 2560);
        float2 iv = lds64f(sb + INV + (ln & 3) * 8);
        const float sc = __uint_as_float(lds32(sb + MX + 16));
        sched_fence(zero);
        mma16816(c1, &W[0], b[0][0], b[0][1]); mma16816(d0, &W[4], b[0][2], b[0][3]); mma16816(d1, &W[8], b[0][2], b[0][3]);
        mma16816(c0, f[0], b[0][0], b[0][1]);
        const char* pr = arb + ar_tile_off(T0 + 2 * w) + ln * 4;
        PINL(pr);
        iv.x *= sc; iv.y *= sc;
        mma16816(c1, &W[16], f[1][0], f[1][1]); mma16816(d0, &W[20], f[1][2], f[1][3]); mma16816(d1, &W[24], f[1][2], f[1][3]);
        mma16816(c0, &W[12], f[1][0], f[1][1]);
        mma16816(c1, &W[32], f[2][0], f[2][1]); mma16816(d0, &W[36], f[2][2], f[2][3]); mma16816(d1, &W[40], f[2][2], f[2][3]);
        mma16816(c0, &W[28], f[2][0], f[2][1]);
        const uint32_t w2 = pack_f16((c1[0] + d1[0]) * iv.x, (c1[1] + d1[1]) * iv.y), w3 = pack_f16((c1[2] + d1[2]) * iv.x, (c1[3] + d1[3]) * iv.y);
        wo_red(pr + ((T0 & 1) ? 768 : 256), w2, w3, ln == 31);
        const uint32_t w0 = pack_f16((c0[0] + d0[0]) * iv.x, (c0[1] + d0[1]) * iv.y), w1 = pack_f16((c0[2] + d0[2]) * iv.x, (c0[3] + d0[3]) * iv.y);
        E1(5, w0 ^ w2);
        wo_red(pr, w0, w1, ln == 31);
        wo_red_extra_p(arb + ar_extra_off(T0 + 2 * w + 1), w2, w3, ln);
        wo_red_extra_p(arb + ar_extra_off(T0 + 2 * w), w0, w1, ln);
        if (TSYNC) bar_sync(4, 384); else bar_arrive(4, 384);
        tref = clk32();
      }
      TSV(2, tref); TS(3);
      if (w == 1 && opq(lane) == 0) {
        asm volatile("cp.async.bulk.wait_group 0;" ::: "memory");
        publish_bulk<0>(&g_sync[layer].kv[s * NH + h]);
      }
      __syncwarp();
      {
        const uint32_t m = ar_read(arb, sb, w, lane, zero, tref, dly, s);
        dly = lds32(sb + MX + 20) ? dly + (int)UP : max(dly - (int)CS, (int)DMIN);
        if (w == 3) TSV(1, dly);
        const int em = __reduce_max_sync(0xffffffffu, (int)(max(m & 0xFFFFu, m >> 16) >> 10) - 13 + 127 - (int)(lds32(sb + MX + 16) >> 23));
        if (opq(lane) == 0) sts32(sb + MX + w * 4, em);
      }
      arb += AR_STEP_BYTES;
    }
    asm volatile("barrier.cluster.arrive.relaxed.aligned;" ::: "memory");
    if (fresh_tid() >= 352) {
      if (fresh_tid() == 352) {
        asm volatile("prefetch.tensormap [%0];" :: "l"(&mwo) : "memory"); asm volatile("prefetch.tensormap [%0];" :: "l"(&moa) : "memory");
        const uint32_t n = fresh_cta() < 64 ? 8 : 4;
        for (int i = 0; i < 7; i++) { mbar_init(sb + tl::FULL + i * 8, 1); mbar_init(sb + tl::EMPTY + i * 8, n); }
        asm volatile("fence.mbarrier_init.release.cluster;" ::: "memory");
      }
      __syncwarp();
      bar_arrive(14, 288);
    }
    bar_sync(12, 384);
    if (LASTG) {
      bf16* kvp = g_kv + ((size_t)((NSEG - 1) * NH + h) * 2 * DH + 64 * j) * NKEY;
#pragma unroll
      for (int k = 0; k < 5; k++) {
        const int u = k * 128 + tid - 256;
        uint32_t v[4];
        lds128(v, sb + KT + u * 16);
        __stcg((uint4*)(kvp + (u < 320 ? u * 8 : DH * NKEY + (u - 320) * 8)), make_uint4(v[0], v[1], v[2], v[3]));
      }
      bar_sync(10, 128);
      if (tid == 256 + 32) {
        asm volatile("cp.async.bulk.wait_group 0;" ::: "memory");
        red_release(&g_sync[layer].kv[(NSEG - 1) * NH + h]);
        GT(0, 1);
        if (TPOS < 2) tail_load(sb, &g_sync[layer], &moa, &mwo, layer);
      }
      __syncwarp();

    } else if (tid == 256 + 32) {
      store_slabs(sb, NSEG - 1, h, j);
      asm volatile("cp.async.bulk.wait_group 0;" ::: "memory");
      publish_bulk<WFEN>(&g_sync[layer].kv[(NSEG - 1) * NH + h]);
    }
  }
  if (TPOS) {
    const uint32_t t = fresh_tid();
    uint32_t sb2 = smem_u32(smraw);
    if (TPOS == 3) sb2 += zero;
    if (TPOS >= 2 && t == 288) tail_load(sb2, &g_sync[layer], &moa, &mwo, layer);
    __syncwarp();
  }
  asm volatile("barrier.cluster.wait.aligned;" ::: "memory");
}

DEVI void bulk_load(uint32_t dst, const void* g, uint32_t bytes, uint32_t bar) {
  if (EVF & 2) asm volatile("cp.async.bulk.shared::cluster.global.mbarrier::complete_tx::bytes.L2::cache_hint [%0], [%1], %2, [%3], %4;" :: "r"(dst), "l"(g), "r"(bytes), "r"(bar), "l"(stream_policy()) : "memory");
  else asm volatile("cp.async.bulk.shared::cluster.global.mbarrier::complete_tx::bytes [%0], [%1], %2, [%3];" :: "r"(dst), "l"(g), "r"(bytes), "r"(bar) : "memory");
}
DEVI void bulk_load_plain(uint32_t dst, const void* g, uint32_t bytes, uint32_t bar) {
  asm volatile("cp.async.bulk.shared::cluster.global.mbarrier::complete_tx::bytes [%0], [%1], %2, [%3];" :: "r"(dst), "l"(g), "r"(bytes), "r"(bar) : "memory");
}
DEVI void tma3d_store(const CUtensorMap* m, uint32_t src, int c0, int c1, int c2) {
  if (EVF & 4) asm volatile("cp.async.bulk.tensor.3d.global.shared::cta.bulk_group.L2::cache_hint [%0, {%2, %3, %4}], [%1], %5;" :: "l"(m), "r"(src), "r"(c0), "r"(c1), "r"(c2), "l"(stream_policy()) : "memory");
  else asm volatile("cp.async.bulk.tensor.3d.global.shared::cta.bulk_group [%0, {%2, %3, %4}], [%1];" :: "l"(m), "r"(src), "r"(c0), "r"(c1), "r"(c2) : "memory");
}
namespace wk {
constexpr uint32_t STAGE = 40960, NST = 4, OST = NST * STAGE;
constexpr uint32_t MISC = OST + 49152;
constexpr uint32_t FULL = MISC, EMPTY = MISC + 32, TFULL = MISC + 64, TEMPTY = MISC + 80, TASK = MISC + 96;
constexpr uint32_t DONE = MISC + 104, FREE = MISC + 120, DTASK = MISC + 136, FIN = MISC + 144, DSLOT = MISC + 152;
constexpr uint32_t CGO = MISC + 160;
constexpr uint32_t LBAR = MISC + 168, TL = MISC + 176;
constexpr uint32_t SMEM = TL + 5136;
#define NP2 10
constexpr int NZ = 16, NP = NZ + 80 + NP2, NQ = 512;
#define S15 8
#define SPLITS rt < RT_SPLIT ? 1 : rt < 11 ? 2 : rt < 13 ? 4 : rt < 15 ? 8 : S15
__host__ __device__ constexpr int split(int rt) { return SPLITS; }
__host__ __device__ constexpr int count_w(int rt) { return rt < 0 ? 0 : 4 * split(rt) + count_w(rt - 1); }
constexpr int NW = count_w(15);
__host__ __device__ constexpr int first_slice(int rt) { return rt <= RT_SPLIT ? 0 : first_slice(rt - 1) + split(rt - 1); }
static_assert(first_slice(16) <= NSL, "slice buffer");
DEVI int slice_of(int rt) {
  constexpr int f9 = first_slice(9), f10 = first_slice(10), f11 = first_slice(11), f12 = first_slice(12), f13 = first_slice(13), f14 = first_slice(14), f15 = first_slice(15);
  return rt < 9 ? 0 : rt == 9 ? f9 : rt == 10 ? f10 : rt == 11 ? f11 : rt == 12 ? f12 : rt == 13 ? f13 : rt == 14 ? f14 : f15;
}
static_assert(RT_SPLIT >= 8, "slice_of");
enum { T_Q, T_W, T_P, T_END, T_G, T_F };
#define RG0 14
#define RG1 13
#define BKVZ (CTAIL ? 12 : 14)
#define PFB 0
#define WLD 2
#define OKEEP 13
#define OPF 0
#define SENT 1
#define FLATE 10
#define WGRID 0
#define PFRONT 0
#define PTAIL 0
#define WPRE 0
#define PFF (CTAIL ? 12 : 14)
#define PFACC 0
#define P2LATE 0
#define LAGK0 16
#define LAGK1 16
#define DEFW0 13
#define DEFW1 13
#define NWE0 0
#define NWE1 0
#define SLATE0 1
#define SLATE1 1
#define SLATE 1
#define FLAG 3
#define FWARM 0
#define SLEV 1
#define SLC 1
#define LFAST 1
#define SCOUT0 13
#define SCOUT1 13
#define NSCOUT 0
#define FVOL 1
#define FXT 10
#define FCGO 0
#define P1M 1
#define TMPF 1
#define ZPRE 1
#define CLQ 8
#define CLW 3
struct Task { int type, rt, a, b; };
DEVI int wtasks(int rt) { return 4 * split(rt); }
DEVI int lsplit(int rt) { return 31 - __clz(split(rt)); }
DEVI Task decode(int id) { return {id >> 24, (id >> 16) & 255, id & 255, (id >> 8) & 255}; }
struct __align__(16) TaskList { int n, tail0, late0, pad; uint32_t t[1280]; };
constexpr void add_w(TaskList& l, int rt, int i0 = 0, int i1 = 64) {
  for (int b = 0; b < split(rt); b++) for (int a = 0; a < 4; a++) if (b * 4 + a >= i0 && b * 4 + a < i1) l.t[l.n++] = (T_W << 24) | (rt << 16) | (b << 8) | a;
}
constexpr void add_f(TaskList& l, int rt, int i0 = 0, int i1 = 64) {
  if (rt >= 0 && split(rt) > 1) for (int a = 0; a < 4; a++) for (int b = 0; b < 128 / FROWS; b++)
    if (a * (128 / FROWS) + b >= i0 && a * (128 / FROWS) + b < i1) l.t[l.n++] = (T_F << 24) | (rt << 16) | (b << 8) | a;
}
constexpr TaskList make_list(int layer) {
  TaskList l = {};
  const int rg = layer == 0 ? RG0 : RG1, lagk = layer == 0 ? LAGK0 : LAGK1, defw = layer == 0 ? DEFW0 : DEFW1, nwe = layer == 0 ? NWE0 : NWE1;
  if (layer == 0) for (int i = NZ; i < (P2LATE ? NZ + 80 : NP) - PTAIL && i < NZ + PFRONT; i++) l.t[l.n++] = (T_P << 24) | i;
  for (int rt = 15; rt >= rg; rt--) for (int h = 0; h < NH; h++) l.t[l.n++] = (T_G << 24) | (rt << 16) | h;
  if (layer == 0) for (int i = NZ + PFRONT; i < (P2LATE ? NZ + 80 : NP) - PTAIL; i++) l.t[l.n++] = (T_P << 24) | i;
  for (int i = 0; i < NZ; i++) l.t[l.n++] = (T_P << 24) | i;
  if (layer == 0 && P2LATE) for (int i = NZ + 80; i < NP; i++) l.t[l.n++] = (T_P << 24) | i;
  for (int rt = 0; rt < 16; rt++) {
    if (rt == 15) l.tail0 = l.n;
    for (int h = 0; h < NH; h++) l.t[l.n++] = (T_Q << 24) | (rt << 16) | ((rt >= rg) << 8) | h;
    if (rt > 0 && rt - 1 < lagk && rt - 1 < defw) add_w(l, rt - 1);
    if (rt >= lagk && rt < defw) add_w(l, rt);
    if (rt == 14 && defw < 14) add_w(l, defw, 0, nwe);
    if (rt == (layer ? SCOUT1 : SCOUT0)) for (int i = 0; i < NSCOUT; i++) l.t[l.n++] = (T_END << 24) | 1;
    if (FWARM && rt - FLAG + 1 == RT_SPLIT) add_f(l, RT_SPLIT, 0, 1);
    if (rt - FLAG < FLATE) add_f(l, rt - FLAG, FWARM && rt - FLAG == RT_SPLIT ? 1 : 0);
  }
  if (layer == 0) for (int i = NP - PTAIL; i < NP; i++) l.t[l.n++] = (T_P << 24) | i;
  if (CTAIL) {
    l.late0 = 1 << 20;
    for (int rt = FLATE; rt < tl::RT0; rt++) add_f(l, rt);
    return l;
  }
  constexpr int W15E = 4 * S15 - 32;
  if (SLATE) add_w(l, 15, 0, W15E);
  if (SLATE && (layer ? SLATE1 : SLATE0) == 2) {
    l.late0 = l.n;
    add_w(l, 14); add_w(l, 15, W15E); add_f(l, 10); add_f(l, 11);
    for (int rt = 12; rt < 16; rt++) add_f(l, rt);
    return l;
  } else if (SLATE) {
    l.late0 = l.n;
    add_w(l, 13); add_w(l, 14); add_w(l, 15, W15E);
  } else {
    for (int rt = defw; rt < 16; rt++) add_w(l, rt, rt == defw && defw < 14 ? nwe : 0);
  }
  for (int rt = FLATE; rt < 16; rt++) add_f(l, rt);
  return l;
}
__device__ const TaskList d_tasks[2] = {make_list(0), make_list(1)};
__host__ __device__ constexpr uint32_t first_task(int layer, int b) {
  if (layer == 0 && PTAIL < NP - NZ) { if (b < PFRONT) return (T_P << 24) | (NZ + b); b -= PFRONT; }
  return (T_G << 24) | ((15 - (b >> 5)) << 16) | (b & 31);
}
constexpr int NLATE = SLATE && !CTAIL ? 96 : 0;
static_assert(CTAIL || !BFL, "flags");
static_assert(!CTAIL || (first_slice(tl::RT0) == tl::SL0 && DEFW0 == tl::RT0 && DEFW1 == tl::RT0 && S15 == 8 && !WGRID && BSL && SLC && LASTG), "tail of the recurrence kernel");
__host__ __device__ constexpr uint32_t late_task(int layer, int i) {
  if ((layer ? SLATE1 : SLATE0) == 2) return i < 64 ? (T_W << 24) | ((14 + (i >> 5)) << 16) | ((((i & 31) >> 2) + (i >> 5) * (S15 - 8)) << 8) | (i & 3)
                                                    : (T_F << 24) | ((6 + (i >> 4)) << 16) | ((i & 3) << 8) | ((i & 15) >> 2);
  return (T_W << 24) | ((13 + (i >> 5)) << 16) | ((((i & 31) >> 2) + (i >> 6) * (S15 - 8)) << 8) | (i & 3);
}
constexpr bool check_first() {
  for (int layer = 0; layer < 2; layer++) {
    const TaskList l = make_list(layer);
    for (int b = 0; b < 64; b++) if (l.t[b] != first_task(layer, b)) return false;
    for (int b = 0; b < NLATE; b++) if (l.t[l.late0 + b] != late_task(layer, b)) return false;
  }
  return true;
}
static_assert(check_first(), "first_task does not match the list");
}

DEVI void pass_stage(uint32_t sb, uint32_t it, int lane) {
  mbar_wait_long(sb + wk::FULL + (it % wk::NST) * 8, (it / wk::NST) & 1);
  if (lane == 0) mbar_arrive(sb + wk::EMPTY + (it % wk::NST) * 8);
}
#define AT(i, x)
template <int NT>
DEVI void attend(uint32_t sb, const uint32_t (&q)[48], int cw, int w, int lane, uint32_t itk, uint32_t itv, uint32_t mid, uint32_t nd) {
  using namespace wk;
  const int g = lane >> 2, t = lane & 3;
  AT(0, q[0]);
  float sc[NT][4];
#pragma unroll
  for (int i = 0; i < NT * 4; i++) sc[i >> 2][i & 3] = 0.f;
  const uint32_t ka = sb + (itk % NST) * STAGE + (w >> 1) * 15360 + lane * 80;
#pragma unroll
  for (int k2 = 0; k2 < 6; k2++) {
    uint32_t b[NT][4];
#pragma unroll
    for (int n = 0; n < NT; n++) ldsm4t(b[n], ka + k2 * 2560 + n * 16);
#pragma unroll
    for (int n = 0; n < NT; n++) mma16816(sc[n], &q[k2 * 8], b[n][0], b[n][1]);
#pragma unroll
    for (int n = 0; n < NT; n++) mma16816(sc[n], &q[k2 * 8 + 4], b[n][2], b[n][3]);
  }
  AT(1, __float_as_uint(sc[NT - 1][0]) ^ __float_as_uint(sc[0][0]));
  __syncwarp();
  if (lane == 0) mbar_arrive(sb + EMPTY + (itk % NST) * 8);
  const float cs = 0.07216878364870322f * 1.4426950408889634f;
  const int r0 = NMEM + (NT == 5 ? 16 : 0) + g;
  float m0 = -INFINITY, m1 = -INFINITY;
#pragma unroll
  for (int n = 0; n < NT; n++)
#pragma unroll
    for (int e = 0; e < 2; e++) {
      const int key = n * 8 + 2 * t + e;
      sc[n][e] = (n < NT - 2 || key <= r0) ? sc[n][e] * cs : -INFINITY; sc[n][2 + e] = (n < NT - 1 || key <= r0 + 8) ? sc[n][2 + e] * cs : -INFINITY;
      m0 = fmaxf(m0, sc[n][e]); m1 = fmaxf(m1, sc[n][2 + e]);
    }
  m0 = fmaxf(m0, __shfl_xor_sync(0xffffffffu, m0, 1)); m1 = fmaxf(m1, __shfl_xor_sync(0xffffffffu, m1, 1));
  m0 = fmaxf(m0, __shfl_xor_sync(0xffffffffu, m0, 2)); m1 = fmaxf(m1, __shfl_xor_sync(0xffffffffu, m1, 2));
  uint32_t P[2 * NT]; float s0 = 0.f, s1 = 0.f;
#pragma unroll
  for (int n = 0; n < NT; n++) {
    const float a = ex2(sc[n][0] - m0), b = ex2(sc[n][1] - m0), c = ex2(sc[n][2] - m1), e = ex2(sc[n][3] - m1);
    s0 += a + b; s1 += c + e; P[2 * n] = pack_bf16(a, b); P[2 * n + 1] = pack_bf16(c, e);
  }
  s0 += __shfl_xor_sync(0xffffffffu, s0, 1); s1 += __shfl_xor_sync(0xffffffffu, s1, 1);
  s0 += __shfl_xor_sync(0xffffffffu, s0, 2); s1 += __shfl_xor_sync(0xffffffffu, s1, 2);
  const float i0 = rcp(s0), i1 = rcp(s1);
  AT(2, __float_as_uint(i0) ^ __float_as_uint(i1));
  mbar_wait_long(sb + FREE + cw * 8, (nd & 1) ^ 1);
  AT(3, 0);
  if (mid != 0xFFFFFFFFu) pass_stage(sb, mid, lane);
  mbar_wait_long(sb + FULL + (itv % NST) * 8, (itv / NST) & 1);
  AT(4, 0);
  const uint32_t vb = sb + (itv % NST) * STAGE + (w >> 1) * 15360;
  const uint32_t va = vb + (lane & 7) * 80 + (lane >> 3) * 16, vc = vb + lane * 80 + 64;
  const uint32_t orow = w * 16 + (lane & 15), ob = sb + OST + cw * 24576 + orow * 128;
#pragma unroll
  for (int n8 = 0; n8 < 3; n8++) {
    uint32_t b[8][4], c[2][4];
    float o[8][4];
#pragma unroll
    for (int i = 0; i < 8; i++) { ldsm4(b[i], va + (n8 * 8 + i) * 640); o[i][0] = o[i][1] = o[i][2] = o[i][3] = 0.f; }
    if (NT == 5) { ldsm4(c[0], vc + n8 * 5120); ldsm4(c[1], vc + n8 * 5120 + 2560); }
#pragma unroll
    for (int i = 0; i < 8; i++) mma16816(o[i], &P[0], b[i][0], b[i][1]);
#pragma unroll
    for (int i = 0; i < 8; i++) { if (NT == 5) mma16816(o[i], &P[4], b[i][2], b[i][3]); else mma1688(o[i], P[4], P[5], b[i][2]); }
    if (NT == 5)
#pragma unroll
      for (int i = 0; i < 8; i++) mma1688(o[i], P[2 * NT - 2], P[2 * NT - 1], c[i >> 2][i & 3]);
#pragma unroll
    for (int i = 0; i < 4; i++)
      stsm4(ob + n8 * 8192 + (((i * 2 + (lane >> 4)) ^ (orow & 7)) << 4), pack_bf16(o[2 * i][0] * i0, o[2 * i][1] * i0), pack_bf16(o[2 * i][2] * i1, o[2 * i][3] * i1),
            pack_bf16(o[2 * i + 1][0] * i0, o[2 * i + 1][1] * i0), pack_bf16(o[2 * i + 1][2] * i1, o[2 * i + 1][3] * i1));
  }
  __syncwarp();
  AT(5, 0);
  if (lane == 0) mbar_arrive(sb + EMPTY + (itv % NST) * 8);
}

__global__ void __launch_bounds__(384, 1)
worker_kernel(int layer, Sync* sy, const bf16* __restrict__ xin, const bf16* __restrict__ wphi, const bf16* __restrict__ wo2,
              const __grid_constant__ CUtensorMap mx, const __grid_constant__ CUtensorMap mq, const __grid_constant__ CUtensorMap moa,
              const __grid_constant__ CUtensorMap mos, const __grid_constant__ CUtensorMap mwo, const __grid_constant__ CUtensorMap mxa,
              const __grid_constant__ CUtensorMap macc, const __grid_constant__ CUtensorMap mwb) {
  using namespace wk;
  extern __shared__ __align__(1024) uint8_t smraw[];
  const uint32_t sb = smem_u32(smraw);
  const int tid = threadIdx.x, lane = tid & 31;
  const int wg = __shfl_sync(0xffffffffu, tid >> 7, 0), w = __shfl_sync(0xffffffffu, (tid >> 5) & 3, 0);
  constexpr int WF = 0;
  if (!WLD) asm volatile("griddepcontrol.launch_dependents;");
  GT(1, 0);
  const int nstat = WGRID ? 0 : min(max((int)gridDim.x - (CTAIL ? 0 : 96), 0), 64);
  int idx0 = 0;
  const int nl = min((int)gridDim.x - nstat, NLATE);
  if (tid == 96 && (int)blockIdx.x >= nstat + nl) idx0 = atomicAdd(&sy->head, 1);
  int id0 = -1;
  uint32_t flag0 = 0;
  if (LFAST && tid == 0 && (int)blockIdx.x >= nstat && (int)blockIdx.x < nstat + nl) {
    if (TMPF) { asm volatile("prefetch.tensormap [%0];" :: "l"(&mwo) : "memory"); asm volatile("prefetch.tensormap [%0];" :: "l"(&moa) : "memory"); }
    id0 = late_task(layer, blockIdx.x - nstat);
    flag0 = ld_acquire(&sy->o[(id0 >> 16 & 255) * 16 + (id0 >> 8 & 255)]);
  }
  if (tid == 0) {
    sts64(sb + FIN, 0, 0);
    for (int i = 0; i < NST; i++) { mbar_init(sb + FULL + i * 8, 1); mbar_init(sb + EMPTY + i * 8, 8); }
    for (int i = 0; i < 2; i++) { mbar_init(sb + TFULL + i * 8, 1); mbar_init(sb + TEMPTY + i * 8, 9); mbar_init(sb + DONE + i * 8, 128); mbar_init(sb + FREE + i * 8, 1); }
    mbar_init(sb + CGO, 1); mbar_init(sb + LBAR, 1);
    asm volatile("fence.mbarrier_init.release.cluster;" ::: "memory");
    mbar_expect(sb + LBAR, sizeof(TaskList));
    bulk_load_plain(sb + TL, &d_tasks[layer], sizeof(TaskList), sb + LBAR);
  }
  uint32_t early = 0;
  if (wg == 0) {
    asm volatile("setmaxnreg.dec.sync.aligned.u32 40;");
    if (LFAST && w == 0) bar_arrive(0, 384); else bar_sync(0, 384);
    if (tid == 96) {
      uint32_t nres = 0;
      bool tail = false;
      int ntask = 0, tail0 = 0, late0 = 0;
      for (uint32_t nt = 0;; nt++) {
        mbar_wait_long(sb + TEMPTY + (nt & 1) * 8, ((nt >> 1) & 1) ^ 1);
        if (nt) mbar_wait_long(sb + CGO, (nt - 1) & 1);
        if (tail) for (int i = 0; i < 4000000 && (lds32(sb + FIN) < nres || lds32(sb + FIN + 4) < nres); i++) {}
        int id;
        if (nt == 0 && (int)blockIdx.x < nstat) id = first_task(layer, blockIdx.x);
        else if (nt == 0 && (int)blockIdx.x < nstat + nl) { id = late_task(layer, blockIdx.x - nstat); tail = true; }
        else {
          const int idx = nstat + (nt ? atomicAdd(&sy->head, 1) : idx0);
          if (!ntask) { mbar_wait_long(sb + LBAR, 0); ntask = lds32(sb + TL); tail0 = lds32(sb + TL + 4); late0 = lds32(sb + TL + 8); }
          const int e = !SLATE || idx < late0 ? idx : idx + nl;
          id = e < ntask ? lds32(sb + TL + 16 + e * 4) : T_END << 24;
          tail = idx >= tail0;
        }
        sts32(sb + TASK + (nt & 1) * 4, id);
        mbar_arrive(sb + TFULL + (nt & 1) * 8);
        if (WLD == 1 && (id >> 24) == T_F && (id >> 16 & 255) >= FLATE) asm volatile("griddepcontrol.launch_dependents;");
        if ((id >> 24) == T_END) {
          if (WLD) asm volatile("griddepcontrol.launch_dependents;");
          early = id & 1;
          break;
        }
        nres += (id >> 24) < T_P;
      }
    } else if (tid == 0) {
      uint32_t it = 0;
      bool have_xn = false, have_zero = false;
      if (TMPF && !LFAST && (int)blockIdx.x >= nstat) {
        asm volatile("prefetch.tensormap [%0];" :: "l"(&mwo) : "memory");
        asm volatile("prefetch.tensormap [%0];" :: "l"(&moa) : "memory");
      }
      if (!BSL && ZPRE && (int)blockIdx.x >= nstat) have_zero = ld_acquire(&sy->zeroed) >= NZ;
      for (uint32_t nt = 0;; nt++) {
        int id = id0;
        if (nt || id0 < 0) {
          mbar_wait_long(sb + TFULL + (nt & 1) * 8, (nt >> 1) & 1);
          id = lds32(sb + TASK + (nt & 1) * 4);
        }
        const Task tk = decode(id);
        if (nt == 0) WS(1, tk.type);
        mbar_arrive(sb + TEMPTY + (nt & 1) * 8);
        if (tk.type == T_END) {
          if (PFB && blockIdx.x < 128) {
            asm volatile("cp.async.bulk.prefetch.L2.global [%0], 19200;" :: "l"((const char*)g_wb1 + blockIdx.x * 19200) : "memory");
            asm volatile("cp.async.bulk.prefetch.L2.global [%0], 6400;" :: "l"((const char*)g_wb2 + blockIdx.x * 6400) : "memory");
          }
          early = id & 1;
          GT(1, 1); break;
        }
        if (tk.type == T_Q && tk.b) {
          for (int c = 0; c < 4; c++, it++) {
            const uint32_t st = it % NST, a = sb + st * STAGE, fb = sb + FULL + st * 8;
            if (!(c & 1)) {
              wait_count_t(&sy->kv[(tk.rt * 4 + c + 1) * NH + tk.a], 3, tk.rt == 15 && c == 2); fence_flag_to_bulk();
              if (LASTG && tk.rt == 15 && c == 2) asm volatile("fence.proxy.async.global;" ::: "memory");
            }
            if (OPF && c == 0 && tk.rt == 15)
              for (int n = 0; n < OPF; n++) tma3d_prefetch(&mos, 0, 13 * 128 + n * 64, tk.a * 3);
            if (c == 2) mbar_arrive(sb + CGO);
            mbar_wait_long(sb + EMPTY + st * 8, ((it / NST) & 1) ^ 1);
            mbar_expect(fb, 30720);
            const bf16* src = g_kv + ((size_t)((tk.rt * 4 + (c & 2)) * NH + tk.a) * 2 + (c & 1)) * DH * NKEY;
            bulk_load(a, src, 15360, fb);
            bulk_load(a + 15360, src + (size_t)NH * 2 * DH * NKEY, 15360, fb);
          }
        } else if (tk.type == T_G) {
          if (!have_xn) { spin_count(&sy->pro[0], 96); asm volatile("fence.proxy.async;" ::: "memory"); have_xn = true; }
          for (int c = 0; c < 10; c++, it++) {
            const uint32_t st = it % NST, a = sb + st * STAGE, fb = sb + FULL + st * 8;
            if (c == CLQ) mbar_arrive(sb + CGO);
            mbar_wait_long(sb + EMPTY + st * 8, ((it / NST) & 1) ^ 1);
            mbar_expect(fb, 40960);
            tma2d(a, &mx, c * 64, tk.rt * 128, fb);
            tma3d(a + 16384, &mq, 0, c * 64, tk.a * 3, fb);
          }
        } else if (tk.type == T_Q) {
          if (!have_xn) { spin_count(&sy->pro[0], 96); asm volatile("fence.proxy.async;" ::: "memory"); have_xn = true; }
          bool have_kv = false;
          for (int c = (WF & 2) ? 8 : 0; c < 14; c++, it++) {
            const uint32_t st = it % NST, a = sb + st * STAGE, fb = sb + FULL + st * 8;
            if (c == CLQ) mbar_arrive(sb + CGO);
            if (c >= 4 && !have_kv) {
              const uint32_t* fl = &sy->kv[(tk.rt * 4 + 3) * NH + tk.a];
              if (c == 10) wait_count(fl, 3);
              if (c == 10 || ld_acquire(fl) >= 3) { have_kv = true; fence_flag_to_bulk(); }
            }
            mbar_wait_long(sb + EMPTY + st * 8, ((it / NST) & 1) ^ 1);
            if (c < 10) {
              mbar_expect(fb, 40960);
              tma2d(a, &mx, c * 64, tk.rt * 128, fb);
              tma3d(a + 16384, &mq, 0, c * 64, tk.a * 3, fb);
            } else {
              mbar_expect(fb, 30720);
              const bf16* src = g_kv + ((size_t)((tk.rt * 4 + (c & 1) * 2) * NH + tk.a) * 2 + ((c - 10) >> 1)) * DH * NKEY;
              bulk_load(a, src, 15360, fb);
              bulk_load(a + 15360, src + (size_t)NH * 2 * DH * NKEY, 15360, fb);
            }
          }
        } else if (tk.type == T_W) {
          const int nc = (WF & 1) ? 2 : 96 >> lsplit(tk.rt), c0 = tk.b * nc;
          if (!BSL && tk.rt >= RT_SPLIT && !have_zero) { wait_count(&sy->zeroed, NZ); have_zero = true; }
          const int npre = WPRE ? min(nc, (int)NST) : 0;
          for (int c = 0; c < npre; c++) {
            const uint32_t st = (it + c) % NST, fb = sb + FULL + st * 8;
            mbar_wait_long(sb + EMPTY + st * 8, (((it + c) / NST) & 1) ^ 1);
            mbar_expect(fb, 36864);
            tma3d(sb + st * STAGE + 16384, &mwo, 0, (c0 + c) * 64, tk.a * 5, fb);
          }
          if (nt || flag0 < (64u >> lsplit(tk.rt))) wait_count_t(&sy->o[tk.rt * 16 + tk.b], 64 >> lsplit(tk.rt), tk.rt == 15);
          if (tk.rt >= 13) XT((tk.rt - 13) * 32 + (tk.b >> (tk.rt == 15 && S15 == 16) & 7) * 4 + tk.a, 0);
          fence_flag_to_bulk();
          if (tk.rt >= 13) XT((tk.rt - 13) * 32 + (tk.b >> (tk.rt == 15 && S15 == 16) & 7) * 4 + tk.a, 1);
          for (int c = 0; c < nc; c++, it++) {
            const uint32_t st = it % NST, a = sb + st * STAGE, fb = sb + FULL + st * 8;
            if (c == max(nc - CLW, 0)) mbar_arrive(sb + CGO);
            if (c >= npre) {
              mbar_wait_long(sb + EMPTY + st * 8, ((it / NST) & 1) ^ 1);
              mbar_expect(fb, 36864);
              tma3d(a + 16384, &mwo, 0, (c0 + c) * 64, tk.a * 5, fb);
            }
            tma2d(a, &moa, (c0 + c) * 64, tk.rt * 128, fb);
          }
        } else if (tk.type == T_P && tk.a >= NZ && tk.a < NZ + 80) {
          const uint32_t st = it % NST, a = sb + st * STAGE, fb = sb + FULL + st * 8;
          const int gq = (tk.a - NZ) / 10, k0 = (tk.a - NZ) % 10 * 64;
          mbar_arrive(sb + CGO);
          mbar_wait_long(sb + EMPTY + st * 8, ((it / NST) & 1) ^ 1);
          mbar_expect(fb, 30720 + 3200);
          for (int p = 0; p < 3; p++) tma2d(a + p * 10240, &mwb, p * DM + gq * 80, k0, fb);
          bulk_load_plain(a + 30720, wphi + gq * 4 * BDH * BDH, 3200, fb);
          it++;
        } else if (tk.type != T_F) mbar_arrive(sb + CGO);
      }
    } else if (tid == 32 || tid == 64) {
      const int cw = (tid >> 5) - 1;
      for (uint32_t n = 0;; n++) {
        mbar_wait_long(sb + DONE + cw * 8, n & 1);
        const Task tk = decode(lds32(sb + DTASK + cw * 4));
        if (tk.type == T_END) {
          if (BFL) red_release(&sy->pad1[0]);
          early = tk.a; break;
        }
        if (tk.type == T_W && tk.rt == FXT) XT(128 + (tk.b & 1) * 4 + tk.a, cw);
        if (tk.type == T_Q && tk.rt >= OKEEP)
          asm volatile("cp.async.bulk.tensor.3d.global.shared::cta.bulk_group [%0, {%2, %3, %4}], [%1];" :: "l"(&mos), "r"(sb + OST + cw * 24576), "r"(0), "r"(tk.rt * 128 + cw * 64), "r"(tk.a * 3) : "memory");
        else if (tk.type == T_Q) tma3d_store(&mos, sb + OST + cw * 24576, 0, tk.rt * 128 + cw * 64, tk.a * 3);
        else if (split(tk.rt) == 1) tma3d_store(&mxa, sb + OST + cw * 24576, 0, tk.rt * 128 + cw * 64, tk.a * 5);
        else if (BSL && SLC) {
          bf16* dst = g_sl + (size_t)(((slice_of(tk.rt) + tk.b) * 4 + tk.a) * 2 + cw) * 10240;
          if (SLEV) bulk_store(dst, sb + OST + cw * 24576, 20480);
          else asm volatile("cp.async.bulk.global.shared::cta.bulk_group [%0], [%1], 20480;" :: "l"(dst), "r"(sb + OST + cw * 24576) : "memory");
        }
        else if (BSL) tma3d_store(&macc, sb + OST + cw * 24576, 0, (slice_of(tk.rt) + tk.b) * 128 + cw * 64, tk.a * 5);
        else {
          const uint32_t slot = lds32(sb + DSLOT + cw * 4);
            asm volatile("cp.reduce.async.bulk.tensor.3d.global.shared::cta.add.tile.bulk_group [%0, {%2, %3, %4}], [%1];"
                         :: "l"(&macc), "r"(sb + slot * STAGE), "r"(0), "r"(layer * ACC_ROWS + (tk.rt - RT_SPLIT) * 128 + cw * 64), "r"(tk.a * 5) : "memory");
          asm volatile("cp.async.bulk.commit_group; cp.async.bulk.wait_group.read 0;" ::: "memory");
          asm volatile("mbarrier.arrive.shared::cta.b64 _, [%0], 8;" :: "r"(sb + EMPTY + slot * 8) : "memory");
        }
        asm volatile("cp.async.bulk.commit_group; cp.async.bulk.wait_group.read 0;" ::: "memory");
        mbar_arrive(sb + FREE + cw * 8);
        if (tk.type == T_Q && tk.rt == 15) XT(96 + tk.a, cw);
        asm volatile("cp.async.bulk.wait_group 0;" ::: "memory");
        if (tk.type == T_Q && tk.rt == 15) XT(96 + tk.a, 2 + cw);
        if (tk.type == T_W && tk.rt >= 13) XT((tk.rt - 13) * 32 + (tk.b >> (tk.rt == 15 && S15 == 16) & 7) * 4 + tk.a, 2 + cw);
        if (tk.type == T_W && tk.rt == FXT) XT(128 + (tk.b & 1) * 4 + tk.a, 2 + cw);
        if (tk.type == T_Q) {
          const int sl = tk.rt * 16 + (tk.a >> (5 - lsplit(tk.rt))) + (CTAIL && tk.rt == 15 ? cw * 8 : 0);
          publish_bulk<WFEN>(&sy->o[sl]);
        } else if (split(tk.rt) > 1) {
          publish_bulk<WFEN>(&sy->wcnt[(tk.rt * 4 + tk.a) * 2 + cw]);
        }
        sts32(sb + FIN + cw * 4, n + 1);
      }
    }
  } else {
    asm volatile("setmaxnreg.inc.sync.aligned.u32 232;");
    bar_sync(0, 384);
    const int cw = wg - 1, g = lane >> 2, t = lane & 3, ct = tid - 128;
    uint32_t it = 0, nd = 0;
    for (uint32_t nt = 0;; nt++) {
      mbar_wait_long(sb + TFULL + (nt & 1) * 8, (nt >> 1) & 1);
      const int tid_ = __shfl_sync(0xffffffffu, (int)lds32(sb + TASK + (nt & 1) * 4), 0);
      const Task tk = decode(tid_);
      if (nt == 0 && ct == 0) WS(2, tid_);
      __syncwarp();
      if (lane == 0) mbar_arrive(sb + TEMPTY + (nt & 1) * 8);
      if (tk.type == T_END) {
        mbar_wait_long(sb + FREE + cw * 8, (nd & 1) ^ 1);
        if (ct == cw * 128) sts32(sb + DTASK + cw * 4, tid_);
        mbar_arrive(sb + DONE + cw * 8);
        early = tid_ & 1;
        break;
      }
      if (tk.type == T_Q || tk.type == T_G) {
        if (PFACC && tk.type == T_Q && tk.rt >= RT_SPLIT && ct == 32)
          asm volatile("cp.async.bulk.prefetch.L2.global [%0], 10240;" :: "l"(g_acc + (size_t)(layer * ACC_ROWS + (tk.rt - RT_SPLIT) * 128 + tk.a * 4) * DM) : "memory");
        uint32_t q[48];
        uint4* qf = g_qf + (size_t)(tk.rt * NH + tk.a) * 12 * 256 + ct;
        if (tk.type == T_Q && tk.b) {
          if ((ct & 127) == 0) wait_count(&sy->gst[tk.rt * NH + tk.a], 2);
          bar_sync(1 + cw, 128);
#pragma unroll
          for (int i = 0; i < 12; i++) { const uint4 u = __ldcg(qf + i * 256); q[4 * i] = u.x; q[4 * i + 1] = u.y; q[4 * i + 2] = u.z; q[4 * i + 3] = u.w; }
        } else {
          float d[96];
#pragma unroll
          for (int i = 0; i < 96; i++) d[i] = 0.f;
          for (int c = 0; c < ((WF & 2) ? 2 : 10); c++, it++) {
            const uint32_t st = it % NST, a = sb + st * STAGE;
            mbar_wait_long(sb + FULL + st * 8, (it / NST) & 1);
            if (c == 0) TM(0);
            const uint64_t da = mkdesc(a + cw * 8192, 16, 1024, 1), db = mkdesc(a + 16384, 8192, 1024, 1);
            wg_fence();
#pragma unroll
            for (int k = 0; k < 4; k++) wgmma_n192_nt(d, da + k * 2, db + k * 128, c | k);
            wg_commit();
            if (c > 0) { wg_wait<1>(); if (lane == 0) mbar_arrive(sb + EMPTY + ((it - 1) % NST) * 8); }
          }
          wg_wait<0>();
          if (lane == 0) mbar_arrive(sb + EMPTY + ((it - 1) % NST) * 8);
#pragma unroll
          for (int i = 0; i < 48; i++) q[i] = pack_bf16(d[2 * i], d[2 * i + 1]);
        }
        TM(1);
        if (tk.type == T_G) {
#pragma unroll
          for (int i = 0; i < 12; i++) __stcg(qf + i * 256, make_uint4(q[4 * i], q[4 * i + 1], q[4 * i + 2], q[4 * i + 3]));
          bar_sync(1 + cw, 128);
          if ((ct & 127) == 0) red_release(&sy->gst[tk.rt * NH + tk.a]);
          __syncwarp();
          TM(2); TM(3);
          continue;
        }
        const uint32_t itk = tk.b ? it + 2 * cw : it + cw, itv = tk.b ? itk + 1 : it + 2 + cw;
        if (cw == 1) { pass_stage(sb, it, lane); if (tk.b) pass_stage(sb, it + 1, lane); }
        mbar_wait_long(sb + FULL + (itk % NST) * 8, (itk / NST) & 1);
        TM(2);
        const uint32_t mid = tk.b ? 0xFFFFFFFFu : itk + 1;
        if (w & 1) attend<5>(sb, q, cw, w, lane, itk, itv, mid, nd); else attend<3>(sb, q, cw, w, lane, itk, itv, mid, nd);
        if (!CTAIL && cw == 0) { if (tk.b) pass_stage(sb, it + 2, lane); pass_stage(sb, it + 3, lane); }
        if (ct == cw * 128) sts32(sb + DTASK + cw * 4, tid_);
        fence_async();
        mbar_arrive(sb + DONE + cw * 8);
        if (CTAIL && cw == 0) { if (tk.b) pass_stage(sb, it + 2, lane); pass_stage(sb, it + 3, lane); }
        it += 4;
        nd++;
        TM(3);
      } else if (tk.type == T_W) {
        float d[80];
#pragma unroll
        for (int i = 0; i < 80; i++) d[i] = 0.f;
        const int nc = (WF & 1) ? 2 : 96 >> lsplit(tk.rt);
        const int off = (tk.rt * 128 + cw * 64 + w * 16 + g) * DM + tk.a * 160 + 2 * t;
        const bool whole = BSL || split(tk.rt) == 1;
        uint32_t res[40];
#pragma unroll
        for (int i = 0; i < 40; i++) res[i] = split(tk.rt) == 1 ? *(const uint32_t*)(xin + off + (i >> 1) * 8 + (i & 1) * 8 * DM) : 0u;
        for (int c = 0; c < nc; c++, it++) {
          const uint32_t st = it % NST, a = sb + st * STAGE;
          mbar_wait_long(sb + FULL + st * 8, (it / NST) & 1);
          if (c == 0) TM(0);
          const uint64_t da = mkdesc(a + cw * 8192, 16, 1024, 1), db = mkdesc(a + 16384, 4096, 512, 2);
          wg_fence();
#pragma unroll
          for (int k = 0; k < 4; k++) wgmma_n160_nt(d, da + k * 2, db + k * 64, c | k);
          wg_commit();
          if (c > 0) { wg_wait<1>(); if (lane == 0 && (whole || c < nc - 1)) mbar_arrive(sb + EMPTY + ((it - 1) % NST) * 8); }
        }
        wg_wait<0>();
        if (lane == 0 && whole) mbar_arrive(sb + EMPTY + ((it - 1) % NST) * 8);
        TM(1);
        mbar_wait_long(sb + FREE + cw * 8, (nd & 1) ^ 1);
        TM(2);
        if (whole) {
          const uint32_t orow = w * 16 + (lane & 15), ob = sb + OST + cw * 24576 + orow * 64;
          float s1[2] = {0.f, 0.f}, s2[2] = {0.f, 0.f};
#pragma unroll
          for (int i2 = 0; i2 < 10; i2++) {
            uint32_t u[4];
#pragma unroll
            for (int e = 0; e < 4; e++) {
              const int i = 2 * i2 + (e >> 1);
              const uint32_t x = res[4 * i2 + e];
              u[e] = pack_bf16(d[4 * i + (e & 1) * 2] + __uint_as_float(x << 16), d[4 * i + (e & 1) * 2 + 1] + __uint_as_float(x & 0xFFFF0000u));
              const float lo = __uint_as_float(u[e] << 16), hi = __uint_as_float(u[e] & 0xFFFF0000u);
              s1[e & 1] += lo + hi; s2[e & 1] = fmaf(lo, lo, fmaf(hi, hi, s2[e & 1]));
            }
            stsm4(ob + (i2 >> 1) * 4096 + ((((i2 & 1) * 2 + (lane >> 4)) ^ ((orow >> 1) & 3)) << 4), u[0], u[1], u[2], u[3]);
          }
          fence_async();
          if (split(tk.rt) == 1)
#pragma unroll
          for (int e = 0; e < 2; e++) {
            s1[e] += __shfl_xor_sync(0xffffffffu, s1[e], 1); s2[e] += __shfl_xor_sync(0xffffffffu, s2[e], 1);
            s1[e] += __shfl_xor_sync(0xffffffffu, s1[e], 2); s2[e] += __shfl_xor_sync(0xffffffffu, s2[e], 2);
            if (t == 0) red_add2(&sy->rstat[tk.rt * 128 + cw * 64 + w * 16 + g + 8 * e], s1[e], s2[e]);
          }
        } else {
          bar_sync(3, 256);
          const uint32_t slot = (it - 2 + cw) % NST, a = sb + slot * STAGE + (w * 16 + g) * 128 + (t & 1) * 8;
#pragma unroll
          for (int i = 0; i < 20; i++) {
            const uint32_t o = a + (i >> 2) * 8192 + ((((i & 3) * 2 + (t >> 1)) ^ g) << 4);
            sts64(o, __float_as_uint(d[4 * i]), __float_as_uint(d[4 * i + 1])); sts64(o + 1024, __float_as_uint(d[4 * i + 2]), __float_as_uint(d[4 * i + 3]));
          }
          if (ct == cw * 128) sts32(sb + DSLOT + cw * 4, slot);
          fence_async();
        }
        if (ct == cw * 128) sts32(sb + DTASK + cw * 4, tid_);
        mbar_arrive(sb + DONE + cw * 8);
        nd++;
        TM(3);
      } else if (BSL && tk.type == T_F) {
        if (tk.rt == BKVZ && tk.b < 2) for (int i = ct; i < NH * BF * 6 / 8; i += 256) ((uint4*)g_bkv)[(tk.a * 2 + tk.b) * (NH * BF * 6 / 8) + i] = make_uint4(0, 0, 0, 0);
        if (PFF && tk.rt == PFF && tk.b < 2 && ct == 32) {
          const int q = tk.a * 2 + tk.b;
          for (int i = 0; i < 20; i++) asm volatile("cp.async.bulk.prefetch.L2.global [%0], 15360;" :: "l"((const char*)g_wb1 + (q * 20 + i) * 15360) : "memory");
          for (int i = 0; i < 8; i++) asm volatile("cp.async.bulk.prefetch.L2.global [%0], 12800;" :: "l"((const char*)g_wb2 + (q * 8 + i) * 12800) : "memory");
          asm volatile("cp.async.bulk.prefetch.L2.global [%0], 9600;" :: "l"((const char*)g_cs + q * 9600) : "memory");
        }
        constexpr int LPR = 256 / FROWS, NU = (20 + LPR - 1) / LPR;
        const int cq = opq(ct), rl = tk.b * FROWS + cq / LPR, q = cq % LPR, r = tk.rt * 128 + rl, c0 = tk.a * 160 + q * 8;
        if (ct == 0) { wait_count_t(&sy->wcnt[(tk.rt * 4 + tk.a) * 2 + tk.b * FROWS / 64], split(tk.rt), TIGHT == 1 && tk.rt >= 13); if (!FCGO) mbar_arrive(sb + CGO); }
        if (ct == 0 && tk.rt == FXT) XT(136 + tk.a * 4 + tk.b, 1);
        uint4 x[NU];
#pragma unroll
        for (int i = 0; i < NU; i++) x[i] = ldcg_if(xin + r * DM + c0 + i * LPR * 8, i * LPR + q < 20);
        bar_sync(3, 256);
        float a[NU][8];
#pragma unroll
        for (int i = 0; i < NU; i++) {
          a[i][0] = __uint_as_float(x[i].x << 16); a[i][1] = __uint_as_float(x[i].x & 0xFFFF0000u); a[i][2] = __uint_as_float(x[i].y << 16); a[i][3] = __uint_as_float(x[i].y & 0xFFFF0000u);
          a[i][4] = __uint_as_float(x[i].z << 16); a[i][5] = __uint_as_float(x[i].z & 0xFFFF0000u); a[i][6] = __uint_as_float(x[i].w << 16); a[i][7] = __uint_as_float(x[i].w & 0xFFFF0000u);
        }
        float y[NU][8];
#pragma unroll
        for (int i = 0; i < NU * 8; i++) y[i >> 3][i & 7] = 0.f;
        const bf16* sl = SLC ? g_sl + (size_t)((slice_of(tk.rt) * 4 + tk.a) * 2 + (rl >> 6)) * 10240 + (q >> 2) * 2048 + (rl & 63) * 32 + (((q & 3) ^ (rl >> 1 & 3)) << 3)
                             : g_sl + (size_t)(slice_of(tk.rt) * 128 + rl) * DM + c0;
        constexpr int US = SLC ? LPR / 4 * 2048 : LPR * 8;
        constexpr int SB = FROWS == 64 ? 4 : 8;
        for (int b0 = 0; b0 < split(tk.rt); b0 += SB) {
          uint4 u[SB][NU];
#pragma unroll
          for (int b = 0; b < SB; b++)
#pragma unroll
            for (int i = 0; i < NU; i++)
              if (FVOL) u[b][i] = ldcg_if(sl + (size_t)(b0 + b) * 128 * DM + i * US, b0 + b < split(tk.rt) && i * LPR + q < 20);
              else u[b][i] = b0 + b < split(tk.rt) && i * LPR + q < 20 ? __ldcg((const uint4*)(sl + (size_t)(b0 + b) * 128 * DM + i * US)) : make_uint4(0, 0, 0, 0);
          if (FVOL) sched_fence(layer >> 4);
#pragma unroll
          for (int b = 0; b < SB; b++)
#pragma unroll
            for (int i = 0; i < NU; i++) {
              y[i][0] += __uint_as_float(u[b][i].x << 16); y[i][1] += __uint_as_float(u[b][i].x & 0xFFFF0000u); y[i][2] += __uint_as_float(u[b][i].y << 16); y[i][3] += __uint_as_float(u[b][i].y & 0xFFFF0000u);
              y[i][4] += __uint_as_float(u[b][i].z << 16); y[i][5] += __uint_as_float(u[b][i].z & 0xFFFF0000u); y[i][6] += __uint_as_float(u[b][i].w << 16); y[i][7] += __uint_as_float(u[b][i].w & 0xFFFF0000u);
            }
        }
        if (FCGO && ct == 0) { loaded(__float_as_uint(y[0][0])); mbar_arrive(sb + CGO); }
        float s1 = 0.f, s2 = 0.f;
#pragma unroll
        for (int i = 0; i < NU; i++) {
          uint32_t z[4];
#pragma unroll
          for (int e = 0; e < 4; e++) {
            z[e] = pack_bf16(a[i][2 * e] + y[i][2 * e], a[i][2 * e + 1] + y[i][2 * e + 1]);
            const float lo = __uint_as_float(z[e] << 16), hi = __uint_as_float(z[e] & 0xFFFF0000u);
            s1 += lo + hi; s2 = fmaf(lo, lo, fmaf(hi, hi, s2));
          }
          asm volatile("{.reg .pred p; setp.ne.u32 p, %5, 0; @p st.global.v4.u32 [%0], {%1,%2,%3,%4};}"
                       :: "l"(g_xa + r * DM + c0 + i * LPR * 8), "r"(z[0]), "r"(z[1]), "r"(z[2]), "r"(z[3]), "r"((uint32_t)(i * LPR + q < 20)) : "memory");
        }
#pragma unroll
        for (int o = 1; o < LPR; o <<= 1) { s1 += __shfl_xor_sync(0xffffffffu, s1, o); s2 += __shfl_xor_sync(0xffffffffu, s2, o); }
        asm volatile("{.reg .pred p; setp.ne.u32 p, %3, 0; @p red.relaxed.gpu.global.add.v2.f32 [%0], {%1,%2};}"
                     :: "l"(&sy->rstat[r]), "f"(s1), "f"(s2), "r"((uint32_t)(q == 0)) : "memory");
        if (ct == 0 && tk.rt == FXT) XT(136 + tk.a * 4 + tk.b, 2);
        TM(0); TM(1); TM(2); TM(3);
      } else if (tk.type == T_F) {
        if (tk.rt == BKVZ) for (int i = ct; i < NH * BF * 6 / 8; i += 256) ((uint4*)g_bkv)[(tk.a * 2 + tk.b) * (NH * BF * 6 / 8) + i] = make_uint4(0, 0, 0, 0);
        if (PFF && tk.rt == PFF && ct == 32) {
          const int q = tk.a * 2 + tk.b;
          for (int i = 0; i < 20; i++) asm volatile("cp.async.bulk.prefetch.L2.global [%0], 15360;" :: "l"((const char*)g_wb1 + (q * 20 + i) * 15360) : "memory");
          for (int i = 0; i < 8; i++) asm volatile("cp.async.bulk.prefetch.L2.global [%0], 12800;" :: "l"((const char*)g_wb2 + (q * 8 + i) * 12800) : "memory");
          asm volatile("cp.async.bulk.prefetch.L2.global [%0], 9600;" :: "l"((const char*)g_cs + q * 9600) : "memory");
        }
        if (ct == 0) { wait_count(&sy->wcnt[(tk.rt * 4 + tk.a) * 2 + tk.b], split(tk.rt)); mbar_arrive(sb + CGO); }
        const int r = tk.rt * 128 + tk.b * 64 + (ct >> 2), c0 = tk.a * 160 + (ct & 3) * 4;
        uint2 x[10];
#pragma unroll
        for (int i = 0; i < 10; i++) x[i] = __ldg((const uint2*)(xin + r * DM + c0 + i * 16));
        bar_sync(3, 256);
        float4 a[10];
#pragma unroll
        for (int i = 0; i < 10; i++) a[i] = __ldcg((const float4*)(g_acc + (layer * ACC_ROWS + r - RT_SPLIT * 128) * DM + c0 + i * 16));
        float s1 = 0.f, s2 = 0.f;
#pragma unroll
        for (int i = 0; i < 10; i++) {
          const uint2 z = make_uint2(pack_bf16(a[i].x + __uint_as_float(x[i].x << 16), a[i].y + __uint_as_float(x[i].x & 0xFFFF0000u)),
                                     pack_bf16(a[i].z + __uint_as_float(x[i].y << 16), a[i].w + __uint_as_float(x[i].y & 0xFFFF0000u)));
          *(uint2*)(g_xa + r * DM + c0 + i * 16) = z;
          const float v0 = __uint_as_float(z.x << 16), v1 = __uint_as_float(z.x & 0xFFFF0000u), v2 = __uint_as_float(z.y << 16), v3 = __uint_as_float(z.y & 0xFFFF0000u);
          s1 += (v0 + v1) + (v2 + v3); s2 = fmaf(v0, v0, fmaf(v1, v1, fmaf(v2, v2, fmaf(v3, v3, s2))));
        }
        s1 += __shfl_xor_sync(0xffffffffu, s1, 1); s2 += __shfl_xor_sync(0xffffffffu, s2, 1);
        s1 += __shfl_xor_sync(0xffffffffu, s1, 2); s2 += __shfl_xor_sync(0xffffffffu, s2, 2);
        if ((ct & 3) == 0) red_add2(&sy->rstat[r], s1, s2);
        TM(0); TM(1); TM(2); TM(3);
      } else if (tk.a < NZ) {
        if (!BSL) for (int i = ct; i < ACC_ROWS * DM / 4 / NZ; i += 256) ((uint4*)(g_acc + layer * ACC_ROWS * DM))[tk.a * (ACC_ROWS * DM / 4 / NZ) + i] = make_uint4(0, 0, 0, 0);
        if (layer == 1) {
          if (ct == 0) wait_count(&sy->pro[0], 96);
          bar_sync(3, 256);
        }
        for (int i = tk.a * 256 + ct; i < (int)(sizeof(Sync) / 16); i += NZ * 256) ((uint4*)&g_sync[layer ^ 1])[i] = make_uint4(0, 0, 0, 0);
        bar_sync(3, 256);
        if (ct == 0) red_release(&sy->zeroed);
        __syncwarp();
      } else if (tk.a >= NZ + 80) {
        const int c = tk.a - NZ - 80, cq = opq(ct);
        uint4 u[20];
#pragma unroll
        for (int i = 0; i < 20; i++) u[i] = __ldg((const uint4*)(wo2 + c * 64 * DM) + i * 256 + cq);
#pragma unroll
        for (int i = 0; i < 20; i++) {
          const int p = i * 256 + cq, kr = p / 80, n8 = p % 80, gq = n8 / 10;
          g_wb2[(gq * 10 + c) * 640 + (n8 % 10 >> 1) * 128 + kr * 2 + ((n8 & 1) ^ (kr >> 2 & 1))] = u[i];
        }
      } else if (P1M) {
        const int gq = (tk.a - NZ) / 10, k0 = (tk.a - NZ) % 10 * 64;
        const uint32_t ln = opq(lane), gg = ln >> 2, tt = ln & 3, wi = opq(ct >> 5);
        const uint32_t T = sb + OST, stg = sb + (it % NST) * STAGE;
        mbar_wait_long(sb + FULL + (it % NST) * 8, (it / NST) & 1);
        uint32_t a0[4], a1[4], a0k[2], a1k;
        {
          const uint32_t pa = stg + 30720 + w * 800 + tt * 80 + gg * 2;
          auto pr = [&](int d, int f) { uint32_t lo, hi;
            asm volatile("ld.shared.u16 %0, [%1];" : "=r"(lo) : "r"(pa + d * 40 + f * 2) : "memory");
            asm volatile("ld.shared.u16 %0, [%1];" : "=r"(hi) : "r"(pa + d * 40 + 40 + f * 2) : "memory");
            return lo | hi << 16; };
          a0[0] = pr(0, 0); a0[1] = pr(0, 8); a0[2] = pr(8, 0); a0[3] = pr(8, 8);
          const int d2 = tt < 2 ? 16 : 0, f2 = gg < 4 ? 16 : 0;
          a0k[0] = pr(d2, 0); a0k[1] = pr(d2, 8);
          a1[0] = pr(0, f2); a1[2] = pr(8, f2); a1k = pr(d2, f2);
          a1[1] = a1[3] = 0;
          if (tt >= 2) a0k[0] = a0k[1] = a1k = 0;
          if (gg >= 4) a1[0] = a1[2] = a1k = 0;
        }
        float c[8][2][4];
        const uint32_t pb = stg + cw * 10240 + gg * 160 + w * 40 + tt * 4;
#pragma unroll
        for (int nt = 0; nt < 8; nt++) {
          const uint32_t b0 = lds32(pb + nt * 1280), b1 = lds32(pb + nt * 1280 + 16);
          uint32_t b2 = lds32(pb + nt * 1280 + (tt < 2 ? 32 : 0));
          if (tt >= 2) b2 = 0;
#pragma unroll
          for (int i = 0; i < 8; i++) c[nt][i >> 2][i & 3] = 0.f;
          mma16816(c[nt][0], a0, b0, b1); mma16816(c[nt][1], a1, b0, b1);
          mma1688(c[nt][0], a0k[0], a0k[1], b2); mma1688(c[nt][1], a1k, 0u, b2);
        }
        uint32_t v[3][4];
        const uint32_t pv = stg + 20480 + (wi * 8 + (ln & 7)) * 160 + (ln >> 3) * 16;
        ldsm4t(v[0], pv); ldsm4t(v[1], pv + 64); ldsm4t(v[2], pv + (ln >> 4 ? 96 : 128));
        mbar_wait_long(sb + FREE + cw * 8, (nd & 1) ^ 1);
        loaded(v[2][3]);
        bar_sync(3, 256);
        if (lane == 0) mbar_arrive(sb + EMPTY + (it % NST) * 8);
        it++;
        {
          const uint32_t n0 = cw * 80 + w * 2 + (gg >> 1) * 8 + (gg & 1);
#pragma unroll
          for (int q = 0; q < 3; q++) {
            const uint32_t n = n0 + q * 32, ro = T + n * 128 + tt * 4, sw = (n >> 3 & 3) * 2 + (n & 1);
            if (q < 2 || gg < 4)
#pragma unroll
              for (int nt = 0; nt < 8; nt++) sts32(ro + ((nt ^ sw) << 4), pack_bf16(c[nt][q >> 1][(q & 1) * 2], c[nt][q >> 1][(q & 1) * 2 + 1]));
          }
#pragma unroll
          for (int i = 0; i < 10; i++) sts32(T + (160 + i * 8 + gg) * 128 + ((wi ^ gg) << 4) + tt * 4, v[i >> 2][i & 3]);
        }
        bar_sync(3, 256);
        const int cq = opq(ct);
        for (int i = cq; i < 240 * 8; i += 256) {
          const uint32_t n = i >> 3, sw = n < 160 ? (n >> 3 & 3) * 2 + (n & 1) : n & 7;
          uint32_t u[4]; lds128(u, T + n * 128 + (((i & 7) ^ sw) << 4));
          *(uint4*)(g_wb1 + (gq * 240 + n) * DM + k0 + (i & 7) * 8) = make_uint4(u[0], u[1], u[2], u[3]);
        }
        if (cq < 240) {
          float cs = 0.f;
#pragma unroll
          for (int i = 0; i < 8; i++) {
            uint32_t u[4]; lds128(u, T + cq * 128 + (((i + cq) & 7) << 4));
#pragma unroll
            for (int e = 0; e < 4; e++) cs += __uint_as_float(u[e] << 16) + __uint_as_float(u[e] & 0xFFFF0000u);
          }
          g_cs[(k0 >> 6) * 3 * DM + gq * 240 + cq] = cs;
        }
        bar_sync(3, 256);
      } else {
        const int gq = (tk.a - NZ) / 10, k0 = (tk.a - NZ) % 10 * 64, r = ct & 63, hh = ct >> 6;
        bf16* T = (bf16*)(smraw + OST);
        float* ph = (float*)(smraw + OST + 30720);
        const uint32_t stg = sb + (it % NST) * STAGE;
        mbar_wait_long(sb + FULL + (it % NST) * 8, (it / NST) & 1);
        uint2 u[3][5];
#pragma unroll
        for (int i = 0; i < 15; i++) { const float2 v = lds64f(stg + (i / 5) * 10240 + r * 160 + hh * 40 + (i % 5) * 8); u[i / 5][i % 5] = make_uint2(__float_as_uint(v.x), __float_as_uint(v.y)); }
        uint32_t pv[4];
#pragma unroll
        for (int i = 0; i < 4; i++) pv[i] = lds32(stg + 30720 + min(ct + i * 256, 799) * 4);
        mbar_wait_long(sb + FREE + cw * 8, (nd & 1) ^ 1);
        loaded(u[2][4].x); loaded(pv[3]);
        bar_sync(3, 256);
        if (lane == 0) mbar_arrive(sb + EMPTY + (it % NST) * 8);
        it++;
#pragma unroll
        for (int i = 0; i < 4; i++) if (ct + i * 256 < 800) *(float2*)(ph + (ct + i * 256) * 2) = make_float2(__uint_as_float(pv[i] << 16), __uint_as_float(pv[i] & 0xFFFF0000u));
        bar_sync(3, 256);
#pragma unroll
        for (int part = 0; part < 2; part++) {
          float a[BDH];
#pragma unroll
          for (int i = 0; i < 5; i++) {
            a[4 * i] = __uint_as_float(u[part][i].x << 16); a[4 * i + 1] = __uint_as_float(u[part][i].x & 0xFFFF0000u);
            a[4 * i + 2] = __uint_as_float(u[part][i].y << 16); a[4 * i + 3] = __uint_as_float(u[part][i].y & 0xFFFF0000u);
          }
#pragma unroll 1
          for (int f4 = 0; f4 < 5; f4++) {
            float4 q = make_float4(0.f, 0.f, 0.f, 0.f);
#pragma unroll
            for (int dd = 0; dd < BDH; dd++) {
              const float4 p = *(const float4*)(ph + (hh * BDH + dd) * BDH + f4 * 4);
              q.x = fmaf(a[dd], p.x, q.x); q.y = fmaf(a[dd], p.y, q.y); q.z = fmaf(a[dd], p.z, q.z); q.w = fmaf(a[dd], p.w, q.w);
            }
            bf16* dst = T + (part * 80 + f4 * 16 + hh * 2) * 64 + r;
            dst[0] = __float2bfloat16(q.x); dst[64] = __float2bfloat16(q.y); dst[8 * 64] = __float2bfloat16(q.z); dst[9 * 64] = __float2bfloat16(q.w);
          }
        }
#pragma unroll
        for (int i = 0; i < 5; i++) {
          uint16_t* dst = (uint16_t*)T + (160 + hh * BDH + i * 4) * 64 + r;
          dst[0] = (uint16_t)u[2][i].x; dst[64] = (uint16_t)(u[2][i].x >> 16); dst[128] = (uint16_t)u[2][i].y; dst[192] = (uint16_t)(u[2][i].y >> 16);
        }
        bar_sync(3, 256);
        for (int i = ct; i < 240 * 8; i += 256) *(uint4*)(g_wb1 + (gq * 240 + (i >> 3)) * DM + k0 + (i & 7) * 8) = *(const uint4*)(T + i * 8);
        if (ct < 240) {
          float cs = 0.f;
#pragma unroll
          for (int i = 0; i < 8; i++) {
            const uint4 v = *(const uint4*)(T + ct * 64 + ((i + ct) & 7) * 8);
            const uint32_t vv[4] = {v.x, v.y, v.z, v.w};
#pragma unroll
            for (int e = 0; e < 4; e++) cs += __uint_as_float(vv[e] << 16) + __uint_as_float(vv[e] & 0xFFFF0000u);
          }
          g_cs[(k0 >> 6) * 3 * DM + gq * 240 + ct] = cs;
        }
        bar_sync(3, 256);
      }
    }
  }
  __syncwarp();
  if (CTAIL ? SENT && blockIdx.x == 0 : !__shfl_sync(0xffffffffu, early, 0)) asm volatile("griddepcontrol.wait;" ::: "memory");
}

#define KVREL 0
#define KVF 0
#define PFA_N 2
#define PFA_DELAY 500
#define PFA_LIMIT 30000
#define PFB_DELAY 2000
#define PFA_ORD 0x0312
#define PFA_SLEEP 0
#define BTPF 0
#define BHALF 0
#define LDL8 3
#define W2E 1
#define PREFETCH_A 0
namespace bk {
constexpr uint32_t STAGE = 47104, NST = 4;
constexpr uint32_t W2 = 0, A2 = 102400;
constexpr uint32_t PHI = 102400, VS = PHI + 128 * 336, KVS = PHI;
constexpr uint32_t OS = A2 + 65536;
constexpr uint32_t PHQ = NST * STAGE;
constexpr uint32_t CS = PHQ;
constexpr uint32_t MISC = PHQ + 128 * 336;
constexpr int NST2 = 7;
constexpr uint32_t FULL = MISC, EMPTY = MISC + 32, EMPTY2 = MISC + 64, BW2 = MISC + 128, BOK = MISC + 136, BKR = MISC + 144, BKV = MISC + 152, FULL2 = MISC + 160;
constexpr uint32_t SMEM = MISC + 256;
}
DEVI void feature_map(const float* d, uint32_t dst) {
#pragma unroll
  for (int r = 0; r < 2; r++) {
    const float l2e = 1.4426950408889634f;
    float mx = d[2 * r], mn = d[2 * r];
#pragma unroll
    for (int i = 1; i < 20; i++) { const float x = d[(i >> 1) * 4 + 2 * r + (i & 1)]; mx = fmaxf(mx, x); mn = fminf(mn, x); }
    mx *= l2e; mn *= l2e;
    float p[20], n[20], sp = 0.f, sn = 0.f;
#pragma unroll
    for (int i = 0; i < 20; i++) {
      const float x = d[(i >> 1) * 4 + 2 * r + (i & 1)];
      p[i] = ex2(fmaf(x, l2e, -mx)); n[i] = ex2(fmaf(x, -l2e, mn)); sp += p[i]; sn += n[i];
    }
    sp = rcp(sp); sn = rcp(sn);
#pragma unroll
    for (int i = 0; i < 5; i++)
      sts128(dst + r * 8 * 336 + i * 16, pack_bf16(p[4 * i] * sp, n[4 * i] * sn), pack_bf16(p[4 * i + 1] * sp, n[4 * i + 1] * sn),
             pack_bf16(p[4 * i + 2] * sp, n[4 * i + 2] * sn), pack_bf16(p[4 * i + 3] * sp, n[4 * i + 3] * sn));
  }
}

__global__ void __launch_bounds__(384, 1)
layerb_kernel(int layer, uint32_t nw2, Sync* sy, const bf16* __restrict__ xin, bf16* __restrict__ out, const void* wa0, const void* wa1, const void* wa2, const void* wa3,
              const __grid_constant__ CUtensorMap mx, const __grid_constant__ CUtensorMap mw1, const __grid_constant__ CUtensorMap mo,
              const __grid_constant__ CUtensorMap mos) {
  using namespace bk;
  extern __shared__ __align__(1024) uint8_t smraw[];
  const uint32_t sb = smem_u32(smraw);
  const int tid = threadIdx.x, lane = tid & 31;
  const int wg = __shfl_sync(0xffffffffu, tid >> 7, 0), w = __shfl_sync(0xffffffffu, (tid >> 5) & 3, 0);
  const int rt = CTAIL ? 15 - (blockIdx.x >> 3) : blockIdx.x >> 3, gq = blockIdx.x & 7;
  if (blockIdx.x >= 128) {
    asm volatile("griddepcontrol.launch_dependents;");
    if (tid == 0) {
      asm volatile("griddepcontrol.wait;" ::: "memory");
      const uint32_t t0 = clk32();
      __nanosleep(PFA_DELAY);
      const int nc = gridDim.x - 128;
      for (int i = blockIdx.x - 128; i < PFA_N * 480 && clk32() - t0 < PFA_LIMIT; i += nc) {
        const int m = PFA_ORD >> (i / 480 * 4) & 3;
        const char* p = (const char*)(m == 0 ? wa0 : m == 1 ? wa1 : m == 2 ? wa2 : wa3) + (size_t)(i % 480) * 16384;
        asm volatile("cp.async.bulk.prefetch.L2.global [%0], 16384;" :: "l"(p) : "memory");
        if (PFA_SLEEP) __nanosleep(PFA_SLEEP);
      }
    }
    return;
  }
  if (tid == 0) {
    for (int i = 0; i < NST; i++) { mbar_init(sb + FULL + i * 8, 1); mbar_init(sb + EMPTY + i * 8, 8); }
    for (int i = 0; i < NST2; i++) { mbar_init(sb + FULL2 + i * 8, 1); mbar_init(sb + EMPTY2 + i * 8, 8); }
    mbar_init(sb + BW2, 1); mbar_init(sb + BOK, 256); mbar_init(sb + BKV, 1); mbar_init(sb + BKR, 1);
    asm volatile("fence.mbarrier_init.release.cluster;" ::: "memory");
  }
  if (!LDL8) asm volatile("griddepcontrol.launch_dependents;");
  if (wg == 0) {
    asm volatile("setmaxnreg.dec.sync.aligned.u32 40;");
    bar_sync(0, 384);
    if (tid == 32 && layer == 0 && PREFETCH_A) {
      asm volatile("griddepcontrol.wait;" ::: "memory");
      __nanosleep(PFB_DELAY);
      for (int i = 0; i < 32; i++) {
        const char* p = (const char*)((i & 1) ? wa0 : wa3) + (size_t)blockIdx.x * 61440 + (i >> 1) * 3840;
        asm volatile("cp.async.bulk.prefetch.L2.global [%0], 3840;" :: "l"(p) : "memory");
        __nanosleep(PREFETCH_A);
      }
    }
    if (w == 2) {
      bar_sync(4, 288);
      if (lane == 0) {
        if (KVREL) red_release(&sy->bkv_cnt[gq]);
        spin_count(&sy->bkv_cnt[gq], 16);
        mbar_arrive(sb + BKR);
      }
    }
    if (tid == 0) {
      if (BTPF) {
        asm volatile("prefetch.tensormap [%0];" :: "l"(&mx) : "memory"); asm volatile("prefetch.tensormap [%0];" :: "l"(&mw1) : "memory");
        asm volatile("prefetch.tensormap [%0];" :: "l"(&mos) : "memory"); asm volatile("prefetch.tensormap [%0];" :: "l"(&mo) : "memory");
      }
      if (BFL) { wait_count(&sy->pad1[0], nw2); asm volatile("fence.proxy.async.global;" ::: "memory"); }
      else asm volatile("griddepcontrol.wait;" ::: "memory");
      GT(2, 0);
      const int npre = BFL && rt >= tl::RT0 ? NST : 0;
      if (npre) {
#pragma unroll 1
        for (int c = 0; c < (int)NST; c++) { mbar_expect(sb + FULL + c * 8, STAGE); tma2d(sb + c * STAGE + 16384, &mw1, c * 64, gq * 240, sb + FULL + c * 8); }
        spin_count(&sy->pro[1 + rt - tl::RT0], 64);
        asm volatile("fence.proxy.async.global;" ::: "memory");
      }
#pragma unroll 1
      for (int c = 0; c < 10; c++) {
        const uint32_t st = c % NST, a = sb + st * STAGE, fb = sb + FULL + st * 8;
        if (c >= npre) {
          mbar_wait_long(sb + EMPTY + st * 8, ((c / NST) & 1) ^ 1);
          mbar_expect(fb, STAGE - (BHALF & 1) * 8192);
        }
        tma2d(a, &mx, c * 64, rt * 128, fb);
        if (c >= npre) tma2d(a + 16384, &mw1, c * 64, gq * 240, fb);
      }
      mbar_wait_long(sb + BKV, 0);
      mbar_expect(sb + BW2, 102400);
      PT(1, 0);
      for (int c = 0; c < 2; c++) bulk_load_plain(sb + W2 + c * 51200, g_wb2 + gq * 6400 + c * 3200, 51200, sb + BW2);
      mbar_wait_long(sb + BOK, 0);
      asm volatile("cp.async.bulk.tensor.2d.global.shared::cta.bulk_group [%0, {%2, %3}], [%1];" :: "l"(&mos), "r"(sb + OS), "r"(gq * 80), "r"(rt * 128) : "memory");
      asm volatile("cp.async.bulk.commit_group; cp.async.bulk.wait_group 0;" ::: "memory");
      publish_bulk<WFEN>(&sy->bo_cnt[rt]);
      spin_count(&sy->bo_cnt[rt], 8);
      fence_flag_to_bulk();
#pragma unroll 1
      for (int c = 0; c < 10; c++) {
        const uint32_t st = c < NST2 ? c : c - NST2, fb = sb + FULL2 + st * 8;
        if (c >= NST2) mbar_wait_long(sb + EMPTY2 + st * 8, 0);
        mbar_expect(fb, 16384 - (BHALF >> 1 & 1) * 8192);
        tma2d(sb + A2 + st * 16384, &mo, c * 64, rt * 128, fb);
      }
    }
  } else {
    asm volatile("setmaxnreg.inc.sync.aligned.u32 232;");
    bar_sync(0, 384);
    if (!BFL) asm volatile("griddepcontrol.wait;" ::: "memory");
    const int cw = wg - 1, g = lane >> 2, t = lane & 3, ct = tid - 128;
    const int row = cw * 64 + w * 16 + g;
    float rs[2], ms[2], cv[10];
    if (BFL) {
      mbar_wait_long(sb + FULL, 0);
#pragma unroll
      for (int e = 0; e < 2; e++) asm volatile("ld.global.cg.v2.f32 {%0,%1}, [%2];" : "=f"(ms[e]), "=f"(rs[e]) : "l"(&sy->rstat[rt * 128 + row + 8 * e]) : "memory");
#pragma unroll
      for (int i = 0; i < 10; i++) asm volatile("ld.global.cg.f32 %0, [%1];" : "=f"(cv[i]) : "l"(g_cs + i * 3 * DM + gq * 240 + min(ct, 239)) : "memory");
    } else {
      float cs = 0.f;
      if (ct < 240) {
#pragma unroll
        for (int i = 0; i < 10; i++) cs += __ldcg(g_cs + i * 3 * DM + gq * 240 + ct);
      }
      if (!CTAIL)
#pragma unroll
      for (int e = 0; e < 2; e++) {
        const float2 st = __ldcg(&sy->rstat[rt * 128 + row + 8 * e]);
        const float m = st.x * (1.0f / DM);
        rs[e] = rsqrtf(fmaxf(st.y * (1.0f / DM) - m * m, 0.f) + 1e-5f);
        ms[e] = -m * rs[e];
      }
      if (ct < 240) sts32(sb + CS + ct * 4, __float_as_uint(cs));
      bar_sync(3, 256);
      if (CTAIL) {
        mbar_wait_long(sb + FULL, 0);
#pragma unroll
        for (int e = 0; e < 2; e++) asm volatile("ld.global.cg.v2.f32 {%0,%1}, [%2];" : "=f"(ms[e]), "=f"(rs[e]) : "l"(&sy->rstat[rt * 128 + row + 8 * e]) : "memory");
      }
    }
    uint32_t res[20];
    const int off = (rt * 128 + row) * DM + gq * 80 + 2 * t;
    {
      float d[120];
#pragma unroll
      for (int i = 0; i < 120; i++) d[i] = 0.f;
      for (int c = 0; c < 10; c++) {
        const uint32_t st = c % NST, a = sb + st * STAGE;
        mbar_wait_long(sb + FULL + st * 8, (c / NST) & 1);
        if (c == 0 && ct == 0) PT(1, 15);
        const uint64_t da = mkdesc(a + cw * 8192, 16, 1024, 1), db = mkdesc(a + 16384, 16, 1024, 1);
        wg_fence();
#pragma unroll
        for (int k = 0; k < 4; k++) wgmma_n240_nn(d, da + k * 2, db + k * 2, c | k);
        wg_commit();
        if (c > 0) { wg_wait<1>(); if (lane == 0) mbar_arrive(sb + EMPTY + ((c - 1) % NST) * 8); }
        if (BFL && c == 8) {
          float cs = 0.f;
#pragma unroll
          for (int i = 0; i < 10; i++) cs += cv[i];
          if (ct < 240) sts32(sb + CS + ct * 4, __float_as_uint(cs));
        }
      }
      if (BFL) bar_sync(3, 256);
      wg_wait<0>();
      if (lane == 0) mbar_arrive(sb + EMPTY + (9 % NST) * 8);
      if (ct == 0) PT(1, 2);
      if (CTAIL)
#pragma unroll
      for (int e = 0; e < 2; e++) {
        const float m = ms[e] * (1.0f / DM);
        rs[e] = rsqrtf(fmaxf(rs[e] * (1.0f / DM) - m * m, 0.f) + 1e-5f);
        ms[e] = -m * rs[e];
      }
#pragma unroll
      for (int i = 0; i < 30; i++) {
        const float2 c = lds64f(sb + CS + (8 * i + 2 * t) * 4);
        d[4 * i] = fmaf(c.x, ms[0], d[4 * i] * rs[0]); d[4 * i + 1] = fmaf(c.y, ms[0], d[4 * i + 1] * rs[0]);
        d[4 * i + 2] = fmaf(c.x, ms[1], d[4 * i + 2] * rs[1]); d[4 * i + 3] = fmaf(c.y, ms[1], d[4 * i + 3] * rs[1]);
      }
      if (ct == 0) PT(1, 11);
      bar_sync(3, 256);
      if (W2E && ct == 0) mbar_arrive(sb + BKV);
      feature_map(&d[40], sb + PHI + row * 336 + t * 80);
      if (ct == 0) PT(1, 12);
#pragma unroll
      for (int i = 0; i < 10; i++) {
        const int c = i * 8 + 2 * t;
        const uint32_t a = sb + VS + row * 208 + (c / 20) * 48 + (c % 20) * 2;
        sts32(a, pack_bf16(d[80 + 4 * i], d[81 + 4 * i])); sts32(a + 8 * 208, pack_bf16(d[82 + 4 * i], d[83 + 4 * i]));
      }
      { const uint32_t a = sb + VS + row * 208 + t * 48 + 40; sts64(a, 0x3F80u, 0u); sts64(a + 8 * 208, 0x3F80u, 0u); }
      bar_sync(3, 256);
      if (ct == 0) PT(1, 13);
      {
        float kv[5][4];
#pragma unroll
        for (int i = 0; i < 20; i++) kv[i >> 2][i & 3] = 0.f;
        const uint32_t pa = sb + PHI + ((lane >> 4) * 8 + (lane & 7)) * 336 + w * 80 + ((lane >> 3) & 1) * 16;
        const uint32_t va = sb + VS + lane * 208 + w * 48;
#pragma unroll
        for (int k2 = 0; k2 < 4; k2++) {
          uint32_t b[3][4];
#pragma unroll
          for (int n = 0; n < 3; n++) ldsm4t(b[n], va + k2 * 32 * 208 + n * 16);
#pragma unroll
          for (int kk = 0; kk < 2; kk++) {
            uint32_t a[4], a2[4];
            ldsm4t(a, pa + (k2 * 32 + kk * 16) * 336 + cw * 32);
            ldsm4t(a2, pa + (k2 * 32 + kk * 16) * 336 + 64);
#pragma unroll
            for (int n = 0; n < 3; n++) mma16816(kv[n], a, b[n][2 * kk], b[n][2 * kk + 1]);
            if (cw == 0) { mma16816(kv[3], a2, b[0][2 * kk], b[0][2 * kk + 1]); mma16816(kv[4], a2, b[1][2 * kk], b[1][2 * kk + 1]); }
            else mma16816(kv[3], a2, b[2][2 * kk], b[2][2 * kk + 1]);
          }
        }
        float* p = g_bkv + ((gq * 4 + w) * BF + g) * 24 + 2 * t;
        PINF(kv[0][0]); PINF(kv[3][0]);
        if (ct == 0) PT(1, 14);
#pragma unroll
        for (int n = 0; n < 3; n++) {
          asm volatile("red.relaxed.gpu.global.add.v2.f32 [%0], {%1,%2};" :: "l"(p + cw * 16 * 24 + n * 8), "f"(kv[n][0]), "f"(kv[n][1]) : "memory");
          asm volatile("red.relaxed.gpu.global.add.v2.f32 [%0], {%1,%2};" :: "l"(p + (cw * 16 + 8) * 24 + n * 8), "f"(kv[n][2]), "f"(kv[n][3]) : "memory");
        }
        asm volatile("red.relaxed.gpu.global.add.v2.f32 [%0], {%1,%2};" :: "l"(p + 32 * 24 + cw * 16), "f"(kv[3][0]), "f"(kv[3][1]) : "memory");
        if (cw == 0) asm volatile("red.relaxed.gpu.global.add.v2.f32 [%0], {%1,%2};" :: "l"(p + 32 * 24 + 8), "f"(kv[4][0]), "f"(kv[4][1]) : "memory");
      }
      if (ct == 0) PT(1, 3);
      if (LDL8 == 4) asm volatile("griddepcontrol.launch_dependents;");
      if (KVF == 1) __threadfence();
      bar_sync(4, 288);
      if (!KVREL) { if (ct == 0) red_release(&sy->bkv_cnt[gq]); __syncwarp(); }
      if (ct == 0) PT(1, 9);
      if (!W2E && ct == 0) mbar_arrive(sb + BKV);
      feature_map(&d[0], sb + PHQ + row * 336 + t * 80);
    }
    if (ct == 0) PT(1, 4);
#pragma unroll
    for (int i = 0; i < 10; i++) { res[2 * i] = __ldcg((const uint32_t*)(g_xa + off + i * 8)); res[2 * i + 1] = __ldcg((const uint32_t*)(g_xa + off + i * 8 + 8 * DM)); }
    mbar_wait_long(sb + BKR, 0);
    if (LDL8 == 1) asm volatile("griddepcontrol.launch_dependents;");
    if (KVF == 2) __threadfence();
    if (KVF == 3) __nanosleep(1500);
    if (ct == 0) PT(1, 5);
    {
      float4 a[4];
#pragma unroll
      for (int i = 0; i < 4; i++) a[i] = __ldcg((const float4*)(g_bkv + gq * 4 * BF * 24) + min(ct + i * 256, 4 * BF * 6 - 1));
#pragma unroll
      for (int i = 0; i < 4; i++) if (ct + i * 256 < 4 * BF * 6) sts64(sb + KVS + (ct + i * 256) * 8, pack_bf16(a[i].x, a[i].y), pack_bf16(a[i].z, a[i].w));
    }
    bar_sync(3, 256);
    {
      float o[4][3][4];
#pragma unroll
      for (int hh = 0; hh < 4; hh++) {
        uint32_t a0[4], a1[4], a2[2], c[4];
        const uint32_t qa = sb + PHQ + (cw * 64 + w * 16 + (lane & 15)) * 336 + hh * 80;
        ldsm4(a0, qa + (lane >> 4) * 16); ldsm4(a1, qa + 32 + (lane >> 4) * 16); ldsm2(a2, qa + 64);
        ldsm4t(c, sb + KVS + hh * 1920 + (32 + (lane & 7)) * 48 + min(lane >> 3, 2) * 16);
#pragma unroll
        for (int n = 0; n < 3; n++) {
          uint32_t b[4];
          ldsm4t(b, sb + KVS + hh * 1920 + lane * 48 + n * 16);
          o[hh][n][0] = o[hh][n][1] = o[hh][n][2] = o[hh][n][3] = 0.f;
          mma16816(o[hh][n], a0, b[0], b[1]); mma16816(o[hh][n], a1, b[2], b[3]); mma1688(o[hh][n], a2[0], a2[1], c[n]);
        }
      }
      const uint32_t oa = sb + OS + row * 160 + t * 4;
#pragma unroll
      for (int hh = 0; hh < 4; hh++) {
        const float i0 = __fdividef(1.0f, __shfl_sync(0xffffffffu, o[hh][2][0], (lane & 28) + 2) + 1e-6f);
        const float i1 = __fdividef(1.0f, __shfl_sync(0xffffffffu, o[hh][2][2], (lane & 28) + 2) + 1e-6f);
#pragma unroll
        for (int n = 0; n < 3; n++)
          if (n < 2 || t < 2) {
            sts32(oa + hh * 40 + n * 16, pack_bf16(o[hh][n][0] * i0, o[hh][n][1] * i0));
            sts32(oa + hh * 40 + n * 16 + 8 * 160, pack_bf16(o[hh][n][2] * i1, o[hh][n][3] * i1));
          }
      }
      fence_async();
    }
    if (ct == 0) PT(1, 6);
    mbar_arrive(sb + BOK);
    if (LDL8 == 2) asm volatile("griddepcontrol.launch_dependents;");
    float d[40];
#pragma unroll
    for (int i = 0; i < 40; i++) d[i] = 0.f;
    mbar_wait_long(sb + BW2, 0);
    for (int c = 0; c < 10; c++) {
      const uint32_t st = c % NST2;
      mbar_wait_long(sb + FULL2 + st * 8, c / NST2);
      if (ct == 0 && c == 0) PT(1, 7);
      if (LDL8 == 3 && c == 0) asm volatile("griddepcontrol.launch_dependents;");
      const uint64_t da = mkdesc(sb + A2 + st * 16384 + cw * 8192, 16, 1024, 1), db = mkdesc(sb + W2 + c * 10240, 2048, 256, 3);
      wg_fence();
#pragma unroll
      for (int k = 0; k < 4; k++) wgmma_n80_nt(d, da + k * 2, db + k * 32, c | k);
      wg_commit();
      if (c > 0 && c <= 10 - NST2) { wg_wait<1>(); if (lane == 0) mbar_arrive(sb + EMPTY2 + (c - 1) * 8); }
    }
    wg_wait<0>();
    if (ct == 0) PT(1, 10);
#pragma unroll
    for (int i = 0; i < 10; i++) {
      *(uint32_t*)(out + off + i * 8) = pack_bf16(d[4 * i] + __uint_as_float(res[2 * i] << 16), d[4 * i + 1] + __uint_as_float(res[2 * i] & 0xFFFF0000u));
      *(uint32_t*)(out + off + i * 8 + 8 * DM) = pack_bf16(d[4 * i + 2] + __uint_as_float(res[2 * i + 1] << 16), d[4 * i + 3] + __uint_as_float(res[2 * i + 1] & 0xFFFF0000u));
    }
    if (ct == 0) PT(1, 8);
    if (ct == 0) GT(2, 1);
  }
}

typedef CUresult (*EncodeFn)(CUtensorMap*, CUtensorMapDataType, cuuint32_t, void*, const cuuint64_t*, const cuuint64_t*, const cuuint32_t*,
                             const cuuint32_t*, CUtensorMapInterleave, CUtensorMapSwizzle, CUtensorMapL2promotion, CUtensorMapFloatOOBfill);
static EncodeFn g_enc = nullptr;
static void make_map(CUtensorMap* m, const void* p, uint64_t cols, uint64_t rows, uint32_t bc, uint32_t br, bool swz = true) {
  cuuint64_t dims[2] = {cols, rows}; cuuint64_t strides[1] = {cols * 2}; cuuint32_t box[2] = {bc, br}; cuuint32_t es[2] = {1, 1};
  g_enc(m, CU_TENSOR_MAP_DATA_TYPE_BFLOAT16, 2, (void*)p, dims, strides, box, es, CU_TENSOR_MAP_INTERLEAVE_NONE, swz ? CU_TENSOR_MAP_SWIZZLE_128B : CU_TENSOR_MAP_SWIZZLE_NONE,
        CU_TENSOR_MAP_L2_PROMOTION_L2_256B, CU_TENSOR_MAP_FLOAT_OOB_FILL_NONE);
}
static void make_map3(CUtensorMap* m, const void* p, uint64_t cols, uint64_t rows, uint32_t cw, uint32_t br, uint32_t bch) {
  cuuint64_t dims[3] = {cw, rows, cols / cw}; cuuint64_t strides[2] = {cols * 2, cw * 2}; cuuint32_t box[3] = {cw, br, bch}; cuuint32_t es[3] = {1, 1, 1};
  g_enc(m, CU_TENSOR_MAP_DATA_TYPE_BFLOAT16, 3, (void*)p, dims, strides, box, es, CU_TENSOR_MAP_INTERLEAVE_NONE,
        cw == 64 ? CU_TENSOR_MAP_SWIZZLE_128B : cw == 32 ? CU_TENSOR_MAP_SWIZZLE_64B : CU_TENSOR_MAP_SWIZZLE_32B, CU_TENSOR_MAP_L2_PROMOTION_L2_256B, CU_TENSOR_MAP_FLOAT_OOB_FILL_NONE);
}
template <typename T> static void* sym(T& s) { void* p = nullptr; cudaGetSymbolAddress(&p, s); return p; }
template <typename... KA, typename... A>
static void launch(void (*k)(KA...), int grid, int smem, bool pdl, A... a) {
  cudaLaunchConfig_t cfg = {};
  cfg.gridDim = dim3(grid); cfg.blockDim = dim3(384); cfg.dynamicSmemBytes = smem; cfg.stream = cudaStreamPerThread;
  cudaLaunchAttribute at[1]; at[0].id = cudaLaunchAttributeProgrammaticStreamSerialization; at[0].val.programmaticStreamSerializationAllowed = 1;
  cfg.attrs = at; cfg.numAttrs = pdl ? 1 : 0;
  cudaLaunchKernelEx(&cfg, k, a...);
}

constexpr int dev_layers = 2, dev_pdl = 1;
#define EV(i)
extern "C" void kernel_launch(void* const* d_in, const int* in_sizes, int n_in, void* d_out, int out_size) {
  static int nsm = 0;
  if (!g_enc) {
    void* fn = nullptr; cudaDriverEntryPointQueryResult st;
    cudaGetDriverEntryPoint("cuTensorMapEncodeTiled", &fn, cudaEnableDefault, &st);
    g_enc = (EncodeFn)fn;
    cudaFuncSetAttribute(chain_kernel, cudaFuncAttributeMaxDynamicSharedMemorySize, ch::SMEM);
    cudaFuncSetAttribute(worker_kernel, cudaFuncAttributeMaxDynamicSharedMemorySize, wk::SMEM);
    cudaFuncSetAttribute(layerb_kernel, cudaFuncAttributeMaxDynamicSharedMemorySize, bk::SMEM);
    cudaDeviceGetAttribute(&nsm, cudaDevAttrMultiProcessorCount, 0);
  }
  CUtensorMap mq, mk, mv, mo, mx, wx, wq, woa, wos, wwo, wxa, wacc, wwb, bx, bw1, bo, bos;
  make_map(&mq, d_in[2], HD, DM, 64, 128); make_map(&mk, d_in[3], HD, DM, 64, 128); make_map(&mv, d_in[4], HD, DM, 64, 128);
  make_map(&mo, d_in[5], DM, HD, 64, 192); make_map3(&mx, sym(g_xn), DM, S_LEN, 64, 32, 5);
  make_map(&wx, sym(g_xn), DM, S_LEN, 64, 128); make_map3(&wq, d_in[2], HD, DM, 64, 64, 3);
  make_map(&woa, sym(g_o), HD, S_LEN, 64, 128); make_map3(&wos, sym(g_o), HD, S_LEN, 64, 64, 3); make_map3(&wwo, d_in[5], DM, HD, 32, 64, 5);
  CUtensorMap toa;
  make_map(&toa, sym(g_o), HD, S_LEN, 64, 64);
  make_map3(&wxa, sym(g_xa), DM, S_LEN, 32, 64, 5);
  if (BSL) make_map3(&wacc, sym(g_sl), DM, NSL * 128, 32, 64, 5);
  else {
    cuuint64_t dims[3] = {32, 2 * ACC_ROWS, DM / 32}, strides[2] = {DM * 4, 128}; cuuint32_t box[3] = {32, 64, 5}, es[3] = {1, 1, 1};
    g_enc(&wacc, CU_TENSOR_MAP_DATA_TYPE_FLOAT32, 3, sym(g_acc), dims, strides, box, es, CU_TENSOR_MAP_INTERLEAVE_NONE, CU_TENSOR_MAP_SWIZZLE_128B,
          CU_TENSOR_MAP_L2_PROMOTION_NONE, CU_TENSOR_MAP_FLOAT_OOB_FILL_NONE);
  }
  make_map(&wwb, d_in[8], 3 * DM, DM, 80, 64, false);
  make_map(&bx, sym(g_xa), DM, S_LEN, 64, (BHALF & 1) ? 64 : 128); make_map(&bw1, sym(g_wb1), DM, 3 * DM, 64, 240);
  make_map(&bo, sym(g_bo), DM, S_LEN, 64, (BHALF & 2) ? 64 : 128); make_map(&bos, sym(g_bo), DM, S_LEN, 80, 128, false);
  cudaStream_t st = cudaStreamPerThread;
  for (int layer = 0; layer < dev_layers; layer++) {
    const bf16* x = layer == 0 ? (const bf16*)d_in[0] : (const bf16*)sym(g_xb);
    Sync* sy = (Sync*)sym(g_sync) + layer;
    EV(layer * 5);
    EV(layer * 5 + 1);
    launch(chain_kernel, 96, ch::SMEM, dev_pdl && layer, mq, mk, mv, mo, mx, (const bf16*)d_in[1], x, 0u, layer, toa, wwo);
    EV(layer * 5 + 2);
    launch(worker_kernel, WGRID ? WGRID : CTAIL ? nsm - 96 : nsm, wk::SMEM, dev_pdl, layer, sy, x, (const bf16*)d_in[9], (const bf16*)d_in[10], wx, wq, woa, wos, wwo, wxa, wacc, wwb);
    EV(layer * 5 + 3);
    launch(layerb_kernel, layer == 0 && PFA_N ? max(128, min(nsm, 132)) : 128, bk::SMEM, dev_pdl, layer, 2u * (nsm - 96), sy, x, layer == 0 ? (bf16*)sym(g_xb) : (bf16*)d_out,
           (const void*)d_in[2], (const void*)d_in[3], (const void*)d_in[4], (const void*)d_in[5], bx, bw1, bo, bos);
    EV(layer * 5 + 4);
  }
}
```

```cpp
#include <cuda_runtime.h>
#include <cuda_bf16.h>
#include <cuda_fp16.h>
#include <cuda.h>
#include <stdint.h>

typedef __nv_bfloat16 bf16;

constexpr int S_LEN = 2048, DM = 640, NH = 32, DH = 192, NMEM = 8, SEG = 32, NSEG = 64;
constexpr int HD = NH * DH;
constexpr int NKEY = NMEM + SEG;
constexpr int SLAB = 64 * NKEY * 2;
constexpr int AR_STEP_BYTES = 24 * 1024;
constexpr int BDH = 20, BF = 40;

__device__ __align__(1024) bf16 g_xn[S_LEN * DM];
__device__ __align__(1024) bf16 g_kv[(size_t)NSEG * NH * 2 * DH * NKEY];
__device__ __align__(1024) bf16 g_o[(size_t)S_LEN * HD];
__device__ __align__(1024) bf16 g_xa[S_LEN * DM];
__device__ __align__(1024) bf16 g_xb[S_LEN * DM];
__device__ __align__(32768) uint32_t g_ar[NSEG * AR_STEP_BYTES / 4];
#define RTS 10
constexpr int RT_SPLIT = RTS;
constexpr int ACC_ROWS = (16 - RT_SPLIT) * 128;
#define BSL 1
#define FROWS 32
__device__ __align__(1024) float g_acc[BSL ? 256 : 2 * ACC_ROWS * DM];
#define BFL 0
#define CTAIL 1
constexpr int NSL = 48;
__device__ __align__(1024) bf16 g_sl[BSL ? NSL * 128 * DM : 512];
__device__ __align__(1024) float g_cs[10 * 3 * DM];
__device__ __align__(1024) bf16 g_wb1[3 * DM * DM];
__device__ __align__(1024) uint4 g_wb2[DM * DM / 8];
__device__ __align__(1024) bf16 g_bo[S_LEN * DM];
__device__ __align__(1024) uint4 g_qf[16 * NH * 12 * 256];
struct __align__(1024) Sync {
  uint32_t kv[NSEG * NH];
  uint32_t o[16 * 16];
  uint32_t bkv_cnt[8], bo_cnt[16];
  uint32_t pro[4];
  uint32_t wmax[96];
  uint32_t pad1[4];
  uint32_t head, pad0[31];
  uint32_t zeroed, pad[31];
  uint32_t gst[16 * NH];
  uint32_t wcnt[16 * 8];
  float2 rstat[S_LEN];
};
__device__ __align__(1024) Sync g_sync[2];
#define BLN 0
#define WREL 0
#define WLN 2
static_assert(!(BLN && WLN), "layer norm");
#define NPRO ((WLN >> layer & 1) ? 128 : 96)
__device__ __align__(1024) float2 g_bst[BLN ? 2048 * 8 : 2];
__device__ uint32_t g_kw;
__device__ __align__(1024) float g_bkv[NH * BF * 24];

#define GT(k, e)
#define WS(e_, v_)
#undef TLOG
#undef TM
#undef PT
#undef XT
#define XT(i, e)
#define TLOG(id, ta)
#define TM(i)
#define PT(k, e)
#define DEVI __device__ __forceinline__
constexpr int SPIN_LIMIT = 20000;
DEVI uint32_t smem_u32(const void* p) { return (uint32_t)__cvta_generic_to_shared(p); }
DEVI uint32_t clk32() { uint64_t c; asm volatile("mov.u64 %0, %%clock64;" : "=l"(c)); return (uint32_t)c; }
DEVI uint32_t mapa(uint32_t a, uint32_t r) { uint32_t o; asm("mapa.shared::cluster.u32 %0, %1, %2;" : "=r"(o) : "r"(a), "r"(r)); return o; }
DEVI void mbar_init(uint32_t bar, uint32_t cnt) { asm volatile("mbarrier.init.shared::cta.b64 [%0], %1;" :: "r"(bar), "r"(cnt) : "memory"); }
DEVI void mbar_expect(uint32_t bar, uint32_t bytes) { asm volatile("mbarrier.arrive.expect_tx.shared::cta.b64 _, [%0], %1;" :: "r"(bar), "r"(bytes) : "memory"); }
DEVI void mbar_arrive(uint32_t bar) { asm volatile("mbarrier.arrive.shared::cta.b64 _, [%0];" :: "r"(bar) : "memory"); }
DEVI void mbar_arrive_cluster(uint32_t rbar) { asm volatile("mbarrier.arrive.relaxed.cluster.shared::cluster.b64 _, [%0];" :: "r"(rbar) : "memory"); }
DEVI bool mbar_try(uint32_t bar, uint32_t par) {
  uint32_t ok;
  asm volatile("{.reg .pred p; mbarrier.try_wait.parity.shared::cta.b64 p, [%1], %2; selp.u32 %0, 1, 0, p;}" : "=r"(ok) : "r"(bar), "r"(par) : "memory");
  return ok;
}
DEVI void mbar_wait(uint32_t bar, uint32_t par) {
  int n = 0;
  while (!mbar_try(bar, par) && ++n < SPIN_LIMIT) {}
}
DEVI void bar_sync(int id, int n) { asm volatile("bar.sync %0, %1;" :: "r"(id), "r"(n) : "memory"); }
DEVI void bar_arrive(int id, int n) { asm volatile("bar.arrive %0, %1;" :: "r"(id), "r"(n) : "memory"); }
DEVI void fence_async() { asm volatile("fence.proxy.async.shared::cta;" ::: "memory"); }
#define RFEN 2
#define CEND 1
#define XFEN 1
#define WFEN 2
template <int M> DEVI void publish_bulk(uint32_t* flag) {
  if (M == 1) asm volatile("fence.proxy.async;" ::: "memory");
  if (M == 2) asm volatile("red.release.gpu.global.add.u32 [%0], 1;" :: "l"(flag) : "memory");
  else asm volatile("red.relaxed.gpu.global.add.u32 [%0], 1;" :: "l"(flag) : "memory");
}
DEVI void fence_flag_to_bulk() {
  if (RFEN == 0) asm volatile("fence.proxy.async;" ::: "memory");
  if (RFEN == 1) asm volatile("fence.proxy.async.global;" ::: "memory");
}
DEVI void cluster_sync_full() { asm volatile("barrier.cluster.arrive.release.aligned; barrier.cluster.wait.acquire.aligned;" ::: "memory"); }
DEVI void tma2d(uint32_t dst, const CUtensorMap* m, int c0, int c1, uint32_t bar) {
  asm volatile("cp.async.bulk.tensor.2d.shared::cluster.global.mbarrier::complete_tx::bytes [%0], [%1, {%3, %4}], [%2];"
               :: "r"(dst), "l"(m), "r"(bar), "r"(c0), "r"(c1) : "memory");
}
DEVI void tma3d(uint32_t dst, const CUtensorMap* m, int c0, int c1, int c2, uint32_t bar) {
  asm volatile("cp.async.bulk.tensor.3d.shared::cluster.global.mbarrier::complete_tx::bytes [%0], [%1, {%3, %4, %5}], [%2];"
               :: "r"(dst), "l"(m), "r"(bar), "r"(c0), "r"(c1), "r"(c2) : "memory");
}
DEVI void tma3d_mc(uint32_t dst, const CUtensorMap* m, int c0, int c1, int c2, uint32_t bar, uint16_t mask) {
  asm volatile("cp.async.bulk.tensor.3d.shared::cluster.global.mbarrier::complete_tx::bytes.multicast::cluster [%0], [%1, {%3, %4, %5}], [%2], %6;"
               :: "r"(dst), "l"(m), "r"(bar), "r"(c0), "r"(c1), "r"(c2), "h"(mask) : "memory");
}
DEVI void tma3d_prefetch(const CUtensorMap* m, int c0, int c1, int c2) {
  asm volatile("cp.async.bulk.prefetch.tensor.3d.L2.global [%0, {%1, %2, %3}];" :: "l"(m), "r"(c0), "r"(c1), "r"(c2) : "memory");
}
DEVI void tma2d_prefetch(const CUtensorMap* m, int c0, int c1) {
  asm volatile("cp.async.bulk.prefetch.tensor.2d.L2.global [%0, {%1, %2}];" :: "l"(m), "r"(c0), "r"(c1) : "memory");
}
#define EVF 7
DEVI uint64_t stream_policy() { uint64_t p; asm("createpolicy.fractional.L2::evict_first.b64 %0, 1.0;" : "=l"(p)); return p; }
DEVI void bulk_store(void* g, uint32_t s, uint32_t bytes) {
  if (EVF & 1) asm volatile("cp.async.bulk.global.shared::cta.bulk_group.L2::cache_hint [%0], [%1], %2, %3;" :: "l"(g), "r"(s), "r"(bytes), "l"(stream_policy()) : "memory");
  else asm volatile("cp.async.bulk.global.shared::cta.bulk_group [%0], [%1], %2;" :: "l"(g), "r"(s), "r"(bytes) : "memory");
}
DEVI void ldsm4(uint32_t (&r)[4], uint32_t a) {
  asm volatile("ldmatrix.sync.aligned.m8n8.x4.shared.b16 {%0,%1,%2,%3}, [%4];" : "=r"(r[0]), "=r"(r[1]), "=r"(r[2]), "=r"(r[3]) : "r"(a) : "memory");
}
DEVI void ldsm4t(uint32_t (&r)[4], uint32_t a) {
  asm volatile("ldmatrix.sync.aligned.m8n8.x4.trans.shared.b16 {%0,%1,%2,%3}, [%4];" : "=r"(r[0]), "=r"(r[1]), "=r"(r[2]), "=r"(r[3]) : "r"(a) : "memory");
}
DEVI void ldsm4t_p(uint32_t* r, uint32_t a) {
  asm volatile("ldmatrix.sync.aligned.m8n8.x4.trans.shared.b16 {%0,%1,%2,%3}, [%4];" : "=r"(r[0]), "=r"(r[1]), "=r"(r[2]), "=r"(r[3]) : "r"(a) : "memory");
}
DEVI void ldsm2(uint32_t (&r)[2], uint32_t a) {
  asm volatile("ldmatrix.sync.aligned.m8n8.x2.shared.b16 {%0,%1}, [%2];" : "=r"(r[0]), "=r"(r[1]) : "r"(a) : "memory");
}
DEVI void stsm4(uint32_t a, uint32_t r0, uint32_t r1, uint32_t r2, uint32_t r3) {
  asm volatile("stmatrix.sync.aligned.m8n8.x4.shared.b16 [%0], {%1,%2,%3,%4};" :: "r"(a), "r"(r0), "r"(r1), "r"(r2), "r"(r3) : "memory");
}
DEVI void mma16816(float (&d)[4], const uint32_t* a, uint32_t b0, uint32_t b1) {
  asm volatile("mma.sync.aligned.m16n8k16.row.col.f32.bf16.bf16.f32 {%0,%1,%2,%3}, {%4,%5,%6,%7}, {%8,%9}, {%0,%1,%2,%3};"
               : "+f"(d[0]), "+f"(d[1]), "+f"(d[2]), "+f"(d[3]) : "r"(a[0]), "r"(a[1]), "r"(a[2]), "r"(a[3]), "r"(b0), "r"(b1));
}
DEVI void mma1688(float (&d)[4], uint32_t a0, uint32_t a1, uint32_t b0) {
  asm volatile("mma.sync.aligned.m16n8k8.row.col.f32.bf16.bf16.f32 {%0,%1,%2,%3}, {%4,%5}, {%6}, {%0,%1,%2,%3};"
               : "+f"(d[0]), "+f"(d[1]), "+f"(d[2]), "+f"(d[3]) : "r"(a0), "r"(a1), "r"(b0));
}
DEVI uint32_t pack_bf16(float lo, float hi) { uint32_t r; asm("cvt.rn.bf16x2.f32 %0, %1, %2;" : "=r"(r) : "f"(hi), "f"(lo)); return r; }
DEVI uint32_t pack_f16(float lo, float hi) { uint32_t r; asm("cvt.rn.f16x2.f32 %0, %1, %2;" : "=r"(r) : "f"(hi), "f"(lo)); return r; }
DEVI uint32_t f16x2_to_bf16x2(uint32_t h) { float2 f = __half22float2(*reinterpret_cast<__half2*>(&h)); return pack_bf16(f.x, f.y); }
DEVI void sts32(uint32_t a, uint32_t v) { asm volatile("st.shared.u32 [%0], %1;" :: "r"(a), "r"(v) : "memory"); }
DEVI void sts64(uint32_t a, uint32_t v0, uint32_t v1) { asm volatile("st.shared.v2.u32 [%0], {%1,%2};" :: "r"(a), "r"(v0), "r"(v1) : "memory"); }
DEVI void sts128(uint32_t a, uint32_t v0, uint32_t v1, uint32_t v2, uint32_t v3) { asm volatile("st.shared.v4.u32 [%0], {%1,%2,%3,%4};" :: "r"(a), "r"(v0), "r"(v1), "r"(v2), "r"(v3) : "memory"); }
DEVI uint32_t lds32(uint32_t a) { uint32_t v; asm volatile("ld.shared.u32 %0, [%1];" : "=r"(v) : "r"(a) : "memory"); return v; }
DEVI float2 lds64f(uint32_t a) { float2 v; asm volatile("ld.shared.v2.f32 {%0,%1}, [%2];" : "=f"(v.x), "=f"(v.y) : "r"(a) : "memory"); return v; }
DEVI void lds128(uint32_t (&r)[4], uint32_t a) { asm volatile("ld.shared.v4.u32 {%0,%1,%2,%3}, [%4];" : "=r"(r[0]), "=r"(r[1]), "=r"(r[2]), "=r"(r[3]) : "r"(a) : "memory"); }
DEVI void st_async64(uint32_t a, float x, float y, uint32_t bar) {
  asm volatile("st.async.weak.shared::cluster.mbarrier::complete_tx::bytes.v2.f32 [%0], {%1,%2}, [%3];" :: "r"(a), "f"(x), "f"(y), "r"(bar) : "memory");
}
DEVI void st_async32(uint32_t a, uint32_t x, uint32_t bar) {
  asm volatile("st.async.weak.shared::cluster.mbarrier::complete_tx::bytes.b32 [%0], %1, [%2];" :: "r"(a), "r"(x), "r"(bar) : "memory");
}
DEVI void ld_relaxed128(uint32_t (&r)[4], const void* p) {
  asm volatile("ld.relaxed.gpu.global.v4.u32 {%0,%1,%2,%3}, [%4];" : "=r"(r[0]), "=r"(r[1]), "=r"(r[2]), "=r"(r[3]) : "l"(p) : "memory");
}
DEVI void red_f16x2(void* p, uint32_t v) { asm volatile("red.relaxed.gpu.global.add.noftz.f16x2 [%0], %1;" :: "l"(p), "r"(v) : "memory"); }
DEVI void red_f16x2_v4(void* p, uint32_t a, uint32_t b, uint32_t c, uint32_t d) {
  asm volatile("red.relaxed.gpu.global.add.noftz.v4.f16x2 [%0], {%1,%2,%3,%4};" :: "l"(p), "r"(a), "r"(b), "r"(c), "r"(d) : "memory");
}
DEVI void red_add2(float2* p, float a, float b) { asm volatile("red.relaxed.gpu.global.add.v2.f32 [%0], {%1,%2};" :: "l"(p), "f"(a), "f"(b) : "memory"); }
DEVI float rcp(float x) { float y; asm("rcp.approx.ftz.f32 %0, %1;" : "=f"(y) : "f"(x)); return y; }
DEVI float ex2(float x) { float y; asm("ex2.approx.ftz.f32 %0, %1;" : "=f"(y) : "f"(x)); return y; }
DEVI uint64_t mkdesc(uint32_t addr, uint32_t lbo, uint32_t sbo, uint32_t swz) {
  return (uint64_t)((addr & 0x3FFFF) >> 4) | ((uint64_t)(lbo >> 4) << 16) | ((uint64_t)(sbo >> 4) << 32) | ((uint64_t)swz << 62);
}
DEVI void wg_fence() { asm volatile("wgmma.fence.sync.aligned;" ::: "memory"); }
DEVI void wg_commit() { asm volatile("wgmma.commit_group.sync.aligned;" ::: "memory"); }
template <int N> DEVI void wg_wait() { asm volatile("wgmma.wait_group.sync.aligned %0;" :: "n"(N) : "memory"); }
#define ACC4(d, o) "+f"(d[o]), "+f"(d[o + 1]), "+f"(d[o + 2]), "+f"(d[o + 3])
constexpr uint32_t DHI_SW128 = (1024u >> 4) | (1u << 30);
DEVI uint32_t desc_lo(uint32_t addr, uint32_t lbo) { return ((addr & 0x3FFFF) >> 4) | ((lbo >> 4) << 16); }
template <int OB_, int ACC> DEVI void wgmma_rs_n32(float (&d)[16], const uint32_t* a, uint32_t b) {
  asm volatile("{.reg .b64 db; .reg .b32 tb; add.u32 tb, %20, %21; mov.b64 db, {tb, %22};\n"
               "wgmma.mma_async.sync.aligned.m64n32k16.f32.bf16.bf16 {%0,%1,%2,%3,%4,%5,%6,%7,%8,%9,%10,%11,%12,%13,%14,%15}, {%16,%17,%18,%19}, db, %23, 1, 1, 0;}"
               : ACC4(d, 0), ACC4(d, 4), ACC4(d, 8), ACC4(d, 12) : "r"(a[0]), "r"(a[1]), "r"(a[2]), "r"(a[3]), "r"(b), "n"(OB_ >> 4), "n"(DHI_SW128), "n"(ACC));
}
template <int K0, int K1, int ACC = 1> struct Unroll {
  static DEVI void kbulk(float (&d)[16], const uint32_t* W, uint32_t x) { wgmma_rs_n32<(K0 >> 2) * 4096 + (K0 & 3) * 32, ACC>(d, W + K0 * 4, x); Unroll<K0 + 1, K1>::kbulk(d, W, x); }
};
template <int K1> struct Unroll<K1, K1, 1> {
  static DEVI void kbulk(float (&)[16], const uint32_t*, uint32_t) {}
};

DEVI void wgmma_n192_nt(float (&d)[96], uint64_t a, uint64_t b, int acc) {
  asm volatile("{.reg .pred p; setp.ne.b32 p, %98, 0;\n"
               "wgmma.mma_async.sync.aligned.m64n192k16.f32.bf16.bf16 {%0,%1,%2,%3,%4,%5,%6,%7,%8,%9,%10,%11,%12,%13,%14,%15,%16,%17,%18,%19,%20,%21,%22,%23,%24,%25,%26,%27,%28,%29,%30,%31,%32,%33,%34,%35,%36,%37,%38,%39,%40,%41,%42,%43,%44,%45,%46,%47,%48,%49,%50,%51,%52,%53,%54,%55,%56,%57,%58,%59,%60,%61,%62,%63,%64,%65,%66,%67,%68,%69,%70,%71,%72,%73,%74,%75,%76,%77,%78,%79,%80,%81,%82,%83,%84,%85,%86,%87,%88,%89,%90,%91,%92,%93,%94,%95}, %96, %97, p, 1, 1, 0, 1;}"
               : ACC4(d, 0), ACC4(d, 4), ACC4(d, 8), ACC4(d, 12), ACC4(d, 16), ACC4(d, 20), ACC4(d, 24), ACC4(d, 28), ACC4(d, 32), ACC4(d, 36), ACC4(d, 40), ACC4(d, 44), ACC4(d, 48), ACC4(d, 52), ACC4(d, 56), ACC4(d, 60), ACC4(d, 64), ACC4(d, 68), ACC4(d, 72), ACC4(d, 76), ACC4(d, 80), ACC4(d, 84), ACC4(d, 88), ACC4(d, 92) : "l"(a), "l"(b), "r"(acc));
}
DEVI void wgmma_n160_nt(float (&d)[80], uint64_t a, uint64_t b, int acc) {
  asm volatile("{.reg .pred p; setp.ne.b32 p, %82, 0;\n"
               "wgmma.mma_async.sync.aligned.m64n160k16.f32.bf16.bf16 {%0,%1,%2,%3,%4,%5,%6,%7,%8,%9,%10,%11,%12,%13,%14,%15,%16,%17,%18,%19,%20,%21,%22,%23,%24,%25,%26,%27,%28,%29,%30,%31,%32,%33,%34,%35,%36,%37,%38,%39,%40,%41,%42,%43,%44,%45,%46,%47,%48,%49,%50,%51,%52,%53,%54,%55,%56,%57,%58,%59,%60,%61,%62,%63,%64,%65,%66,%67,%68,%69,%70,%71,%72,%73,%74,%75,%76,%77,%78,%79}, %80, %81, p, 1, 1, 0, 1;}"
               : ACC4(d, 0), ACC4(d, 4), ACC4(d, 8), ACC4(d, 12), ACC4(d, 16), ACC4(d, 20), ACC4(d, 24), ACC4(d, 28), ACC4(d, 32), ACC4(d, 36), ACC4(d, 40), ACC4(d, 44), ACC4(d, 48), ACC4(d, 52), ACC4(d, 56), ACC4(d, 60), ACC4(d, 64), ACC4(d, 68), ACC4(d, 72), ACC4(d, 76) : "l"(a), "l"(b), "r"(acc));
}
DEVI void wgmma_n240_nn(float (&d)[120], uint64_t a, uint64_t b, int acc) {
  asm volatile("{.reg .pred p; setp.ne.b32 p, %122, 0;\n"
               "wgmma.mma_async.sync.aligned.m64n240k16.f32.bf16.bf16 {%0,%1,%2,%3,%4,%5,%6,%7,%8,%9,%10,%11,%12,%13,%14,%15,%16,%17,%18,%19,%20,%21,%22,%23,%24,%25,%26,%27,%28,%29,%30,%31,%32,%33,%34,%35,%36,%37,%38,%39,%40,%41,%42,%43,%44,%45,%46,%47,%48,%49,%50,%51,%52,%53,%54,%55,%56,%57,%58,%59,%60,%61,%62,%63,%64,%65,%66,%67,%68,%69,%70,%71,%72,%73,%74,%75,%76,%77,%78,%79,%80,%81,%82,%83,%84,%85,%86,%87,%88,%89,%90,%91,%92,%93,%94,%95,%96,%97,%98,%99,%100,%101,%102,%103,%104,%105,%106,%107,%108,%109,%110,%111,%112,%113,%114,%115,%116,%117,%118,%119}, %120, %121, p, 1, 1, 0, 0;}"
               : ACC4(d, 0), ACC4(d, 4), ACC4(d, 8), ACC4(d, 12), ACC4(d, 16), ACC4(d, 20), ACC4(d, 24), ACC4(d, 28), ACC4(d, 32), ACC4(d, 36), ACC4(d, 40), ACC4(d, 44), ACC4(d, 48), ACC4(d, 52), ACC4(d, 56), ACC4(d, 60), ACC4(d, 64), ACC4(d, 68), ACC4(d, 72), ACC4(d, 76), ACC4(d, 80), ACC4(d, 84), ACC4(d, 88), ACC4(d, 92), ACC4(d, 96), ACC4(d, 100), ACC4(d, 104), ACC4(d, 108), ACC4(d, 112), ACC4(d, 116) : "l"(a), "l"(b), "r"(acc));
}
DEVI void wgmma_n80_nt(float (&d)[40], uint64_t a, uint64_t b, int acc) {
  asm volatile("{.reg .pred p; setp.ne.b32 p, %42, 0;\n"
               "wgmma.mma_async.sync.aligned.m64n80k16.f32.bf16.bf16 {%0,%1,%2,%3,%4,%5,%6,%7,%8,%9,%10,%11,%12,%13,%14,%15,%16,%17,%18,%19,%20,%21,%22,%23,%24,%25,%26,%27,%28,%29,%30,%31,%32,%33,%34,%35,%36,%37,%38,%39}, %40, %41, p, 1, 1, 0, 1;}"
               : ACC4(d, 0), ACC4(d, 4), ACC4(d, 8), ACC4(d, 12), ACC4(d, 16), ACC4(d, 20), ACC4(d, 24), ACC4(d, 28), ACC4(d, 32), ACC4(d, 36) : "l"(a), "l"(b), "r"(acc));
}

#define ACQ 0
DEVI uint32_t ld_acquire(const uint32_t* p) {
  uint32_t v;
  if (ACQ) asm volatile("ld.acquire.gpu.global.u32 %0, [%1];" : "=r"(v) : "l"(p) : "memory");
  else asm volatile("ld.relaxed.gpu.global.u32 %0, [%1];" : "=r"(v) : "l"(p) : "memory");
  return v;
}
DEVI uint4 ldcg_if(const void* p, bool on) {
  uint4 v;
  asm volatile("{.reg .pred p; setp.ne.u32 p, %5, 0; mov.u32 %0, 0; mov.u32 %1, 0; mov.u32 %2, 0; mov.u32 %3, 0;\n"
               "@p ld.global.cg.v4.u32 {%0,%1,%2,%3}, [%4];}" : "=&r"(v.x), "=&r"(v.y), "=&r"(v.z), "=&r"(v.w) : "l"(p), "r"((uint32_t)on) : "memory");
  return v;
}
DEVI void red_release(uint32_t* p) { asm volatile("red.release.gpu.global.add.u32 [%0], 1;" :: "l"(p) : "memory"); }
#define TIGHT 1
DEVI void wait_count_t(const uint32_t* p, uint32_t n, bool tight) {
  for (int i = 0; i < 4000000 && ld_acquire(p) < n; i++) if (!(TIGHT && tight)) __nanosleep(100);
}
DEVI void wait_count(const uint32_t* p, uint32_t n) {
  for (int i = 0; i < 4000000 && ld_acquire(p) < n; i++) __nanosleep(100);
}
DEVI void spin_count(const uint32_t* p, uint32_t n) { for (int i = 0; i < 4000000 && ld_acquire(p) < n; i++) {} }
DEVI void mbar_wait_long(uint32_t bar, uint32_t par) { for (int n = 0; n < 4000000 && !mbar_try(bar, par); n++) {} }
DEVI void ln_row(float (&v)[20], bf16* y, int lane) {
  float s = 0.f;
#pragma unroll
  for (int i = 0; i < 20; i++) s += v[i];
#pragma unroll
  for (int o = 16; o; o >>= 1) s += __shfl_xor_sync(0xffffffffu, s, o);
  const float m = s * (1.0f / DM); float q = 0.f;
#pragma unroll
  for (int i = 0; i < 20; i++) { v[i] -= m; q += v[i] * v[i]; }
#pragma unroll
  for (int o = 16; o; o >>= 1) q += __shfl_xor_sync(0xffffffffu, q, o);
  const float r = rsqrtf(q * (1.0f / DM) + 1e-5f);
#pragma unroll
  for (int i = 0; i < 5; i++) *(uint2*)(y + i * 128 + lane * 4) = make_uint2(pack_bf16(v[4 * i] * r, v[4 * i + 1] * r), pack_bf16(v[4 * i + 2] * r, v[4 * i + 3] * r));
}

DEVI uint32_t mag4(uint32_t m, const uint32_t* f) {
  return __vmaxu2(__vmaxu2(m, __vmaxu2(f[0] & 0x7FFF7FFFu, f[1] & 0x7FFF7FFFu)), __vmaxu2(f[2] & 0x7FFF7FFFu, f[3] & 0x7FFF7FFFu));
}
DEVI void publish_max(uint32_t a, uint32_t m) {
  m = __reduce_max_sync(0xffffffffu, max(m & 0xFFFFu, m >> 16));
  if ((threadIdx.x & 31) == 0) asm volatile("red.shared.max.u32 [%0], %1;" :: "r"(a), "r"(m) : "memory");
}

namespace ch {
constexpr uint32_t WQ = 0;
constexpr uint32_t WOF2 = 81920;
constexpr uint32_t WOF = 106496;
constexpr uint32_t XB = 143360;
constexpr uint32_t MEMB = 184320;
constexpr uint32_t KT = 194560;
constexpr uint32_t VT = 199680;
constexpr uint32_t PK = 204800;
constexpr uint32_t QS = 212992;
constexpr uint32_t KP = 215040;
constexpr uint32_t EX = 217088;
constexpr uint32_t OB = 221184;
constexpr uint32_t SX = 224256;
constexpr uint32_t WOF3 = 226176;
constexpr uint32_t WOSTAGE = 143360;
constexpr uint32_t PB = OB;
constexpr uint32_t WMX = OB + 128;
constexpr uint32_t MISC = 228224;
constexpr uint32_t BAR_XF = MISC + 56;
constexpr uint32_t BAR_WK = MISC + 48, BAR_W1 = MISC, BAR_W2 = MISC + 8, BAR_X0 = MISC + 16, BAR_X1 = MISC + 24, BAR_S = MISC + 32, BAR_O = MISC + 40;
constexpr uint32_t MX = MISC + 64;
constexpr uint32_t INV = MX + 32;
#define PD_ 550
#define XD_ 150
#define X1D_ 0
#define PFW 0
constexpr uint32_t SMEM = 228352;
}

#define TS(e)
#define TSV(e, v)
#define TSX(x)
#define TSD(e, x)

#define SS(e)
#define E1(id, x)
#define PIN(x) asm volatile("" : "+r"(x))
#define PINF(x) asm volatile("" : "+f"(x))
#define PINL(x) asm volatile("" : "+l"(x))

DEVI uint32_t ar_line_off(uint32_t l) { return (l >> 2) * 1024 + (l & 3) * 128; }
DEVI uint32_t ar_tile_off(int T) { return (T >> 1) * 1024 + (T & 1) * 256; }
DEVI uint32_t ar_extra_off(uint32_t T) { return ar_line_off(80 + (T >> 2)) + (T & 3) * 32; }

DEVI void wo_red(const char* p, uint32_t w0, uint32_t w1, bool last) {
  red_f16x2((void*)p, last ? 0x3C00u : w0);
  red_f16x2((void*)(p + 128), last ? 0x3C00u : w1);
}
DEVI void wo_red_extra_p(const char* px, uint32_t w0, uint32_t w1, uint32_t ln) {
  asm volatile("{.reg .pred p; setp.eq.u32 p, %5, 31; @p red.relaxed.gpu.global.add.noftz.v4.f16x2 [%0], {%1,%2,%3,%4};}"
               :: "l"(px), "r"(w0), "r"(w1), "r"(0u), "r"(0x3C00u), "r"(ln) : "memory");
}

#define ARH 2
DEVI void sched_fence(uint32_t zero) {
#pragma unroll 1
  for (uint32_t i = 0; i < zero; i++) asm volatile("nanosleep.u32 0;" ::: "memory");
}
template <int N> DEVI void code_pad(uint32_t zero) {
  if (N > 0) {
#pragma unroll 1
    for (uint32_t i = 0; i < zero; i++) {
#pragma unroll
      for (int k = 0; k < N; k++) asm volatile("nanosleep.u32 0;" ::: "memory");
    }
  }
}
#define PAD1 0
#define PAD0 0
DEVI void loaded(uint32_t x) { asm volatile("{.reg .pred p; setp.eq.u32 p, %0, 0xdeadbeef; @p nanosleep.u32 0;}" :: "r"(x) : "memory"); }
DEVI uint32_t opq(uint32_t x) { asm volatile("" : "+r"(x)); return x; }

DEVI uint32_t ar_read(const char* arb, uint32_t sb, int w, uint32_t lane_, uint32_t zero, uint32_t tref, int dly, int s) {
  const int wg = 2; (void)wg; (void)s;
  const uint32_t lane = opq(lane_);
  const int b0 = (w >> 1) * 10 + (w & 1);
  const uint32_t e = min(lane, 9u), T = 2 * b0 + 4 * (e >> 1) + (e & 1);
  const char* p0 = arb + b0 * 1024 + lane * 16;
  const char* p2 = arb + ar_extra_off(T);
  uint32_t dst = sb + ch::MEMB + b0 * 512 + lane * 16, dst2 = sb + ch::MEMB + (16 * T + 7) * 16 + 12;
  uint32_t v[6][4];
  PINL(p0); PINL(p2); PIN(dst); PIN(dst2);
  while ((int)(clk32() - tref) < dly) {}
#pragma unroll
  for (int i = 0; i < 5; i++) ld_relaxed128(v[i], p0 + i * 2048);
  ld_relaxed128(v[5], p2);
  sched_fence(zero);
  TS(4);
  uint32_t bad = 0;
#pragma unroll
  for (int i = 0; i < 5; i++) bad |= v[i][3] ^ 0x5000u;
  if ((lane & 7) != 7) bad = 0;
  bad |= v[5][3] ^ 0x5000u;
  TSD(5, bad);
  E1(6, bad);
  int n = 0;
  if (__any_sync(0xffffffffu, bad != 0)) {
    if (lane == 0) sts32(sb + ch::MX + 20, 1u);
    while (true) {
      bad = 0;
#pragma unroll
      for (int i = 0; i < 6; i++) if ((i == 5 || (lane & 7) == 7) && v[i][3] != 0x5000u) bad |= 1u << i;
      bad = __reduce_or_sync(0xffffffffu, bad);
      if (!bad || ++n > SPIN_LIMIT) break;
#pragma unroll
      for (int i = 0; i < 6; i++) if (bad >> i & 1) ld_relaxed128(v[i], i < 5 ? p0 + i * 2048 : p2);
    }
  }
  TSV(6, n);
  const uint32_t x0 = f16x2_to_bf16x2(v[5][0]), x1 = f16x2_to_bf16x2(v[5][1]);
#pragma unroll
  for (int i = 0; i < 5; i++) {
    sts128(dst + i * 1024, f16x2_to_bf16x2(v[i][0]), f16x2_to_bf16x2(v[i][1]), f16x2_to_bf16x2(v[i][2]), f16x2_to_bf16x2(v[i][3]));
    if (i == ARH - 1 || i == 4) {
      __syncwarp();
      sts32(dst2, x0); sts32(dst2 + 128, x1);
      if (i < 4) { TS(7); bar_arrive(1, 384); sched_fence(zero); } else { TSX(TS(1)); bar_sync(3, 384); }
    }
  }
  const uint32_t keep = (lane & 7) == 7 ? 0u : 0x7FFF7FFFu;
  uint32_t m = __vmaxu2(v[5][0] & 0x7FFF7FFFu, v[5][1] & 0x7FFF7FFFu);
#pragma unroll
  for (int i = 0; i < 5; i++) m = __vmaxu2(__vmaxu2(m, __vmaxu2(v[i][0] & 0x7FFF7FFFu, v[i][1] & 0x7FFF7FFFu)), __vmaxu2(v[i][2] & 0x7FFF7FFFu, v[i][3] & keep));
  return m;
}

#define VL 0
struct Peers {
  uint32_t a[2];
  DEVI Peers(uint32_t sb, int j) {
#pragma unroll
    for (int r = 0; r < 2; r++) { int peer = j + 1 + r; if (peer >= 3) peer -= 3; a[r] = mapa(sb, peer); }
  }
};
DEVI uint32_t lane_id() { const uint32_t l = threadIdx.x & 31; return __shfl_sync(0xffffffffu, l, l); }
DEVI void score_tile(uint32_t sb, uint32_t qa, const uint32_t (&b0)[4], const uint32_t (&b1)[4], const Peers& pe, uint32_t off, uint32_t lane) {
  float c0[4] = {0.f, 0.f, 0.f, 0.f}, c1[4] = {0.f, 0.f, 0.f, 0.f};
  uint32_t a0[4], a1[4], a2[4], a3[4];
  ldsm4t(a0, qa); ldsm4t(a1, qa + 256); ldsm4t(a2, qa + 512); ldsm4t(a3, qa + 768);
  mma16816(c0, a0, b0[0], b0[1]); mma16816(c1, a1, b0[2], b0[3]);
  mma16816(c0, a2, b1[0], b1[1]); mma16816(c1, a3, b1[2], b1[3]);
  if (!VL) asm volatile("bar.arrive 5, 288;" : "+f"(c0[0]), "+f"(c1[0]) :: "memory");
  const float cs = 0.25f * 0.07216878364870322f * 1.4426950408889634f;
  const float x = ((c0[0] + c0[2]) + (c1[0] + c1[2])) * cs, y = ((c0[1] + c0[3]) + (c1[1] + c1[3])) * cs;
  uint32_t u; asm("cvt.rn.satfinite.f16x2.f32 %0, %1, %2;" : "=r"(u) : "f"(y), "f"(x));
  st_async32(pe.a[0] + off, u, pe.a[0] + ch::BAR_S);
  st_async32(pe.a[1] + off, u, pe.a[1] + ch::BAR_S);
  sts32(sb + off, u);
  __syncwarp();
  if (lane == 0) mbar_arrive(sb + ch::BAR_S);
}
DEVI uint32_t hadd2(uint32_t a, uint32_t b) { uint32_t r; asm("add.rn.f16x2 %0, %1, %2;" : "=r"(r) : "r"(a), "r"(b)); return r; }
DEVI uint32_t hmax2(uint32_t a, uint32_t b) { uint32_t r; asm("max.f16x2 %0, %1, %2;" : "=r"(r) : "r"(a), "r"(b)); return r; }
DEVI uint32_t add_bf16x2(uint32_t a, uint32_t b) { uint32_t r; asm("add.rn.bf16x2 %0, %1, %2;" : "=r"(r) : "r"(a), "r"(b)); return r; }

DEVI uint32_t slab_off(uint32_t base, int w, uint32_t lane) { return base + (16 * w + (lane >> 2)) * 80 + (lane & 3) * 4; }
DEVI void release_x(uint32_t sb, int half, int w, uint32_t lane) {
  if (lane == 0) {
    if (w == 0) mbar_expect(sb + ch::BAR_X0 + half * 8, 20480);
    mbar_arrive_cluster(mapa(sb + ch::BAR_XF, half));
  }
}
#define TSYNC 1
#define KORD 0
#define X0E 0
#define X0D_ 0
#define X1E 1
#define KS2 0
#define SKIPT 0
DEVI void store_slabs(uint32_t sb, int s, int h, int j) {
  bf16* kvp = g_kv + ((size_t)(s * NH + h) * 2 * DH + 64 * j) * NKEY;
  fence_async();
  bulk_store(kvp, sb + ch::KT, SLAB);
  bulk_store(kvp + DH * NKEY, sb + ch::VT, SLAB);
  asm volatile("cp.async.bulk.commit_group;" ::: "memory");
}

template <int MODE>
DEVI void tokens_partial(uint32_t sb, uint32_t dst, const uint32_t* W, uint32_t xdesc, int w, uint32_t lane) {
  float d[16];
#pragma unroll
  for (int i = 0; i < 16; i++) d[i] = 0.f;
  wg_fence();
  if (!((SKIPT >> (MODE == 3 ? 1 : MODE)) & 1)) Unroll<20, 40, 0>::kbulk(d, W - 80, xdesc);
  wg_commit();
  if (MODE == 1) bar_sync(12, 384);
  if (!KS2 && MODE == 2) bar_sync(11, 256);
  wg_wait<0>();
  if (!KS2 && (MODE == 1 || MODE == 3)) release_x(sb, 1, w, lane);
  if (MODE == 1) bar_sync(13, 384);
  if (KS2 && MODE == 2) release_x(sb, 1, w, lane);
  dst += sb + w * 512 + opq(lane) * 16;
#pragma unroll
  for (int i = 0; i < 4; i++)
    sts128(dst + i * 2048, __float_as_uint(d[4 * i]), __float_as_uint(d[4 * i + 1]), __float_as_uint(d[4 * i + 2]), __float_as_uint(d[4 * i + 3]));
  if (KS2 && MODE == 2) bar_arrive(11, 256);
}
#define LSH 0
#define KPK 16
template <bool LOOP>
DEVI void tokens_finish(uint32_t sb, const uint32_t* W, uint32_t xdesc, int w, uint32_t lane, int s = 0, const CUtensorMap* mx = nullptr) {
  const uint32_t ln = opq(lane), t16 = sb + w * 512 + ln * 16, slab = sb + slab_off(16, w, ln);
  float d[16]; uint32_t e[4][4];
#pragma unroll
  for (int i = 0; i < 16; i++) d[i] = 0.f;
  wg_fence();
  if (!(LOOP && (SKIPT & 8))) Unroll<0, 20, 0>::kbulk(d, W + 80, xdesc);
  wg_commit();
  if (!KS2 && !KORD && LOOP) bar_arrive(6, 256);
  if (LOOP && LSH == 2 && s < 0) bar_sync(8, 256);
  if (!LOOP) {
    bar_sync(8, 256);
    if (w == 3 && lane == 0) { mbar_expect(sb + ch::BAR_X1, 20480); tma3d(sb + ch::XB + 20480, mx, 0, SEG, 5, sb + ch::BAR_X1); }
    __syncwarp();
  }
#pragma unroll
  for (int i = 0; i < 4; i++) lds128(e[i], t16 + ch::QS + i * 2048);
  wg_wait<0>();
  uint32_t u[8];
#pragma unroll
  for (int i = 0; i < 4; i++) {
    u[2 * i] = pack_bf16(d[4 * i] + __uint_as_float(e[i][0]), d[4 * i + 1] + __uint_as_float(e[i][1]));
    u[2 * i + 1] = pack_bf16(d[4 * i + 2] + __uint_as_float(e[i][2]), d[4 * i + 3] + __uint_as_float(e[i][3]));
  }
  wg_fence();
  if (!(LOOP && (SKIPT & 16))) Unroll<0, 6, 0>::kbulk(d, W, xdesc);
#pragma unroll
  for (int i = 0; i < 4; i++) { sts32(slab + ch::VT + i * 16, u[2 * i]); sts32(slab + ch::VT + i * 16 + 640, u[2 * i + 1]); }
  if (KS2) {
    if (!(LOOP && (SKIPT & 16))) Unroll<6, KPK>::kbulk(d, W, xdesc);
    if (LOOP) bar_sync(11, 256);
  }
#pragma unroll
  for (int i = 0; i < 4; i++) lds128(e[i], t16 + ch::PK + i * 2048);
  if (!KS2) {
    if (!(LOOP && (SKIPT & 16))) Unroll<6, KPK>::kbulk(d, W, xdesc);
    if (LOOP) asm volatile("bar.arrive 11, 256;" : "+r"(e[0][0]), "+r"(e[1][0]), "+r"(e[2][0]), "+r"(e[3][0]) :: "memory");
  }
  if (!(LOOP && (SKIPT & 16))) Unroll<KPK, 20>::kbulk(d, W, xdesc);
  wg_commit(); wg_wait<0>();
  release_x(sb, 0, w, lane);
  if (LOOP) E1(7, __float_as_uint(d[0]));
#pragma unroll
  for (int i = 0; i < 4; i++) {
    sts32(slab + ch::KT + i * 16, pack_bf16(d[4 * i] + __uint_as_float(e[i][0]), d[4 * i + 1] + __uint_as_float(e[i][1])));
    sts32(slab + ch::KT + i * 16 + 640, pack_bf16(d[4 * i + 2] + __uint_as_float(e[i][2]), d[4 * i + 3] + __uint_as_float(e[i][3])));
  }
}

DEVI uint32_t afrag_off(int w, uint32_t lane) { return ((lane >> 4) * 8 + (lane & 7)) * 128 + (((w * 2 + ((lane >> 3) & 1)) ^ (lane & 7)) << 4); }
#define NF 5
#define WQR 0
DEVI void ldwq(uint32_t (&f)[4], uint32_t a) { if (WQR) lds128(f, a); else ldsm4t(f, a); }
DEVI void proj_stage(uint32_t (&f)[NF][4], uint32_t qa) {
#pragma unroll
  for (int i = 0; i < NF; i++) ldwq(f[i], qa + i * 2048);
}
template <int WG>
DEVI void proj_mem(float (&q)[4], float (&k)[4], float (&v)[4], uint32_t (&f)[NF][4], const uint32_t* W, uint32_t qa, uint32_t ba, uint32_t sb, int w, int s) {
  uint32_t b[2][4];
  const int wg = WG; (void)wg; (void)sb; (void)w; (void)s;
#pragma unroll
  for (int i = 0; i < 4; i++) q[i] = k[i] = v[i] = 0.f;
  bar_sync(1, 384);
  ldsm4t(b[0], ba);
  if (WG == 0) E1(8, b[0][0]);
  if (WG == 1) { TSX(TSD(5, b[0][0])); }
#pragma unroll
  for (int k2 = 0; k2 < 10; k2++) {
    if (WG == 1 && k2 + 1 == 2 * ARH) { TSX(TSD(7, __float_as_uint(v[0]))); }
    if (k2 + 1 == 2 * ARH) bar_sync(3, 384);
    if (k2 < 9) ldsm4t(b[(k2 + 1) & 1], ba + (k2 + 1) * 512);
    if (WG == 1 && k2 + 1 == 2 * ARH) { TSX(TSD(6, b[(k2 + 1) & 1][0])); }
    if (WG == 0 && k2 + 1 == 2 * ARH) { TSX(TSD(7, __float_as_uint(v[0]))); }
    mma16816(q, f[(2 * k2) % NF], b[k2 & 1][0], b[k2 & 1][1]);
    if (2 * k2 + NF < 20) ldwq(f[(2 * k2) % NF], qa + (2 * k2 + NF) * 2048);
    mma16816(k, &W[k2 * 8], b[k2 & 1][0], b[k2 & 1][1]);
    mma16816(v, &W[80 + k2 * 8], b[k2 & 1][0], b[k2 & 1][1]);
    mma16816(q, f[(2 * k2 + 1) % NF], b[k2 & 1][2], b[k2 & 1][3]);
    if (2 * k2 + 1 + NF < 20) ldwq(f[(2 * k2 + 1) % NF], qa + (2 * k2 + 1 + NF) * 2048);
    mma16816(k, &W[k2 * 8 + 4], b[k2 & 1][2], b[k2 & 1][3]);
    mma16816(v, &W[84 + k2 * 8], b[k2 & 1][2], b[k2 & 1][3]);
  }
}

template <bool BAR>
DEVI void wo_tile_smem(uint32_t sb, uint32_t fa, uint32_t ob, int par, const char* p, const char* px, bool last, float& sc) {
  uint32_t f[6][4], b[2][4];
  float c0[4] = {0.f, 0.f, 0.f, 0.f}, c1[4] = {0.f, 0.f, 0.f, 0.f};
#pragma unroll
  for (int k = 0; k < 6; k++) lds128(f[k], fa + k * 512);
  if (BAR) bar_sync(9, 384);
  ldsm4t(b[0], ob); ldsm4t(b[1], ob + 512);
  sc = __uint_as_float(lds32(sb + ch::MX + 16));
  float2 iv = lds64f(sb + ch::INV + (opq(threadIdx.x) & 3) * 8);
  iv.x *= sc; iv.y *= sc;
  mma16816(c0, f[0], b[0][0], b[0][1]); mma16816(c1, f[1], b[0][2], b[0][3]);
  mma16816(c0, f[2], b[1][0], b[1][1]); mma16816(c1, f[3], b[1][2], b[1][3]);
#pragma unroll
  for (int k = 0; k < 4; k++) lds128(f[k], fa + (6 + k) * 512);
  mbar_wait(sb + ch::BAR_O, par);
  ldsm4t(b[0], ob + 1024); ldsm4t(b[1], ob + 1536);
  mma16816(c0, f[4], b[0][0], b[0][1]); mma16816(c1, f[5], b[0][2], b[0][3]);
  lds128(f[4], fa + 10 * 512); lds128(f[5], fa + 11 * 512);
  ldsm4t(b[0], ob + 2048);
  mma16816(c0, f[0], b[1][0], b[1][1]); mma16816(c1, f[1], b[1][2], b[1][3]);
  ldsm4t(b[1], ob + 2560);
  mma16816(c0, f[2], b[0][0], b[0][1]); mma16816(c1, f[3], b[0][2], b[0][3]);
  mma16816(c0, f[4], b[1][0], b[1][1]); mma16816(c1, f[5], b[1][2], b[1][3]);
  const uint32_t w0 = pack_f16((c0[0] + c1[0]) * iv.x, (c0[1] + c1[1]) * iv.y), w1 = pack_f16((c0[2] + c1[2]) * iv.x, (c0[3] + c1[3]) * iv.y);
  wo_red(p, w0, w1, last);
  wo_red_extra_p(px, w0, w1, last ? 31u : 0u);
}

#define LNFIRST 0
DEVI void chain_prepare(const bf16* __restrict__ x) {
  const int t = threadIdx.x, lane = t & 31, r0 = blockIdx.x * 11 + (t >> 5);
  asm volatile("griddepcontrol.wait;" ::: "memory");
  uint2 u[2][5];
#pragma unroll
  for (int i = 0; i < 10; i++) u[i / 5][i % 5] = __ldcg((const uint2*)(x + min(r0 + (i / 5) * 1056, S_LEN - 1) * DM + (i % 5) * 128 + lane * 4));
#pragma unroll
  for (int rr = 0; rr < 2; rr++) {
    float v[20];
#pragma unroll
    for (int i = 0; i < 5; i++) {
      v[4 * i] = __uint_as_float(u[rr][i].x << 16); v[4 * i + 1] = __uint_as_float(u[rr][i].x & 0xFFFF0000u);
      v[4 * i + 2] = __uint_as_float(u[rr][i].y << 16); v[4 * i + 3] = __uint_as_float(u[rr][i].y & 0xFFFF0000u);
    }
    if (r0 + rr * 1056 < S_LEN) ln_row(v, g_xn + (r0 + rr * 1056) * DM, lane);
  }
}
#define LNF 0
#define PWIN 3
#define PWIN1 4
#define LASTG 1
#define PSPL 1
DEVI void load_weights(uint32_t (&W)[160], uint32_t sb, int G, int w, int j, int layer) {
  using namespace ch;
  const uint32_t lane = threadIdx.x & 31;
  const uint32_t wa = sb + G * 40960 + afrag_off(w, lane);
#pragma unroll 1
  for (int i = 0; i < 5; i++) mbar_wait_long(sb + PB + i * 8, 0);
  if (threadIdx.x == 0) PT(0, 10);
#pragma unroll
  for (int kk = 0; kk < 20; kk++) ldsm4t_p(&W[80 + kk * 4], wa + 81920 + kk * 2048);
  uint32_t m = 0;
#pragma unroll
  for (int kk = 0; kk < 20; kk++) m = mag4(m, &W[80 + kk * 4]);
  publish_max(sb + WMX, m);
  bar_sync(8, 256);
  if (threadIdx.x == 0) mbar_arrive(sb + BAR_W1);
#pragma unroll 1
  for (int i = 7; i < 12; i++) mbar_wait_long(sb + PB + i * 8, 0);
  if (threadIdx.x == 0) PT(0, 9);
#pragma unroll
  for (int kk = 0; kk < 20; kk++) ldsm4t_p(&W[kk * 4], wa + kk * 2048);
  loaded(W[79]);
  bar_sync(8, 256);
  if (threadIdx.x == 0) mbar_arrive(sb + BAR_WK);
  m = 0;
  mbar_wait_long(sb + PB + (G == 0 ? 13 : 6) * 8, 0);
  if (threadIdx.x == 0) PT(0, 11);
  const uint32_t src = (G == 0 ? sb + WOF : sb + WOSTAGE + 2 * 24576) + afrag_off(w, lane);
  if (G == 1) {
    for (int kk = 0; kk < 12; kk++) { uint32_t f[4]; ldsm4t(f, src + kk * 2048); m = mag4(m, f); }
    publish_max(sb + WMX + 4, m);
    bar_sync(7, 384);
  }
  if (G == 1 || w < 2) {
    for (int kk = 0; kk < 12; kk++) {
      uint32_t f[4];
      ldsm4t(f, src + ((kk + 4 * j) % 12) * 2048);
      sts128(sb + WOF + ((G == 0 ? 4 + w : w) * 12 + kk) * 512 + lane * 16, f[0], f[1], f[2], f[3]);
      if (G == 0) m = mag4(m, f);
    }
  }
  if (G == 0) { publish_max(sb + WMX + 4, m); bar_sync(7, 384); }
  bar_sync(7, 384);
}
DEVI void arrange_wq(uint32_t sb, int G, int w, int layer) {
  using namespace ch;
  const uint32_t lane = threadIdx.x & 31;
  mbar_wait_long(sb + BAR_W2, 0);
  if (threadIdx.x == 0) PT(0, 15);
  if (WQR) {
    const uint32_t src = sb + WQ + G * 40960 + afrag_off(w, lane), dst = sb + WQ + G * 40960 + w * 512 + lane * 16;
#pragma unroll 1
    for (int r = 0; r < 5; r++) {
      uint32_t f[4][4];
#pragma unroll
      for (int i = 0; i < 4; i++) ldsm4t(f[i], src + (r * 4 + i) * 2048);
      bar_sync(14 + G, 128);
#pragma unroll
      for (int i = 0; i < 4; i++) sts128(dst + (r * 4 + i) * 2048, f[i][0], f[i][1], f[i][2], f[i][3]);
    }
    __syncwarp();
  }
}

namespace tl {
constexpr uint32_t FULL = 225280, EMPTY = FULL + 56;
#define TSL0 10
constexpr int RT0 = 13, SL0 = TSL0;
}
DEVI uint32_t fresh_tid() { uint32_t t; asm volatile("mov.u32 %0, %%tid.x;" : "=r"(t)); return t; }
DEVI int fresh_cta() { uint32_t t; asm volatile("mov.u32 %0, %%ctaid.x;" : "=r"(t)); const uint32_t h = t * 86 >> 8; return (t - h * 3) * 32 + h; }
DEVI void ldcg128(uint32_t (&r)[4], const void* p) { asm volatile("ld.global.cg.v4.u32 {%0,%1,%2,%3}, [%4];" : "=r"(r[0]), "=r"(r[1]), "=r"(r[2]), "=r"(r[3]) : "l"(p) : "memory"); }
#define TNST 3
#define TCV 0
#define TPOS 2
DEVI void tail_load(uint32_t sb, Sync* sy, const CUtensorMap* moa, const CUtensorMap* mwo, int layer) {
  using namespace tl;
  (void)layer;
  const int i = fresh_cta(), a = i & 3, b = (i & 31) >> 2, rt = RT0 + (i >> 5);
  const bool last = rt == 15;
  const int nst = last ? 7 : TNST, npre = last ? 7 : 0;
  const uint32_t ab = last ? 8192 : 16384, stage = ab + 20480;
#pragma unroll 1
  for (int g = 0; g < npre; g++) { mbar_expect(sb + FULL + g * 8, stage); tma3d(sb + g * stage + ab, mwo, 0, (b * 12 + g) * 64, a * 5, sb + FULL + g * 8); }
  spin_count(&sy->o[rt * 16 + b], last ? 4 : 8);
  if (!last) XT(i, 0);
  fence_flag_to_bulk();
  int st = 0, par = 1;
#pragma unroll 1
  for (int g = 0; g < (last ? 24 : 12); g++) {
    const uint32_t dst = sb + st * stage, fb = sb + FULL + st * 8;
    const int k = (b * 12 + (g < 12 ? g : g < 19 ? g - 7 : g - 19)) * 64;
    if (g == 12) { spin_count(&sy->o[15 * 16 + 8 + b], 4); XT(i, 0); fence_flag_to_bulk(); }
    if (g >= npre) {
      mbar_wait_long(sb + EMPTY + st * 8, par);
      mbar_expect(fb, g >= 12 && g < 19 ? ab : stage);
      if (g < 12 || g >= 19) tma3d(dst + ab, mwo, 0, k, a * 5, fb);
    }
    tma2d(dst, moa, k, rt * 128 + (g >= 12) * 64, fb);
    if (!last) tma2d(dst + 8192, moa, k, rt * 128 + 64, fb);
    if (++st == nst) { st = 0; par ^= 1; }
  }
}
DEVI void tail_sum(uint32_t sb, Sync* sy, const bf16* __restrict__ xin, int layer) {
  using namespace tl;
  const int ct = fresh_tid(), lane = ct & 31, cw = __shfl_sync(0xffffffffu, ct >> 7, 0), w = ct >> 5 & 3;
  const int i = TCV ? __shfl_sync(0xffffffffu, fresh_cta(), 0) : blockIdx.x % 3 * 32 + blockIdx.x / 3, a = i & 3, b = (i & 31) >> 2, rt = RT0 + (i >> 5);
  const bool last = rt == 15;
  const uint32_t nst = last ? 7 : TNST, stage = last ? 28672 : 36864, ao = last ? 0 : cw * 8192, bo = stage - 20480, ost = sb + (last ? 200704 : 184320 + cw * 20480);
  float d[80];
#pragma unroll
  for (int n = 0; n < 80; n++) d[n] = 0.f;
  bar_sync(14, 288);
  if (last && cw) bar_sync(6, 256);
  uint32_t st = last && cw ? 5 : 0, par = last && cw, prev = 0;
#pragma unroll 1
  for (int c = 0; c < 12; c++) {
    mbar_wait_long(sb + FULL + st * 8, par);
    if (c == 0 && ct == 128) XT(i, 1);
    const uint64_t da = mkdesc(sb + st * stage + ao, 16, 1024, 1), db = mkdesc(sb + st * stage + bo, 4096, 512, 2);
    wg_fence();
#pragma unroll
    for (int k = 0; k < 4; k++) wgmma_n160_nt(d, da + k * 2, db + k * 64, c | k);
    wg_commit();
    if (c > 0) { wg_wait<1>(); if (lane == 0) mbar_arrive(prev); }
    prev = sb + EMPTY + st * 8;
    if (++st == nst) { st = 0; par ^= 1; }
  }
  if (last && !cw) bar_arrive(6, 256);
  const int rl = last ? cw * 64 + b * 8 + (ct >> 4 & 7) : b * 16 + (ct >> 4), q = ct & 15, r = rt * 128 + rl;
  const int c0 = r * DM + a * 160 + q * 8, c1 = c0 + 128 - (q & 12) * 8;
  uint32_t u[9][2][4];
  ldcg128(u[8][0], xin + c0); ldcg128(u[8][1], xin + c1);
  if (last && cw) bar_sync(5, 256);
  wg_wait<0>();
  if (lane == 0) mbar_arrive(prev);
  const uint32_t orow = w * 16 + (lane & 15), ob = ost + orow * 64;
#pragma unroll
  for (int n = 0; n < 10; n++)
    stsm4(ob + (n >> 1) * 4096 + ((((n & 1) * 2 + (lane >> 4)) ^ ((orow >> 1) & 3)) << 4), pack_bf16(d[8 * n], d[8 * n + 1]), pack_bf16(d[8 * n + 2], d[8 * n + 3]),
          pack_bf16(d[8 * n + 4], d[8 * n + 5]), pack_bf16(d[8 * n + 6], d[8 * n + 7]));
  fence_async();
  bar_sync(7 + cw, 128);
  const int sl0 = SL0 * 8 + (rt - RT0) * 64 + a * 16;
  if ((ct & 127) == 0) {
    bulk_store(g_sl + (size_t)(sl0 + cw * 8 + b) * 10240, ost, 20480);
    asm volatile("cp.async.bulk.commit_group; cp.async.bulk.wait_group 0;" ::: "memory");
    XT(i, 2 + cw);
    publish_bulk<WFEN>(&sy->wcnt[(rt * 4 + a) * 2 + cw]);
  }
  if ((ct & 127) == 32) spin_count(&sy->wcnt[(rt * 4 + a) * 2 + (rl >> 6)], 8);
  __syncwarp();
  bar_sync(7 + cw, 128);
  const bf16* sl = g_sl + (size_t)(sl0 + (rl >> 6) * 8) * 10240 + (rl & 63) * 32 + (((q & 3) ^ (rl >> 1 & 3)) << 3);
#pragma unroll
  for (int n = 0; n < 8; n++) { ldcg128(u[n][0], sl + n * 10240 + (q >> 2) * 2048); ldcg128(u[n][1], sl + n * 10240 + 8192); }
  if (last && !cw) bar_arrive(5, 256);
  if (ct == 128 && last) XT(128 + (i & 31), 0);
  sched_fence(layer >> 4);
  const uint32_t id = (lane >> 2) == (lane & 3) * 2 ? 0x3F80u : (lane >> 2) == (lane & 3) * 2 + 1 ? 0x3F800000u : 0u;
  float y[4][4], s1 = 0.f, s2 = 0.f;
#pragma unroll
  for (int e = 0; e < 16; e++) y[e >> 2][e & 3] = 0.f;
#pragma unroll
  for (int n = 0; n < 9; n++)
#pragma unroll
    for (int m = 0; m < 2; m++) { mma16816(y[2 * m], u[n][m], id, 0u); mma16816(y[2 * m + 1], u[n][m], 0u, id); }
#pragma unroll
  for (int m = 0; m < 2; m++) {
    const bool on = !m || q < 4;
    uint32_t z[4];
    float t1 = 0.f, t2 = 0.f;
#pragma unroll
    for (int e = 0; e < 4; e++) {
      z[e] = pack_bf16(y[2 * m + (e >> 1)][(e & 1) * 2], y[2 * m + (e >> 1)][(e & 1) * 2 + 1]);
      const float lo = __uint_as_float(z[e] << 16), hi = __uint_as_float(z[e] & 0xFFFF0000u);
      t1 += lo + hi; t2 = fmaf(lo, lo, fmaf(hi, hi, t2));
    }
    if (on) { s1 += t1; s2 += t2; }
    asm volatile("{.reg .pred p; setp.ne.u32 p, %5, 0; @p st.global.v4.u32 [%0], {%1,%2,%3,%4};}"
                 :: "l"(g_xa + (m ? c1 : c0)), "r"(z[0]), "r"(z[1]), "r"(z[2]), "r"(z[3]), "r"((uint32_t)on) : "memory");
  }
#pragma unroll
  for (int o = 1; o < 16; o <<= 1) { s1 += __shfl_xor_sync(0xffffffffu, s1, o); s2 += __shfl_xor_sync(0xffffffffu, s2, o); }
  asm volatile("{.reg .pred p; setp.ne.u32 p, %3, 0; @p red.relaxed.gpu.global.add.v2.f32 [%0], {%1,%2};}"
               :: "l"(&sy->rstat[r]), "f"(s1), "f"(s2), "r"((uint32_t)(q == 0)) : "memory");
  if (ct == 128 && last) XT(128 + (i & 31), 1);
  if (BFL) {
    bar_sync(7 + cw, 128);
    if ((ct & 127) == 0) red_release(&sy->pro[1 + rt - RT0]);
    if (ct == 128 && last) XT(128 + (i & 31), 2);
    __syncwarp();
  }
}

__global__ void __cluster_dims__(3, 1, 1) __launch_bounds__(384, 1)
chain_kernel(const __grid_constant__ CUtensorMap mq, const __grid_constant__ CUtensorMap mk, const __grid_constant__ CUtensorMap mv,
             const __grid_constant__ CUtensorMap mo, const __grid_constant__ CUtensorMap mx, const bf16* __restrict__ mem0, const bf16* __restrict__ xin, uint32_t zero, int layer
             , const __grid_constant__ CUtensorMap moa, const __grid_constant__ CUtensorMap mwo
             ) {
  using namespace ch;
  extern __shared__ __align__(1024) uint8_t smraw[];
  const uint32_t sb = smem_u32(smraw);
  const int tid = threadIdx.x;
  const int wg = __shfl_sync(0xffffffffu, tid >> 7, 0), w = __shfl_sync(0xffffffffu, (tid >> 5) & 3, 0);
  int h, j;
  asm("mov.u32 %0, %%clusterid.x;" : "=r"(h));
  asm("mov.u32 %0, %%cluster_ctarank;" : "=r"(j));
  h = __shfl_sync(0xffffffffu, h, 0); j = __shfl_sync(0xffffffffu, j, 0);
  const int T0 = j == 0 ? 0 : (j == 1 ? 14 : 27), NT = j == 0 ? 14 : 13;
  const uint32_t PD = PD_, XD = XD_, X1D = X1D_;
  constexpr uint32_t CS = 0, UP = 0, DMIN = 0, FL = 0, SD = 0;

  if (tid == 0) {
    mbar_init(sb + BAR_W1, 1); mbar_init(sb + BAR_W2, 1); mbar_init(sb + BAR_X0, 1); mbar_init(sb + BAR_X1, 1);
    mbar_init(sb + BAR_S, 6); mbar_init(sb + BAR_O, 1); mbar_init(sb + BAR_WK, 1); mbar_init(sb + BAR_XF, 12);
    for (int i = 0; i < 14; i++) mbar_init(sb + PB + i * 8, 1);
    sts64(sb + WMX, 0, 0);
    asm volatile("fence.mbarrier_init.release.cluster;" ::: "memory");
    mbar_expect(sb + BAR_W2, 81920);
    mbar_expect(sb + BAR_S, 1280); mbar_expect(sb + BAR_O, 2048);
  }
  asm volatile("griddepcontrol.launch_dependents;");
  GT(0, 0);
  __syncthreads();
  asm volatile("barrier.cluster.arrive.relaxed.aligned;" ::: "memory");
  asm volatile("barrier.cluster.wait.aligned;" ::: "memory");
  if (tid == 0) PT(0, 0);
  const char* arb = (const char*)g_ar;
  const uint32_t xdesc = desc_lo(sb + XB, 16);

  if (wg < 2) {
    asm volatile("setmaxnreg.inc.sync.aligned.u32 208;");
    if (!(BLN && layer) && !(WLN >> layer & 1)) chain_prepare(xin);
    if (WLN != 3) bar_arrive(9, 352);
    uint32_t W[160];
    load_weights(W, sb, wg, w, j, layer);
    float inv_sc = 1.0f;
    if (wg == 0) {
      const uint32_t lane = lane_id();
      code_pad<PAD0>(zero);
      mbar_wait_long(sb + BAR_X0, 0);
      if (tid == 0) PT(0, 12);
      if (LSH == 1) bar_sync(8, 256);
      if (!LSH) {
        tokens_finish<false>(sb, W, xdesc, w, lane, 0, &mx);
        if (tid == 0) PT(0, 13);
        if (!KS2) bar_arrive(8, 256);
        arrange_wq(sb, 0, w, layer);
      }
#pragma unroll 1
      for (int s = LSH ? -1 : 0; s < NSEG; s++) {
        float sc = 1.0f;
        if (!LSH || s >= 0) {
        uint32_t A0[2];
        {
          float q[4], k[4], v[4];
          const uint32_t ln = opq(lane), t16 = w * 512 + ln * 16;
          uint32_t f[NF][4], wq = sb + WQ + (WQR ? t16 : afrag_off(w, ln)), ba = sb + MEMB + ln * 16;
          proj_stage(f, wq);
          PIN(ba);
          proj_mem<0>(q, k, v, f, W, wq, ba, sb, w, s);
          const uint32_t qd = sb + QS + w * 256 + ln * 4;
          sts32(qd, pack_bf16(q[0] * inv_sc, q[1] * inv_sc)); sts32(qd + 128, pack_bf16(q[2] * inv_sc, q[3] * inv_sc));
          sts32(qd + 2048, pack_bf16(k[0] * inv_sc, k[1] * inv_sc)); sts32(qd + 2048 + 128, pack_bf16(k[2] * inv_sc, k[3] * inv_sc));
          sts128(sb + EX + t16, __float_as_uint(k[0]), __float_as_uint(k[1]), __float_as_uint(k[2]), __float_as_uint(k[3]));
          E1(1, __float_as_uint(v[0]) ^ __float_as_uint(q[0]));
          uint32_t qa = sb + QS + ((ln >> 3) & 1) * 1024 + ((ln >> 4) * 8 + (ln & 7)) * 16;
          PIN(qa);
          TS(0);
          bar_sync(2, 384);
          if (w == 3 && s < NSEG - 1) {
            uint32_t b0[4], b1[4], c0[4], c1[4];
            const uint32_t ka = sb + KP + ln * 16;
            ldsm4t(b0, ka); ldsm4t(c0, ka + 1024); ldsm4t(b1, ka + 512); ldsm4t(c1, ka + 1536);
#pragma unroll
            for (int i = 0; i < 4; i++) { b0[i] = add_bf16x2(b0[i], c0[i]); b1[i] = add_bf16x2(b1[i], c1[i]); }
            score_tile(sb, qa, b0, b1, Peers(sb, j), SX + j * 640 + ln * 4, ln);
          }
          uint32_t e[4];
          lds128(e, sb + EX + 2048 + t16);
          A0[0] = pack_bf16((v[0] + __uint_as_float(e[0])) * inv_sc, (v[1] + __uint_as_float(e[1])) * inv_sc);
          A0[1] = pack_bf16((v[2] + __uint_as_float(e[2])) * inv_sc, (v[3] + __uint_as_float(e[3])) * inv_sc);
          const uint32_t slab = slab_off(VT, w, ln);
          sts32(sb + slab, A0[0]); sts32(sb + slab + 640, A0[1]);
          bar_arrive(12, 384);
        }
        if (s == NSEG - 1) break;
        {
          const uint32_t ln = opq(lane);
          const uint32_t va = sb + VT + (16 * w + (ln & 15)) * 80 + 16 + (ln >> 4) * 16;
          const uint32_t sa = sb + SX + ln * 4, off = OB + w * 256 + ln * 4;
          const Peers pe(sb, j);
          uint32_t f1[4], f2[4];
          ldsm4(f1, va); ldsm4(f2, va + 32);
          TSX(TS(1));
          mbar_wait(sb + BAR_S, s & 1);
          TS(2);
          uint32_t u[3][5];
#pragma unroll
          for (int i = 0; i < 15; i++) u[i / 5][i % 5] = lds32(sa + (i % 5) * 128 + (i / 5) * 640);
          E1(2, u[0][0]);
          sched_fence(zero);
          uint32_t hs[5];
#pragma unroll
          for (int i = 0; i < 5; i++) hs[i] = hadd2(hadd2(u[0][i], u[1][i]), u[2][i]);
          uint32_t m2 = hmax2(hmax2(hmax2(hs[0], hs[1]), hmax2(hs[2], hs[3])), hs[4]);
          asm volatile("bar.arrive 13, 384;" : "+r"(m2) :: "memory");
          m2 = hmax2(m2, __byte_perm(m2, 0, 0x1032));
          m2 = hmax2(m2, __shfl_xor_sync(0xffffffffu, m2, 1));
          m2 = hmax2(m2, __shfl_xor_sync(0xffffffffu, m2, 2));
          TSX(TSD(3, m2));
          const float m4 = -4.0f * __low2float(*reinterpret_cast<__half2*>(&m2));
          uint32_t P[5];
#pragma unroll
          for (int i = 0; i < 5; i++) {
            const float2 x = __half22float2(*reinterpret_cast<__half2*>(&hs[i]));
            P[i] = pack_bf16(ex2(fmaf(x.x, 4.0f, m4)), ex2(fmaf(x.y, 4.0f, m4)));
          }
          float o[4] = {0.f, 0.f, 0.f, 0.f}, o2[4] = {0.f, 0.f, 0.f, 0.f}, o3[4] = {0.f, 0.f, 0.f, 0.f};
          mma16816(o2, f1, P[1], P[2]); mma1688(o, A0[0], A0[1], P[0]); mma16816(o3, f2, P[3], P[4]);
          const uint32_t w0 = pack_bf16((o[0] + o2[0]) + o3[0], (o[1] + o2[1]) + o3[1]), w1 = pack_bf16((o[2] + o2[2]) + o3[2], (o[3] + o2[3]) + o3[3]);
#pragma unroll
          for (int r = 0; r < 2; r++) { st_async32(pe.a[r] + off + (2 - r) * 1024, w0, pe.a[r] + BAR_O); st_async32(pe.a[r] + off + (2 - r) * 1024 + 128, w1, pe.a[r] + BAR_O); }
          E1(3, w0 ^ w1);
          sts32(sb + off, w0); sts32(sb + off + 128, w1);
          if (w == 3) {
            float z[4] = {0.f, 0.f, 0.f, 0.f}, z2[4] = {0.f, 0.f, 0.f, 0.f};
            const uint32_t one[4] = {0x3F803F80u, 0x3F803F80u, 0x3F803F80u, 0x3F803F80u};
            mma1688(z, one[0], one[1], P[0]); mma16816(z2, one, P[1], P[2]); mma16816(z, one, P[3], P[4]);
            if (ln < 4) sts64(sb + INV + ln * 8, __float_as_uint(rcp(z[0] + z2[0])), __float_as_uint(rcp(z[1] + z2[1])));
          }
          TS(4);
        }
        if (12 + w < NT) {
          const uint32_t ln = opq(lane);
          const char* pr = arb + ar_tile_off(T0 + 12 + w) + ln * 4; const char* px = arb + ar_extra_off(T0 + 12 + w);
          PINL(pr);
          wo_tile_smem<true>(sb, sb + WOF + (4 + w) * 6144 + ln * 16, sb + OB + ln * 16, s & 1, pr, px, ln == 31, sc);
        } else {
          bar_sync(9, 384);
          sc = __uint_as_float(lds32(sb + MX + 16));
          if (w == 3 && lane == 0) {
            mbar_expect(sb + BAR_S, 1280);
            if (!KS2 && !X1E && j == 1 && s + 2 < NSEG) {
              mbar_wait(sb + BAR_XF, s & 1);
              tma3d_mc(sb + XB + 20480, &mx, 0, (s + 2) * SEG, 5, sb + BAR_X1, 7);
            }
            mbar_wait(sb + BAR_O, s & 1);
            mbar_expect(sb + BAR_O, 2048);
          }
          __syncwarp();
        }
        TSX(TS(5));
        if (w == 1) SS(0);
        mbar_wait(sb + BAR_X0, (s + 1) & 1);
        if (w == 1) SS(1);
        bar_sync(4, 384);
        if (w == 1) SS(2);
        arb += AR_STEP_BYTES;
        }
        tokens_finish<true>(sb, W, xdesc, w, lane, s);
        TS(6);
        if (LSH && s < 0) {
          if (tid == 0) PT(0, 13);
          arrange_wq(sb, 0, w, layer);
        }
        inv_sc = __uint_as_float(0x7F000000u - __float_as_uint(sc));
      }
    } else {
      const uint32_t lane = lane_id();
      static_assert(!X0E && !KS2, "prologue");
      code_pad<PAD1>(zero);
#pragma unroll 1
      for (int pass = 0; pass < (LSH ? 1 : 2); pass++) {
        mbar_wait_long(sb + BAR_X1, pass);
        if (pass) bar_sync(8, 256);
        tokens_partial<0>(sb, PK, W, xdesc, w, lane);
        if (pass) break;
        mbar_wait(sb + BAR_X1, 0);
        tokens_partial<0>(sb, QS, W + 80, xdesc, w, lane);
        bar_sync(8, 256);
      }
      if (LSH) {
        if (w == 3 && lane == 0) { mbar_expect(sb + BAR_X1, 20480); tma3d(sb + XB + 20480, &mx, 0, SEG, 5, sb + BAR_X1); }
        __syncwarp();
      } else {
        if (tid == 128) PT(0, 14);
        arrange_wq(sb, 1, w, layer);
      }
#pragma unroll 1
      for (int s = LSH ? -1 : 0; s < NSEG; s++) {
        float sc = 1.0f;
        if (!LSH || s >= 0) {
        {
          float q[4], k[4], v[4];
          const uint32_t ln = opq(lane), t16 = w * 512 + ln * 16;
          uint32_t f[NF][4], wq = sb + WQ + 40960 + (WQR ? t16 : afrag_off(w, ln)), ba = sb + MEMB + 5120 + ln * 16;
          proj_stage(f, wq);
          PIN(ba);
          proj_mem<1>(q, k, v, f, W, wq, ba, sb, w, s);
          const uint32_t qd = sb + QS + 1024 + w * 256 + ln * 4;
          sts32(qd, pack_bf16(q[0] * inv_sc, q[1] * inv_sc)); sts32(qd + 128, pack_bf16(q[2] * inv_sc, q[3] * inv_sc));
          sts32(qd + 2048, pack_bf16(k[0] * inv_sc, k[1] * inv_sc)); sts32(qd + 2048 + 128, pack_bf16(k[2] * inv_sc, k[3] * inv_sc));
          sts128(sb + EX + 2048 + t16, __float_as_uint(v[0]), __float_as_uint(v[1]), __float_as_uint(v[2]), __float_as_uint(v[3]));
          TSX(TS(0));
          bar_sync(2, 384);
          uint32_t e[4];
          lds128(e, sb + EX + t16);
          const uint32_t slab = slab_off(KT, w, ln);
          sts32(sb + slab, pack_bf16((k[0] + __uint_as_float(e[0])) * inv_sc, (k[1] + __uint_as_float(e[1])) * inv_sc));
          sts32(sb + slab + 640, pack_bf16((k[2] + __uint_as_float(e[2])) * inv_sc, (k[3] + __uint_as_float(e[3])) * inv_sc));
        }
        if (s == NSEG - 1) { bar_arrive(12, 384); break; }
        if (w == 1) SS(3);
        if (KS2) mbar_wait(sb + BAR_X1, (s + 1) & 1);
        if (w == 1) SS(4);
        if (VL) {
          bar_arrive(12, 384); bar_arrive(13, 384);
          bar_sync(9, 384);
          tokens_partial<3>(sb, QS, W + 80, xdesc, w, lane);
        } else {
          bar_sync(5, 288);
          TSX(TS(1));
          tokens_partial<1>(sb, QS, W + 80, xdesc, w, lane);
        }
        if (!KS2 && X1E && j == 1 && w == 3 && s + 2 < NSEG) {
          if (opq(lane) == 0) {
            mbar_wait(sb + BAR_XF, s & 1);
            tma3d_mc(sb + XB + 20480, &mx, 0, (s + 2) * SEG, 5, sb + BAR_X1, 7);
          }
          __syncwarp();
        }
        TS(2);
        {
          const uint32_t ln = opq(lane);
          const char* pr = arb + ar_tile_off(T0 + 8 + w) + ln * 4; const char* px = arb + ar_extra_off(T0 + 8 + w);
          PINL(pr);
          wo_tile_smem<!VL>(sb, sb + WOF + w * 6144 + ln * 16, sb + OB + ln * 16, s & 1, pr, px, ln == 31, sc);
        }
        if (KS2) bar_sync(4, 384);
        else if (KORD) {
          if (s + 2 < NSEG) mbar_wait(sb + BAR_X1, s & 1);
          bar_sync(4, 384);
        } else {
          bar_arrive(4, 384);
        }
        arb += AR_STEP_BYTES;
        }
        if (!KS2 && !KORD) {
          if (s + 2 < NSEG) { if (LSH && s < 0) mbar_wait_long(sb + BAR_X1, 1); else mbar_wait(sb + BAR_X1, s & 1); }
          bar_sync(6, 256);
        }
        tokens_partial<2>(sb, PK, W, xdesc, w, lane);
        if (LSH && s < 0) {
          if (tid == 128) PT(0, 14);
          arrange_wq(sb, 1, w, layer);
        }
        if (X0E && j == 0 && w == 2 && s + 2 < NSEG) {
          if (opq(lane) == 0) {
            mbar_wait(sb + BAR_XF, (s + 1) & 1);
            const uint32_t t9 = clk32();
            while (clk32() - t9 < X0D_) {}
            tma3d_mc(sb + XB, &mx, 0, (s + 2) * SEG, 0, sb + BAR_X0, 7);
          }
          __syncwarp();
        }
        if (KS2 && j == 1 && w == 0 && s + 2 < NSEG) {
          if (opq(lane) == 0) {
            mbar_wait(sb + BAR_XF, s & 1);
            tma3d_mc(sb + XB + 20480, &mx, 0, (s + 2) * SEG, 5, sb + BAR_X1, 7);
          }
          __syncwarp();
        }
        TS(4);
        inv_sc = __uint_as_float(0x7F000000u - __float_as_uint(sc));
      }
    }
    asm volatile("barrier.cluster.arrive.relaxed.aligned;" ::: "memory");
    tail_sum(sb, &g_sync[layer], xin, layer);
  } else {
    asm volatile("setmaxnreg.dec.sync.aligned.u32 88;");
    const uint32_t lane = lane_id();
    uint32_t W[44];
    if (tid - 256 < 80) asm volatile("prefetch.global.L2 [%0];" :: "l"(mem0 + (tid - 256) * 64) : "memory");
    if (w == 3) {
      if (layer && LNF == 1) bar_sync(10, 64);
      const int win = layer ? PWIN1 : PWIN;
#pragma unroll
      for (int part = 0; part < 2; part++) {
        if (lane == 0) {
#pragma unroll
          for (int i = part ? 2 : 0; i < (part ? 14 : 2); i++) {
            const uint32_t bar = sb + PB + i * 8;
            if (i >= win) mbar_wait_long(bar - win * 8, 0);
            if (i == 12) mbar_wait_long(sb + BAR_W1, 0);
            if (i < 5 || (i >= 7 && i < 12)) {
              mbar_expect(bar, 16384);
              if (i < 5) tma2d(sb + 81920 + i * 16384, &mv, h * DH + 64 * j, i * 128, bar);
              else tma2d(sb + (i - 7) * 16384, &mk, h * DH + 64 * j, (i - 7) * 128, bar);
            } else {
              const int bx = i < 7 ? i - 4 : (i - 12) * 3;
              mbar_expect(bar, 24576);
              tma2d(bx < 3 ? sb + WOSTAGE + bx * 24576 : sb + WOF, &mo, T0 * 16 + 64 * bx, h * DH, bar);
            }
          }
        }
        __syncwarp();
        if (part == 0 && layer && LNF == 2) bar_sync(10, 64);
      }
      if (lane == 0) {
        mbar_wait_long(sb + BAR_WK, 0);
        for (int i = 0; i < 2; i++) tma2d(sb + WQ + i * 16384, &mq, h * DH + 64 * j, i * 128, sb + BAR_W2);
      }
      __syncwarp();
    } else {
      if (!(BLN && layer) && !(WLN >> layer & 1)) {
        chain_prepare(xin);
        for (int i = blockIdx.x * 96 + tid - 256; i < (NSEG - 1) * 24 * 32; i += 96 * 96) ((uint4*)g_ar)[(i >> 5) * 64 + (i & 31)] = make_uint4(0, 0, 0, 0);
      } else if (BLN && w == 0) asm volatile("griddepcontrol.wait;" ::: "memory");
      if (WLN != 3) bar_sync(9, 352);
    }
    PT(0, 1);
    if (w == 0) {
      if (lane == 0) {
        if (layer) sts32(sb + MX + 24, __ldcg(&g_kw));
        if (!(WLN >> layer & 1)) red_release(&g_sync[layer].pro[0]);
        else if (layer && blockIdx.x == 0) {
          asm volatile("griddepcontrol.wait;" ::: "memory");
          if (WREL) red_release(&g_sync[1].pro[1]);
          else asm volatile("red.relaxed.gpu.global.add.u32 [%0], 1;" :: "l"(&g_sync[1].pro[1]) : "memory");
        }
      }
      PT(0, 2);
      __syncwarp();
      if (layer && LNF) bar_arrive(10, 64);
    }
    if (!(PSPL && layer) && !(WLN & 1) && tid == 256) spin_count(&g_sync[layer].pro[0], 96);
    __syncwarp();
    PT(0, 3);
    mbar_wait_long(sb + PB + 5 * 8, 0); mbar_wait_long(sb + PB + 12 * 8, 0);
    PT(0, 4);
    {
      const int i = lane >> 3, r = lane & 7;
      uint32_t m = 0;
#pragma unroll
      for (int kk = 0; kk < 12; kk++)
#pragma unroll
        for (int tt = 0; tt < 2; tt++) {
          const int tl = 2 * w + tt;
          const uint32_t src = sb + WOSTAGE + (tl >> 2) * 24576 + (((kk + 4 * j) % 12) * 16 + (i >> 1) * 8 + r) * 128 + ((((tl & 3) * 2 + (i & 1)) ^ r) << 4);
          const int q = kk * 2 + tt;
          if (q >= 13) { ldsm4t_p(&W[(q - 13) * 4], src); m = mag4(m, &W[(q - 13) * 4]); }
          else { uint32_t f[4]; ldsm4t(f, src); sts128(sb + (q < 12 ? WOF2 + (w * 12 + q) * 512 : WOF3 + w * 512) + lane * 16, f[0], f[1], f[2], f[3]); m = mag4(m, f); }
        }
      publish_max(sb + WMX + 4, m);
    }
    bar_sync(7, 384);
    PT(0, 5);
    if (tid == 256 && !layer) {
      const float2 mm = lds64f(sb + WMX);
      asm volatile("st.relaxed.gpu.global.u32 [%0], %1;" :: "l"(&g_sync[layer].wmax[blockIdx.x]), "r"(0x10000u | (__float_as_uint(mm.x) >> 7 << 8) | (__float_as_uint(mm.y) >> 7)) : "memory");
    }
    uint32_t m0[3][8];
#pragma unroll
    for (int i = 0; i < 24; i++) m0[i >> 3][i & 7] = __ldg((const uint32_t*)(mem0 + (i & 7) * DM) + min(tid - 256 + (i >> 3) * 128, DM / 2 - 1));
    if (tid == 352) {
      if (BLN) asm volatile("griddepcontrol.wait;" ::: "memory");
      else if (WLN >> layer & 1) spin_count(&g_sync[layer].pro[2], 4);
      else if (PSPL && layer) spin_count(&g_sync[layer].pro[0], 96);
      if (XFEN == 0) asm volatile("fence.proxy.async;" ::: "memory");
      if (XFEN == 1) asm volatile("fence.proxy.async.global;" ::: "memory");
      mbar_expect(sb + BAR_X1, 20480); tma3d(sb + XB + 20480, &mx, 0, 0, 5, sb + BAR_X1);
      mbar_expect(sb + BAR_X0, 20480); tma3d(sb + XB, &mx, 0, 0, 0, sb + BAR_X0);
      for (int i = 2; i < 5; i++) tma2d(sb + WQ + i * 16384, &mq, h * DH + 64 * j, i * 128, sb + BAR_W2);
    }
    __syncwarp();
    bar_sync(7, 384);
    PT(0, 6);
    uint32_t wv[3];
    if (w == 0 && !layer)
#pragma unroll
      for (int i = 0; i < 3; i++) asm volatile("ld.relaxed.gpu.global.u32 %0, [%1];" : "=r"(wv[i]) : "l"(&g_sync[layer].wmax[lane + i * 32]) : "memory");
    {
      int em;
      uint32_t m = 0;
#pragma unroll
      for (int i = 0; i < 3; i++) {
        const int p = tid - 256 + i * 128;
        if (p < DM / 2) {
          uint32_t lo[4], hi[4];
#pragma unroll
          for (int q = 0; q < 4; q++) { lo[q] = __byte_perm(m0[i][2 * q], m0[i][2 * q + 1], 0x5410); hi[q] = __byte_perm(m0[i][2 * q], m0[i][2 * q + 1], 0x7632); }
          sts128(sb + MEMB + p * 32, lo[0], lo[1], lo[2], lo[3]); sts128(sb + MEMB + p * 32 + 16, hi[0], hi[1], hi[2], hi[3]);
        }
#pragma unroll
        for (int q = 0; q < 8; q++) m = __vmaxu2(m, m0[i][q] & 0x7FFF7FFFu);
      }
      em = __reduce_max_sync(0xffffffffu, (int)(max(m & 0xFFFFu, m >> 16) >> 7) - 126);
      if (lane == 0) sts32(sb + MX + w * 4, em);
    }
    if ((WLN >> layer & 1) && tid == 352) spin_count(&g_sync[layer].pro[0], 128);
    __syncwarp();
    PT(0, 7);
    bar_arrive(1, 384);
    bar_sync(3, 384);
    if (w == 0 && !layer) {
      for (int n = 0; n < 4000000 && !__all_sync(0xffffffffu, (wv[0] & wv[1] & wv[2]) >> 16); n++) {
#pragma unroll
        for (int i = 0; i < 3; i++) asm volatile("ld.relaxed.gpu.global.u32 %0, [%1];" : "=r"(wv[i]) : "l"(&g_sync[layer].wmax[lane + i * 32]) : "memory");
      }
      const int ev = __reduce_max_sync(0xffffffffu, max(max(wv[0] >> 8 & 255, wv[1] >> 8 & 255), wv[2] >> 8 & 255));
      const int eo = __reduce_max_sync(0xffffffffu, max(max(wv[0] & 255, wv[1] & 255), wv[2] & 255));
      if (lane == 0) {
        sts32(sb + MX + 24, 245 - ev - eo);
        if (blockIdx.x == 0) g_kw = 245 - ev - eo;
      }
      __syncwarp();
    }
    int dly = PD;
    PT(0, 8);
    for (int s = 0; s < NSEG; s++) {
      const uint32_t t0 = clk32();
      TS(0);
      {
        uint32_t b0[4], b1[4];
        const uint32_t ln = opq(lane);
        const uint32_t ka = sb + KT + ln * 80 + (1 + w) * 16;
        ldsm4t(b0, ka); ldsm4t(b1, ka + 2560);
        if (w == 0 && ln == 0 && s + 1 < NSEG) {
          if (!X0E && j == 0) {
            mbar_wait(sb + BAR_XF, s & 1);
            while (clk32() - t0 < XD) {}
            tma3d_mc(sb + XB, &mx, 0, (s + 1) * SEG, 0, sb + BAR_X0, 7);
          }
          if (s + 2 < NSEG - 1 && !(FL & 2)) asm volatile("prefetch.global.L2 [%0];" :: "l"(arb + 2 * AR_STEP_BYTES + ar_line_off(h * 3 + j)) : "memory");
          if (PFW && layer == 0 && s >= PFW && s < PFW + 10) tma2d_prefetch(s & 1 ? &mk : &mv, h * DH + 64 * j, ((s - PFW) >> 1) * 128);
          if (j == 2 && h == (s & 31) && s + 3 < NSEG) { tma3d_prefetch(&mx, 0, (s + 3) * SEG, 0); tma3d_prefetch(&mx, 0, (s + 3) * SEG, 5); }
        }
        __syncwarp();
        uint32_t qa = sb + QS + ((ln >> 3) & 1) * 1024 + ((ln >> 4) * 8 + (ln & 7)) * 16, off = SX + j * 640 + (1 + w) * 128 + ln * 4;
        PIN(qa); PIN(off);
        bar_sync(2, 384);
        if (s == NSEG - 1) break;
        score_tile(sb, qa, b0, b1, Peers(sb, j), off, ln);
        bar_sync(12, 384);
        if (SD) bar_sync(13, 384);
        if (w == 1 && ln == 0 && !(FL & 1)) {
          store_slabs(sb, s, h, j);
        }

        __syncwarp();
      }
      if (w == 0) {
        uint32_t v[4]; lds128(v, sb + MX);
        const int kw = lds32(sb + MX + 24);
        const int em = max(max(max((int)v[0], (int)v[1]), max((int)v[2], (int)v[3])), 1);
        const int e = min(max(kw - em, -120), 120);
        if (opq(lane) == 0) { sts32(sb + MX + 16, (uint32_t)(e + 127) << 23); sts32(sb + MX + 20, 0u); }
      }
      if (!SD) bar_sync(13, 384);
      uint32_t tref;
      {
        float c0[4] = {0.f, 0.f, 0.f, 0.f}, c1[4] = {0.f, 0.f, 0.f, 0.f}, d0[4] = {0.f, 0.f, 0.f, 0.f}, d1[4] = {0.f, 0.f, 0.f, 0.f};
        uint32_t f[4][4], b[2][4];
        const uint32_t ln = opq(lane);
        const uint32_t fa = sb + WOF2 + w * 6144 + ln * 16, ob = sb + OB + ln * 16;
#pragma unroll
        for (int i = 0; i < 4; i++) lds128(f[i], fa + i * 512);
        if (w == 1) SS(5);
        asm volatile("cp.async.bulk.wait_group.read 0;" ::: "memory");
        if (w == 1) SS(6);
        bar_sync(9, 384);
        ldsm4t(b[0], ob); ldsm4t(b[1], ob + 512);
        mma16816(c0, f[0], b[0][0], b[0][1]); mma16816(c1, f[1], b[0][0], b[0][1]);
        lds128(f[0], fa + 2048); lds128(f[1], fa + 2560);
        mma16816(d0, f[2], b[0][2], b[0][3]); mma16816(d1, f[3], b[0][2], b[0][3]);
        lds128(f[2], fa + 3072); lds128(f[3], fa + 3584);
        mma16816(c0, f[0], b[1][0], b[1][1]); mma16816(c1, f[1], b[1][0], b[1][1]);
        mma16816(d0, f[2], b[1][2], b[1][3]); mma16816(d1, f[3], b[1][2], b[1][3]);
#pragma unroll
        for (int i = 0; i < 4; i++) lds128(f[i], fa + (8 + i) * 512);
        mbar_wait(sb + BAR_O, s & 1);
        ldsm4t(b[0], ob + 1024);
        E1(4, b[0][0]);
        mma16816(c0, f[0], b[0][0], b[0][1]); mma16816(c1, f[1], b[0][0], b[0][1]);
        mma16816(d0, f[2], b[0][2], b[0][3]); mma16816(d1, f[3], b[0][2], b[0][3]);
        ldsm4t(b[0], ob + 1536); lds128(f[0], sb + WOF3 + w * 512 + ln * 16); ldsm4t(f[1], ob + 2048); ldsm4t(f[2], ob + 2560);
        float2 iv = lds64f(sb + INV + (ln & 3) * 8);
        const float sc = __uint_as_float(lds32(sb + MX + 16));
        sched_fence(zero);
        mma16816(c1, &W[0], b[0][0], b[0][1]); mma16816(d0, &W[4], b[0][2], b[0][3]); mma16816(d1, &W[8], b[0][2], b[0][3]);
        mma16816(c0, f[0], b[0][0], b[0][1]);
        const char* pr = arb + ar_tile_off(T0 + 2 * w) + ln * 4;
        PINL(pr);
        iv.x *= sc; iv.y *= sc;
        mma16816(c1, &W[16], f[1][0], f[1][1]); mma16816(d0, &W[20], f[1][2], f[1][3]); mma16816(d1, &W[24], f[1][2], f[1][3]);
        mma16816(c0, &W[12], f[1][0], f[1][1]);
        mma16816(c1, &W[32], f[2][0], f[2][1]); mma16816(d0, &W[36], f[2][2], f[2][3]); mma16816(d1, &W[40], f[2][2], f[2][3]);
        mma16816(c0, &W[28], f[2][0], f[2][1]);
        const uint32_t w2 = pack_f16((c1[0] + d1[0]) * iv.x, (c1[1] + d1[1]) * iv.y), w3 = pack_f16((c1[2] + d1[2]) * iv.x, (c1[3] + d1[3]) * iv.y);
        wo_red(pr + ((T0 & 1) ? 768 : 256), w2, w3, ln == 31);
        const uint32_t w0 = pack_f16((c0[0] + d0[0]) * iv.x, (c0[1] + d0[1]) * iv.y), w1 = pack_f16((c0[2] + d0[2]) * iv.x, (c0[3] + d0[3]) * iv.y);
        E1(5, w0 ^ w2);
        wo_red(pr, w0, w1, ln == 31);
        wo_red_extra_p(arb + ar_extra_off(T0 + 2 * w + 1), w2, w3, ln);
        wo_red_extra_p(arb + ar_extra_off(T0 + 2 * w), w0, w1, ln);
        if (TSYNC) bar_sync(4, 384); else bar_arrive(4, 384);
        tref = clk32();
      }
      TSV(2, tref); TS(3);
      if (w == 1 && opq(lane) == 0) {
        asm volatile("cp.async.bulk.wait_group 0;" ::: "memory");
        publish_bulk<0>(&g_sync[layer].kv[s * NH + h]);
      }
      __syncwarp();
      {
        const uint32_t m = ar_read(arb, sb, w, lane, zero, tref, dly, s);
        dly = lds32(sb + MX + 20) ? dly + (int)UP : max(dly - (int)CS, (int)DMIN);
        if (w == 3) TSV(1, dly);
        const int em = __reduce_max_sync(0xffffffffu, (int)(max(m & 0xFFFFu, m >> 16) >> 10) - 13 + 127 - (int)(lds32(sb + MX + 16) >> 23));
        if (opq(lane) == 0) sts32(sb + MX + w * 4, em);
      }
      arb += AR_STEP_BYTES;
    }
    asm volatile("barrier.cluster.arrive.relaxed.aligned;" ::: "memory");
    if (fresh_tid() >= 352) {
      if (fresh_tid() == 352) {
        asm volatile("prefetch.tensormap [%0];" :: "l"(&mwo) : "memory"); asm volatile("prefetch.tensormap [%0];" :: "l"(&moa) : "memory");
        const uint32_t n = fresh_cta() < 64 ? 8 : 4;
        for (int i = 0; i < 7; i++) { mbar_init(sb + tl::FULL + i * 8, 1); mbar_init(sb + tl::EMPTY + i * 8, n); }
        asm volatile("fence.mbarrier_init.release.cluster;" ::: "memory");
      }
      __syncwarp();
      bar_arrive(14, 288);
    }
    bar_sync(12, 384);
    if (LASTG) {
      bf16* kvp = g_kv + ((size_t)((NSEG - 1) * NH + h) * 2 * DH + 64 * j) * NKEY;
#pragma unroll
      for (int k = 0; k < 5; k++) {
        const int u = k * 128 + tid - 256;
        uint32_t v[4];
        lds128(v, sb + KT + u * 16);
        __stcg((uint4*)(kvp + (u < 320 ? u * 8 : DH * NKEY + (u - 320) * 8)), make_uint4(v[0], v[1], v[2], v[3]));
      }
      bar_sync(10, 128);
      if (tid == 256 + 32) {
        asm volatile("cp.async.bulk.wait_group 0;" ::: "memory");
        red_release(&g_sync[layer].kv[(NSEG - 1) * NH + h]);
        GT(0, 1);
        if (TPOS < 2) tail_load(sb, &g_sync[layer], &moa, &mwo, layer);
      }
      __syncwarp();

    } else if (tid == 256 + 32) {
      store_slabs(sb, NSEG - 1, h, j);
      asm volatile("cp.async.bulk.wait_group 0;" ::: "memory");
      publish_bulk<WFEN>(&g_sync[layer].kv[(NSEG - 1) * NH + h]);
    }
  }
  if (TPOS) {
    const uint32_t t = fresh_tid();
    uint32_t sb2 = smem_u32(smraw);
    if (TPOS == 3) sb2 += zero;
    if (TPOS >= 2 && t == 288) tail_load(sb2, &g_sync[layer], &moa, &mwo, layer);
    __syncwarp();
  }
  asm volatile("barrier.cluster.wait.aligned;" ::: "memory");
}

DEVI void bulk_load(uint32_t dst, const void* g, uint32_t bytes, uint32_t bar) {
  if (EVF & 2) asm volatile("cp.async.bulk.shared::cluster.global.mbarrier::complete_tx::bytes.L2::cache_hint [%0], [%1], %2, [%3], %4;" :: "r"(dst), "l"(g), "r"(bytes), "r"(bar), "l"(stream_policy()) : "memory");
  else asm volatile("cp.async.bulk.shared::cluster.global.mbarrier::complete_tx::bytes [%0], [%1], %2, [%3];" :: "r"(dst), "l"(g), "r"(bytes), "r"(bar) : "memory");
}
DEVI void bulk_load_plain(uint32_t dst, const void* g, uint32_t bytes, uint32_t bar) {
  asm volatile("cp.async.bulk.shared::cluster.global.mbarrier::complete_tx::bytes [%0], [%1], %2, [%3];" :: "r"(dst), "l"(g), "r"(bytes), "r"(bar) : "memory");
}
DEVI void tma3d_store(const CUtensorMap* m, uint32_t src, int c0, int c1, int c2) {
  if (EVF & 4) asm volatile("cp.async.bulk.tensor.3d.global.shared::cta.bulk_group.L2::cache_hint [%0, {%2, %3, %4}], [%1], %5;" :: "l"(m), "r"(src), "r"(c0), "r"(c1), "r"(c2), "l"(stream_policy()) : "memory");
  else asm volatile("cp.async.bulk.tensor.3d.global.shared::cta.bulk_group [%0, {%2, %3, %4}], [%1];" :: "l"(m), "r"(src), "r"(c0), "r"(c1), "r"(c2) : "memory");
}
namespace wk {
constexpr uint32_t STAGE = 40960, NST = 4, OST = NST * STAGE;
constexpr uint32_t MISC = OST + 49152;
constexpr uint32_t FULL = MISC, EMPTY = MISC + 32, TFULL = MISC + 64, TEMPTY = MISC + 80, TASK = MISC + 96;
constexpr uint32_t DONE = MISC + 104, FREE = MISC + 120, DTASK = MISC + 136, FIN = MISC + 144, DSLOT = MISC + 152;
constexpr uint32_t CGO = MISC + 160;
constexpr uint32_t LBAR = MISC + 168, TL = MISC + 176;
constexpr uint32_t SMEM = TL + 5136;
#define NP2 10
constexpr int NZ = 16, NP = NZ + 80 + NP2, NQ = 512;
#define S15 8
#define SPLITS rt < RT_SPLIT ? 1 : rt < 11 ? 2 : rt < 13 ? 4 : rt < 15 ? 8 : S15
__host__ __device__ constexpr int split(int rt) { return SPLITS; }
__host__ __device__ constexpr int count_w(int rt) { return rt < 0 ? 0 : 4 * split(rt) + count_w(rt - 1); }
constexpr int NW = count_w(15);
__host__ __device__ constexpr int first_slice(int rt) { return rt <= RT_SPLIT ? 0 : first_slice(rt - 1) + split(rt - 1); }
static_assert(first_slice(16) <= NSL, "slice buffer");
DEVI int slice_of(int rt) {
  constexpr int f9 = first_slice(9), f10 = first_slice(10), f11 = first_slice(11), f12 = first_slice(12), f13 = first_slice(13), f14 = first_slice(14), f15 = first_slice(15);
  return rt < 9 ? 0 : rt == 9 ? f9 : rt == 10 ? f10 : rt == 11 ? f11 : rt == 12 ? f12 : rt == 13 ? f13 : rt == 14 ? f14 : f15;
}
static_assert(RT_SPLIT >= 8, "slice_of");
enum { T_Q, T_W, T_P, T_END, T_G, T_F };
#define RG0 14
#define RG1 13
#define BKVZ (CTAIL ? 12 : 14)
#define PFB 0
#define WLD 2
#define OKEEP 13
#define OPF 0
#define SENT 1
#define FLATE 10
#define WGRID 0
#define PFRONT 0
#define PTAIL 0
#define WPRE 0
#define PFF (CTAIL ? 12 : 14)
#define PFACC 0
#define P2LATE 0
#define LAGK0 16
#define LAGK1 16
#define DEFW0 13
#define DEFW1 13
#define NWE0 0
#define NWE1 0
#define SLATE0 1
#define SLATE1 1
#define SLATE 1
#define FLAG 3
#define FWARM 0
#define SLEV 1
#define SLC 1
#define LFAST 1
#define SCOUT0 13
#define SCOUT1 13
#define NSCOUT 0
#define FVOL 1
#define FXT 10
#define FCGO 0
#define P1M 1
#define TMPF 1
#define ZPRE 1
#define CLQ 8
#define CLW 3
struct Task { int type, rt, a, b; };
DEVI int wtasks(int rt) { return 4 * split(rt); }
DEVI int lsplit(int rt) { return 31 - __clz(split(rt)); }
DEVI Task decode(int id) { return {id >> 24, (id >> 16) & 255, id & 255, (id >> 8) & 255}; }
struct __align__(16) TaskList { int n, tail0, late0, pad; uint32_t t[1280]; };
constexpr void add_w(TaskList& l, int rt, int i0 = 0, int i1 = 64) {
  for (int b = 0; b < split(rt); b++) for (int a = 0; a < 4; a++) if (b * 4 + a >= i0 && b * 4 + a < i1) l.t[l.n++] = (T_W << 24) | (rt << 16) | (b << 8) | a;
}
constexpr void add_f(TaskList& l, int rt, int i0 = 0, int i1 = 64) {
  if (rt >= 0 && split(rt) > 1) for (int a = 0; a < 4; a++) for (int b = 0; b < 128 / FROWS; b++)
    if (a * (128 / FROWS) + b >= i0 && a * (128 / FROWS) + b < i1) l.t[l.n++] = (T_F << 24) | (rt << 16) | (b << 8) | a;
}
constexpr TaskList make_list(int layer) {
  TaskList l = {};
  const int rg = layer == 0 ? RG0 : RG1, lagk = layer == 0 ? LAGK0 : LAGK1, defw = layer == 0 ? DEFW0 : DEFW1, nwe = layer == 0 ? NWE0 : NWE1;
  if (layer == 0) for (int i = NZ; i < (P2LATE ? NZ + 80 : NP) - PTAIL && i < NZ + PFRONT; i++) l.t[l.n++] = (T_P << 24) | i;
  for (int rt = 15; rt >= rg; rt--) for (int h = 0; h < NH; h++) l.t[l.n++] = (T_G << 24) | (rt << 16) | h;
  if (layer == 0) for (int i = NZ + PFRONT; i < (P2LATE ? NZ + 80 : NP) - PTAIL; i++) l.t[l.n++] = (T_P << 24) | i;
  for (int i = 0; i < NZ; i++) l.t[l.n++] = (T_P << 24) | i;
  if (layer == 0 && P2LATE) for (int i = NZ + 80; i < NP; i++) l.t[l.n++] = (T_P << 24) | i;
  for (int rt = 0; rt < 16; rt++) {
    if (rt == 15) l.tail0 = l.n;
    for (int h = 0; h < NH; h++) l.t[l.n++] = (T_Q << 24) | (rt << 16) | ((rt >= rg) << 8) | h;
    if (rt > 0 && rt - 1 < lagk && rt - 1 < defw) add_w(l, rt - 1);
    if (rt >= lagk && rt < defw) add_w(l, rt);
    if (rt == 14 && defw < 14) add_w(l, defw, 0, nwe);
    if (rt == (layer ? SCOUT1 : SCOUT0)) for (int i = 0; i < NSCOUT; i++) l.t[l.n++] = (T_END << 24) | 1;
    if (FWARM && rt - FLAG + 1 == RT_SPLIT) add_f(l, RT_SPLIT, 0, 1);
    if (rt - FLAG < FLATE) add_f(l, rt - FLAG, FWARM && rt - FLAG == RT_SPLIT ? 1 : 0);
  }
  if (layer == 0) for (int i = NP - PTAIL; i < NP; i++) l.t[l.n++] = (T_P << 24) | i;
  if (CTAIL) {
    l.late0 = 1 << 20;
    for (int rt = FLATE; rt < tl::RT0; rt++) add_f(l, rt);
    return l;
  }
  constexpr int W15E = 4 * S15 - 32;
  if (SLATE) add_w(l, 15, 0, W15E);
  if (SLATE && (layer ? SLATE1 : SLATE0) == 2) {
    l.late0 = l.n;
    add_w(l, 14); add_w(l, 15, W15E); add_f(l, 10); add_f(l, 11);
    for (int rt = 12; rt < 16; rt++) add_f(l, rt);
    return l;
  } else if (SLATE) {
    l.late0 = l.n;
    add_w(l, 13); add_w(l, 14); add_w(l, 15, W15E);
  } else {
    for (int rt = defw; rt < 16; rt++) add_w(l, rt, rt == defw && defw < 14 ? nwe : 0);
  }
  for (int rt = FLATE; rt < 16; rt++) add_f(l, rt);
  return l;
}
__device__ const TaskList d_tasks[2] = {make_list(0), make_list(1)};
__host__ __device__ constexpr uint32_t first_task(int layer, int b) {
  if (layer == 0 && PTAIL < NP - NZ) { if (b < PFRONT) return (T_P << 24) | (NZ + b); b -= PFRONT; }
  return (T_G << 24) | ((15 - (b >> 5)) << 16) | (b & 31);
}
constexpr int NLATE = SLATE && !CTAIL ? 96 : 0;
static_assert(CTAIL || !BFL, "flags");
static_assert(!CTAIL || (first_slice(tl::RT0) == tl::SL0 && DEFW0 == tl::RT0 && DEFW1 == tl::RT0 && S15 == 8 && !WGRID && BSL && SLC && LASTG), "tail of the recurrence kernel");
__host__ __device__ constexpr uint32_t late_task(int layer, int i) {
  if ((layer ? SLATE1 : SLATE0) == 2) return i < 64 ? (T_W << 24) | ((14 + (i >> 5)) << 16) | ((((i & 31) >> 2) + (i >> 5) * (S15 - 8)) << 8) | (i & 3)
                                                    : (T_F << 24) | ((6 + (i >> 4)) << 16) | ((i & 3) << 8) | ((i & 15) >> 2);
  return (T_W << 24) | ((13 + (i >> 5)) << 16) | ((((i & 31) >> 2) + (i >> 6) * (S15 - 8)) << 8) | (i & 3);
}
constexpr bool check_first() {
  for (int layer = 0; layer < 2; layer++) {
    const TaskList l = make_list(layer);
    for (int b = 0; b < 64; b++) if (l.t[b] != first_task(layer, b)) return false;
    for (int b = 0; b < NLATE; b++) if (l.t[l.late0 + b] != late_task(layer, b)) return false;
  }
  return true;
}
static_assert(check_first(), "first_task does not match the list");
}

DEVI void pass_stage(uint32_t sb, uint32_t it, int lane) {
  mbar_wait_long(sb + wk::FULL + (it % wk::NST) * 8, (it / wk::NST) & 1);
  if (lane == 0) mbar_arrive(sb + wk::EMPTY + (it % wk::NST) * 8);
}
#define AT(i, x)
template <int NT>
DEVI void attend(uint32_t sb, const uint32_t (&q)[48], int cw, int w, int lane, uint32_t itk, uint32_t itv, uint32_t mid, uint32_t nd) {
  using namespace wk;
  const int g = lane >> 2, t = lane & 3;
  AT(0, q[0]);
  float sc[NT][4];
#pragma unroll
  for (int i = 0; i < NT * 4; i++) sc[i >> 2][i & 3] = 0.f;
  const uint32_t ka = sb + (itk % NST) * STAGE + (w >> 1) * 15360 + lane * 80;
#pragma unroll
  for (int k2 = 0; k2 < 6; k2++) {
    uint32_t b[NT][4];
#pragma unroll
    for (int n = 0; n < NT; n++) ldsm4t(b[n], ka + k2 * 2560 + n * 16);
#pragma unroll
    for (int n = 0; n < NT; n++) mma16816(sc[n], &q[k2 * 8], b[n][0], b[n][1]);
#pragma unroll
    for (int n = 0; n < NT; n++) mma16816(sc[n], &q[k2 * 8 + 4], b[n][2], b[n][3]);
  }
  AT(1, __float_as_uint(sc[NT - 1][0]) ^ __float_as_uint(sc[0][0]));
  __syncwarp();
  if (lane == 0) mbar_arrive(sb + EMPTY + (itk % NST) * 8);
  const float cs = 0.07216878364870322f * 1.4426950408889634f;
  const int r0 = NMEM + (NT == 5 ? 16 : 0) + g;
  float m0 = -INFINITY, m1 = -INFINITY;
#pragma unroll
  for (int n = 0; n < NT; n++)
#pragma unroll
    for (int e = 0; e < 2; e++) {
      const int key = n * 8 + 2 * t + e;
      sc[n][e] = (n < NT - 2 || key <= r0) ? sc[n][e] * cs : -INFINITY; sc[n][2 + e] = (n < NT - 1 || key <= r0 + 8) ? sc[n][2 + e] * cs : -INFINITY;
      m0 = fmaxf(m0, sc[n][e]); m1 = fmaxf(m1, sc[n][2 + e]);
    }
  m0 = fmaxf(m0, __shfl_xor_sync(0xffffffffu, m0, 1)); m1 = fmaxf(m1, __shfl_xor_sync(0xffffffffu, m1, 1));
  m0 = fmaxf(m0, __shfl_xor_sync(0xffffffffu, m0, 2)); m1 = fmaxf(m1, __shfl_xor_sync(0xffffffffu, m1, 2));
  uint32_t P[2 * NT]; float s0 = 0.f, s1 = 0.f;
#pragma unroll
  for (int n = 0; n < NT; n++) {
    const float a = ex2(sc[n][0] - m0), b = ex2(sc[n][1] - m0), c = ex2(sc[n][2] - m1), e = ex2(sc[n][3] - m1);
    s0 += a + b; s1 += c + e; P[2 * n] = pack_bf16(a, b); P[2 * n + 1] = pack_bf16(c, e);
  }
  s0 += __shfl_xor_sync(0xffffffffu, s0, 1); s1 += __shfl_xor_sync(0xffffffffu, s1, 1);
  s0 += __shfl_xor_sync(0xffffffffu, s0, 2); s1 += __shfl_xor_sync(0xffffffffu, s1, 2);
  const float i0 = rcp(s0), i1 = rcp(s1);
  AT(2, __float_as_uint(i0) ^ __float_as_uint(i1));
  mbar_wait_long(sb + FREE + cw * 8, (nd & 1) ^ 1);
  AT(3, 0);
  if (mid != 0xFFFFFFFFu) pass_stage(sb, mid, lane);
  mbar_wait_long(sb + FULL + (itv % NST) * 8, (itv / NST) & 1);
  AT(4, 0);
  const uint32_t vb = sb + (itv % NST) * STAGE + (w >> 1) * 15360;
  const uint32_t va = vb + (lane & 7) * 80 + (lane >> 3) * 16, vc = vb + lane * 80 + 64;
  const uint32_t orow = w * 16 + (lane & 15), ob = sb + OST + cw * 24576 + orow * 128;
#pragma unroll
  for (int n8 = 0; n8 < 3; n8++) {
    uint32_t b[8][4], c[2][4];
    float o[8][4];
#pragma unroll
    for (int i = 0; i < 8; i++) { ldsm4(b[i], va + (n8 * 8 + i) * 640); o[i][0] = o[i][1] = o[i][2] = o[i][3] = 0.f; }
    if (NT == 5) { ldsm4(c[0], vc + n8 * 5120); ldsm4(c[1], vc + n8 * 5120 + 2560); }
#pragma unroll
    for (int i = 0; i < 8; i++) mma16816(o[i], &P[0], b[i][0], b[i][1]);
#pragma unroll
    for (int i = 0; i < 8; i++) { if (NT == 5) mma16816(o[i], &P[4], b[i][2], b[i][3]); else mma1688(o[i], P[4], P[5], b[i][2]); }
    if (NT == 5)
#pragma unroll
      for (int i = 0; i < 8; i++) mma1688(o[i], P[2 * NT - 2], P[2 * NT - 1], c[i >> 2][i & 3]);
#pragma unroll
    for (int i = 0; i < 4; i++)
      stsm4(ob + n8 * 8192 + (((i * 2 + (lane >> 4)) ^ (orow & 7)) << 4), pack_bf16(o[2 * i][0] * i0, o[2 * i][1] * i0), pack_bf16(o[2 * i][2] * i1, o[2 * i][3] * i1),
            pack_bf16(o[2 * i + 1][0] * i0, o[2 * i + 1][1] * i0), pack_bf16(o[2 * i + 1][2] * i1, o[2 * i + 1][3] * i1));
  }
  __syncwarp();
  AT(5, 0);
  if (lane == 0) mbar_arrive(sb + EMPTY + (itv % NST) * 8);
}

__global__ void __launch_bounds__(384, 1)
worker_kernel(int layer, Sync* sy, const bf16* __restrict__ xin, const bf16* __restrict__ wphi, const bf16* __restrict__ wo2,
              const __grid_constant__ CUtensorMap mx, const __grid_constant__ CUtensorMap mq, const __grid_constant__ CUtensorMap moa,
              const __grid_constant__ CUtensorMap mos, const __grid_constant__ CUtensorMap mwo, const __grid_constant__ CUtensorMap mxa,
              const __grid_constant__ CUtensorMap macc, const __grid_constant__ CUtensorMap mwb) {
  using namespace wk;
  extern __shared__ __align__(1024) uint8_t smraw[];
  const uint32_t sb = smem_u32(smraw);
  const int tid = threadIdx.x, lane = tid & 31;
  const int wg = __shfl_sync(0xffffffffu, tid >> 7, 0), w = __shfl_sync(0xffffffffu, (tid >> 5) & 3, 0);
  constexpr int WF = 0;
  if (!WLD) asm volatile("griddepcontrol.launch_dependents;");
  GT(1, 0);
  const int nstat = WGRID ? 0 : min(max((int)gridDim.x - (CTAIL ? 0 : 96), 0), 64);
  int idx0 = 0;
  const int nl = min((int)gridDim.x - nstat, NLATE);
  if (tid == 96 && (int)blockIdx.x >= nstat + nl) idx0 = atomicAdd(&sy->head, 1);
  int id0 = -1;
  uint32_t flag0 = 0;
  if (LFAST && tid == 0 && (int)blockIdx.x >= nstat && (int)blockIdx.x < nstat + nl) {
    if (TMPF) { asm volatile("prefetch.tensormap [%0];" :: "l"(&mwo) : "memory"); asm volatile("prefetch.tensormap [%0];" :: "l"(&moa) : "memory"); }
    id0 = late_task(layer, blockIdx.x - nstat);
    flag0 = ld_acquire(&sy->o[(id0 >> 16 & 255) * 16 + (id0 >> 8 & 255)]);
  }
  if (tid == 0) {
    sts64(sb + FIN, 0, 0);
    for (int i = 0; i < NST; i++) { mbar_init(sb + FULL + i * 8, 1); mbar_init(sb + EMPTY + i * 8, 8); }
    for (int i = 0; i < 2; i++) { mbar_init(sb + TFULL + i * 8, 1); mbar_init(sb + TEMPTY + i * 8, 9); mbar_init(sb + DONE + i * 8, 128); mbar_init(sb + FREE + i * 8, 1); }
    mbar_init(sb + CGO, 1); mbar_init(sb + LBAR, 1);
    asm volatile("fence.mbarrier_init.release.cluster;" ::: "memory");
    mbar_expect(sb + LBAR, sizeof(TaskList));
    bulk_load_plain(sb + TL, &d_tasks[layer], sizeof(TaskList), sb + LBAR);
  }
  uint32_t early = 0;
  if (wg == 0) {
    asm volatile("setmaxnreg.dec.sync.aligned.u32 40;");
    if (LFAST && w == 0) bar_arrive(0, 384); else bar_sync(0, 384);
    if (tid == 96) {
      uint32_t nres = 0;
      bool tail = false;
      int ntask = 0, tail0 = 0, late0 = 0;
      for (uint32_t nt = 0;; nt++) {
        mbar_wait_long(sb + TEMPTY + (nt & 1) * 8, ((nt >> 1) & 1) ^ 1);
        if (nt) mbar_wait_long(sb + CGO, (nt - 1) & 1);
        if (tail) for (int i = 0; i < 4000000 && (lds32(sb + FIN) < nres || lds32(sb + FIN + 4) < nres); i++) {}
        int id;
        if (nt == 0 && (int)blockIdx.x < nstat) id = first_task(layer, blockIdx.x);
        else if (nt == 0 && (int)blockIdx.x < nstat + nl) { id = late_task(layer, blockIdx.x - nstat); tail = true; }
        else {
          const int idx = nstat + (nt ? atomicAdd(&sy->head, 1) : idx0);
          if (!ntask) { mbar_wait_long(sb + LBAR, 0); ntask = lds32(sb + TL); tail0 = lds32(sb + TL + 4); late0 = lds32(sb + TL + 8); }
          const int e = !SLATE || idx < late0 ? idx : idx + nl;
          id = e < ntask ? lds32(sb + TL + 16 + e * 4) : T_END << 24;
          tail = idx >= tail0;
        }
        sts32(sb + TASK + (nt & 1) * 4, id);
        mbar_arrive(sb + TFULL + (nt & 1) * 8);
        if (WLD == 1 && (id >> 24) == T_F && (id >> 16 & 255) >= FLATE) asm volatile("griddepcontrol.launch_dependents;");
        if ((id >> 24) == T_END) {
          if (WLD) asm volatile("griddepcontrol.launch_dependents;");
          early = id & 1;
          break;
        }
        nres += (id >> 24) < T_P;
      }
    } else if (tid == 0) {
      uint32_t it = 0;
      bool have_xn = false, have_zero = false;
      if (TMPF && !LFAST && (int)blockIdx.x >= nstat) {
        asm volatile("prefetch.tensormap [%0];" :: "l"(&mwo) : "memory");
        asm volatile("prefetch.tensormap [%0];" :: "l"(&moa) : "memory");
      }
      if (!BSL && ZPRE && (int)blockIdx.x >= nstat) have_zero = ld_acquire(&sy->zeroed) >= NZ;
      for (uint32_t nt = 0;; nt++) {
        int id = id0;
        if (nt || id0 < 0) {
          mbar_wait_long(sb + TFULL + (nt & 1) * 8, (nt >> 1) & 1);
          id = lds32(sb + TASK + (nt & 1) * 4);
        }
        const Task tk = decode(id);
        if (nt == 0) WS(1, tk.type);
        mbar_arrive(sb + TEMPTY + (nt & 1) * 8);
        if (tk.type == T_END) {
          if (PFB && blockIdx.x < 128) {
            asm volatile("cp.async.bulk.prefetch.L2.global [%0], 19200;" :: "l"((const char*)g_wb1 + blockIdx.x * 19200) : "memory");
            asm volatile("cp.async.bulk.prefetch.L2.global [%0], 6400;" :: "l"((const char*)g_wb2 + blockIdx.x * 6400) : "memory");
          }
          early = id & 1;
          GT(1, 1); break;
        }
        if (tk.type == T_Q && tk.b) {
          for (int c = 0; c < 4; c++, it++) {
            const uint32_t st = it % NST, a = sb + st * STAGE, fb = sb + FULL + st * 8;
            if (!(c & 1)) {
              wait_count_t(&sy->kv[(tk.rt * 4 + c + 1) * NH + tk.a], 3, tk.rt == 15 && c == 2); fence_flag_to_bulk();
              if (LASTG && tk.rt == 15 && c == 2) asm volatile("fence.proxy.async.global;" ::: "memory");
            }
            if (OPF && c == 0 && tk.rt == 15)
              for (int n = 0; n < OPF; n++) tma3d_prefetch(&mos, 0, 13 * 128 + n * 64, tk.a * 3);
            if (c == 2) mbar_arrive(sb + CGO);
            mbar_wait_long(sb + EMPTY + st * 8, ((it / NST) & 1) ^ 1);
            mbar_expect(fb, 30720);
            const bf16* src = g_kv + ((size_t)((tk.rt * 4 + (c & 2)) * NH + tk.a) * 2 + (c & 1)) * DH * NKEY;
            bulk_load(a, src, 15360, fb);
            bulk_load(a + 15360, src + (size_t)NH * 2 * DH * NKEY, 15360, fb);
          }
        } else if (tk.type == T_G) {
          if (!have_xn) { spin_count(&sy->pro[0], NPRO); asm volatile("fence.proxy.async;" ::: "memory"); have_xn = true; }
          for (int c = 0; c < 10; c++, it++) {
            const uint32_t st = it % NST, a = sb + st * STAGE, fb = sb + FULL + st * 8;
            if (c == CLQ) mbar_arrive(sb + CGO);
            mbar_wait_long(sb + EMPTY + st * 8, ((it / NST) & 1) ^ 1);
            mbar_expect(fb, 40960);
            tma2d(a, &mx, c * 64, tk.rt * 128, fb);
            tma3d(a + 16384, &mq, 0, c * 64, tk.a * 3, fb);
          }
        } else if (tk.type == T_Q) {
          if (!have_xn) { spin_count(&sy->pro[0], NPRO); asm volatile("fence.proxy.async;" ::: "memory"); have_xn = true; }
          bool have_kv = false;
          for (int c = (WF & 2) ? 8 : 0; c < 14; c++, it++) {
            const uint32_t st = it % NST, a = sb + st * STAGE, fb = sb + FULL + st * 8;
            if (c == CLQ) mbar_arrive(sb + CGO);
            if (c >= 4 && !have_kv) {
              const uint32_t* fl = &sy->kv[(tk.rt * 4 + 3) * NH + tk.a];
              if (c == 10) wait_count(fl, 3);
              if (c == 10 || ld_acquire(fl) >= 3) { have_kv = true; fence_flag_to_bulk(); }
            }
            mbar_wait_long(sb + EMPTY + st * 8, ((it / NST) & 1) ^ 1);
            if (c < 10) {
              mbar_expect(fb, 40960);
              tma2d(a, &mx, c * 64, tk.rt * 128, fb);
              tma3d(a + 16384, &mq, 0, c * 64, tk.a * 3, fb);
            } else {
              mbar_expect(fb, 30720);
              const bf16* src = g_kv + ((size_t)((tk.rt * 4 + (c & 1) * 2) * NH + tk.a) * 2 + ((c - 10) >> 1)) * DH * NKEY;
              bulk_load(a, src, 15360, fb);
              bulk_load(a + 15360, src + (size_t)NH * 2 * DH * NKEY, 15360, fb);
            }
          }
        } else if (tk.type == T_W) {
          const int nc = (WF & 1) ? 2 : 96 >> lsplit(tk.rt), c0 = tk.b * nc;
          if (!BSL && tk.rt >= RT_SPLIT && !have_zero) { wait_count(&sy->zeroed, NZ); have_zero = true; }
          const int npre = WPRE ? min(nc, (int)NST) : 0;
          for (int c = 0; c < npre; c++) {
            const uint32_t st = (it + c) % NST, fb = sb + FULL + st * 8;
            mbar_wait_long(sb + EMPTY + st * 8, (((it + c) / NST) & 1) ^ 1);
            mbar_expect(fb, 36864);
            tma3d(sb + st * STAGE + 16384, &mwo, 0, (c0 + c) * 64, tk.a * 5, fb);
          }
          if (nt || flag0 < (64u >> lsplit(tk.rt))) wait_count_t(&sy->o[tk.rt * 16 + tk.b], 64 >> lsplit(tk.rt), tk.rt == 15);
          if (tk.rt >= 13) XT((tk.rt - 13) * 32 + (tk.b >> (tk.rt == 15 && S15 == 16) & 7) * 4 + tk.a, 0);
          fence_flag_to_bulk();
          if (tk.rt >= 13) XT((tk.rt - 13) * 32 + (tk.b >> (tk.rt == 15 && S15 == 16) & 7) * 4 + tk.a, 1);
          for (int c = 0; c < nc; c++, it++) {
            const uint32_t st = it % NST, a = sb + st * STAGE, fb = sb + FULL + st * 8;
            if (c == max(nc - CLW, 0)) mbar_arrive(sb + CGO);
            if (c >= npre) {
              mbar_wait_long(sb + EMPTY + st * 8, ((it / NST) & 1) ^ 1);
              mbar_expect(fb, 36864);
              tma3d(a + 16384, &mwo, 0, (c0 + c) * 64, tk.a * 5, fb);
            }
            tma2d(a, &moa, (c0 + c) * 64, tk.rt * 128, fb);
          }
        } else if (tk.type == T_P && tk.a >= NZ && tk.a < NZ + 80) {
          const uint32_t st = it % NST, a = sb + st * STAGE, fb = sb + FULL + st * 8;
          const int gq = (tk.a - NZ) / 10, k0 = (tk.a - NZ) % 10 * 64;
          mbar_arrive(sb + CGO);
          mbar_wait_long(sb + EMPTY + st * 8, ((it / NST) & 1) ^ 1);
          mbar_expect(fb, 30720 + 3200);
          for (int p = 0; p < 3; p++) tma2d(a + p * 10240, &mwb, p * DM + gq * 80, k0, fb);
          bulk_load_plain(a + 30720, wphi + gq * 4 * BDH * BDH, 3200, fb);
          it++;
        } else if (tk.type != T_F) mbar_arrive(sb + CGO);
      }
    } else if (tid == 32 || tid == 64) {
      const int cw = (tid >> 5) - 1;
      for (uint32_t n = 0;; n++) {
        mbar_wait_long(sb + DONE + cw * 8, n & 1);
        const Task tk = decode(lds32(sb + DTASK + cw * 4));
        if (tk.type == T_END) {
          if (BFL) red_release(&sy->pad1[0]);
          early = tk.a; break;
        }
        if (tk.type == T_W && tk.rt == FXT) XT(128 + (tk.b & 1) * 4 + tk.a, cw);
        if (tk.type == T_Q && tk.rt >= OKEEP)
          asm volatile("cp.async.bulk.tensor.3d.global.shared::cta.bulk_group [%0, {%2, %3, %4}], [%1];" :: "l"(&mos), "r"(sb + OST + cw * 24576), "r"(0), "r"(tk.rt * 128 + cw * 64), "r"(tk.a * 3) : "memory");
        else if (tk.type == T_Q) tma3d_store(&mos, sb + OST + cw * 24576, 0, tk.rt * 128 + cw * 64, tk.a * 3);
        else if (split(tk.rt) == 1) tma3d_store(&mxa, sb + OST + cw * 24576, 0, tk.rt * 128 + cw * 64, tk.a * 5);
        else if (BSL && SLC) {
          bf16* dst = g_sl + (size_t)(((slice_of(tk.rt) + tk.b) * 4 + tk.a) * 2 + cw) * 10240;
          if (SLEV) bulk_store(dst, sb + OST + cw * 24576, 20480);
          else asm volatile("cp.async.bulk.global.shared::cta.bulk_group [%0], [%1], 20480;" :: "l"(dst), "r"(sb + OST + cw * 24576) : "memory");
        }
        else if (BSL) tma3d_store(&macc, sb + OST + cw * 24576, 0, (slice_of(tk.rt) + tk.b) * 128 + cw * 64, tk.a * 5);
        else {
          const uint32_t slot = lds32(sb + DSLOT + cw * 4);
            asm volatile("cp.reduce.async.bulk.tensor.3d.global.shared::cta.add.tile.bulk_group [%0, {%2, %3, %4}], [%1];"
                         :: "l"(&macc), "r"(sb + slot * STAGE), "r"(0), "r"(layer * ACC_ROWS + (tk.rt - RT_SPLIT) * 128 + cw * 64), "r"(tk.a * 5) : "memory");
          asm volatile("cp.async.bulk.commit_group; cp.async.bulk.wait_group.read 0;" ::: "memory");
          asm volatile("mbarrier.arrive.shared::cta.b64 _, [%0], 8;" :: "r"(sb + EMPTY + slot * 8) : "memory");
        }
        asm volatile("cp.async.bulk.commit_group; cp.async.bulk.wait_group.read 0;" ::: "memory");
        mbar_arrive(sb + FREE + cw * 8);
        if (tk.type == T_Q && tk.rt == 15) XT(96 + tk.a, cw);
        asm volatile("cp.async.bulk.wait_group 0;" ::: "memory");
        if (tk.type == T_Q && tk.rt == 15) XT(96 + tk.a, 2 + cw);
        if (tk.type == T_W && tk.rt >= 13) XT((tk.rt - 13) * 32 + (tk.b >> (tk.rt == 15 && S15 == 16) & 7) * 4 + tk.a, 2 + cw);
        if (tk.type == T_W && tk.rt == FXT) XT(128 + (tk.b & 1) * 4 + tk.a, 2 + cw);
        if (tk.type == T_Q) {
          const int sl = tk.rt * 16 + (tk.a >> (5 - lsplit(tk.rt))) + (CTAIL && tk.rt == 15 ? cw * 8 : 0);
          publish_bulk<WFEN>(&sy->o[sl]);
        } else if (split(tk.rt) > 1) {
          publish_bulk<WFEN>(&sy->wcnt[(tk.rt * 4 + tk.a) * 2 + cw]);
        }
        sts32(sb + FIN + cw * 4, n + 1);
      }
    }
  } else {
    asm volatile("setmaxnreg.inc.sync.aligned.u32 232;");
    bar_sync(0, 384);
    const int cw = wg - 1, g = lane >> 2, t = lane & 3, ct = tid - 128;
    if (WLN >> layer & 1) {
      if (layer) { if (ct == 0) spin_count(&sy->pro[1], 1); bar_sync(3, 256); }
      uint2 u[2][10];
      const bf16* x = xin + (ct >> 5) * 2 * DM + lane * 4;
      int un = blockIdx.x, n = 0;
#pragma unroll
      for (int i = 0; i < 10; i++) u[1][i] = __ldcg((const uint2*)(x + un * 16 * DM + i * 128));
#pragma unroll 1
      for (; un < 128; un += gridDim.x, n++) {
#pragma unroll
        for (int i = 0; i < 10; i++) { u[0][i] = u[1][i]; u[1][i] = __ldcg((const uint2*)(x + min(un + (int)gridDim.x, 127) * 16 * DM + i * 128)); }
#pragma unroll
        for (int rr = 0; rr < 2; rr++) {
          float v[20];
#pragma unroll
          for (int i = 0; i < 5; i++) {
            const uint2 e = u[0][rr * 5 + i];
            v[4 * i] = __uint_as_float(e.x << 16); v[4 * i + 1] = __uint_as_float(e.x & 0xFFFF0000u);
            v[4 * i + 2] = __uint_as_float(e.y << 16); v[4 * i + 3] = __uint_as_float(e.y & 0xFFFF0000u);
          }
          ln_row(v, g_xn + (un * 16 + (ct >> 5) * 2 + rr) * DM, lane);
        }
        if (un < 4) {
          bar_sync(3, 256);
          if (ct == 0) red_release(&sy->pro[2]);
          __syncwarp();
        }
      }
      for (int i = blockIdx.x * 256 + ct; i < (NSEG - 1) * 24 * 32; i += gridDim.x * 256) ((uint4*)g_ar)[(i >> 5) * 64 + (i & 31)] = make_uint4(0, 0, 0, 0);
      bar_sync(3, 256);
      if (ct == 0) asm volatile("red.release.gpu.global.add.u32 [%0], %1;" :: "l"(&sy->pro[0]), "r"(n) : "memory");
      __syncwarp();
    }
    uint32_t it = 0, nd = 0;
    for (uint32_t nt = 0;; nt++) {
      mbar_wait_long(sb + TFULL + (nt & 1) * 8, (nt >> 1) & 1);
      const int tid_ = __shfl_sync(0xffffffffu, (int)lds32(sb + TASK + (nt & 1) * 4), 0);
      const Task tk = decode(tid_);
      if (nt == 0 && ct == 0) WS(2, tid_);
      __syncwarp();
      if (lane == 0) mbar_arrive(sb + TEMPTY + (nt & 1) * 8);
      if (tk.type == T_END) {
        mbar_wait_long(sb + FREE + cw * 8, (nd & 1) ^ 1);
        if (ct == cw * 128) sts32(sb + DTASK + cw * 4, tid_);
        mbar_arrive(sb + DONE + cw * 8);
        early = tid_ & 1;
        break;
      }
      if (tk.type == T_Q || tk.type == T_G) {
        if (PFACC && tk.type == T_Q && tk.rt >= RT_SPLIT && ct == 32)
          asm volatile("cp.async.bulk.prefetch.L2.global [%0], 10240;" :: "l"(g_acc + (size_t)(layer * ACC_ROWS + (tk.rt - RT_SPLIT) * 128 + tk.a * 4) * DM) : "memory");
        uint32_t q[48];
        uint4* qf = g_qf + (size_t)(tk.rt * NH + tk.a) * 12 * 256 + ct;
        if (tk.type == T_Q && tk.b) {
          if ((ct & 127) == 0) wait_count(&sy->gst[tk.rt * NH + tk.a], 2);
          bar_sync(1 + cw, 128);
#pragma unroll
          for (int i = 0; i < 12; i++) { const uint4 u = __ldcg(qf + i * 256); q[4 * i] = u.x; q[4 * i + 1] = u.y; q[4 * i + 2] = u.z; q[4 * i + 3] = u.w; }
        } else {
          float d[96];
#pragma unroll
          for (int i = 0; i < 96; i++) d[i] = 0.f;
          for (int c = 0; c < ((WF & 2) ? 2 : 10); c++, it++) {
            const uint32_t st = it % NST, a = sb + st * STAGE;
            mbar_wait_long(sb + FULL + st * 8, (it / NST) & 1);
            if (c == 0) TM(0);
            const uint64_t da = mkdesc(a + cw * 8192, 16, 1024, 1), db = mkdesc(a + 16384, 8192, 1024, 1);
            wg_fence();
#pragma unroll
            for (int k = 0; k < 4; k++) wgmma_n192_nt(d, da + k * 2, db + k * 128, c | k);
            wg_commit();
            if (c > 0) { wg_wait<1>(); if (lane == 0) mbar_arrive(sb + EMPTY + ((it - 1) % NST) * 8); }
          }
          wg_wait<0>();
          if (lane == 0) mbar_arrive(sb + EMPTY + ((it - 1) % NST) * 8);
#pragma unroll
          for (int i = 0; i < 48; i++) q[i] = pack_bf16(d[2 * i], d[2 * i + 1]);
        }
        TM(1);
        if (tk.type == T_G) {
#pragma unroll
          for (int i = 0; i < 12; i++) __stcg(qf + i * 256, make_uint4(q[4 * i], q[4 * i + 1], q[4 * i + 2], q[4 * i + 3]));
          bar_sync(1 + cw, 128);
          if ((ct & 127) == 0) red_release(&sy->gst[tk.rt * NH + tk.a]);
          __syncwarp();
          TM(2); TM(3);
          continue;
        }
        const uint32_t itk = tk.b ? it + 2 * cw : it + cw, itv = tk.b ? itk + 1 : it + 2 + cw;
        if (cw == 1) { pass_stage(sb, it, lane); if (tk.b) pass_stage(sb, it + 1, lane); }
        mbar_wait_long(sb + FULL + (itk % NST) * 8, (itk / NST) & 1);
        TM(2);
        const uint32_t mid = tk.b ? 0xFFFFFFFFu : itk + 1;
        if (w & 1) attend<5>(sb, q, cw, w, lane, itk, itv, mid, nd); else attend<3>(sb, q, cw, w, lane, itk, itv, mid, nd);
        if (!CTAIL && cw == 0) { if (tk.b) pass_stage(sb, it + 2, lane); pass_stage(sb, it + 3, lane); }
        if (ct == cw * 128) sts32(sb + DTASK + cw * 4, tid_);
        fence_async();
        mbar_arrive(sb + DONE + cw * 8);
        if (CTAIL && cw == 0) { if (tk.b) pass_stage(sb, it + 2, lane); pass_stage(sb, it + 3, lane); }
        it += 4;
        nd++;
        TM(3);
      } else if (tk.type == T_W) {
        float d[80];
#pragma unroll
        for (int i = 0; i < 80; i++) d[i] = 0.f;
        const int nc = (WF & 1) ? 2 : 96 >> lsplit(tk.rt);
        const int off = (tk.rt * 128 + cw * 64 + w * 16 + g) * DM + tk.a * 160 + 2 * t;
        const bool whole = BSL || split(tk.rt) == 1;
        uint32_t res[40];
#pragma unroll
        for (int i = 0; i < 40; i++) res[i] = split(tk.rt) == 1 ? *(const uint32_t*)(xin + off + (i >> 1) * 8 + (i & 1) * 8 * DM) : 0u;
        for (int c = 0; c < nc; c++, it++) {
          const uint32_t st = it % NST, a = sb + st * STAGE;
          mbar_wait_long(sb + FULL + st * 8, (it / NST) & 1);
          if (c == 0) TM(0);
          const uint64_t da = mkdesc(a + cw * 8192, 16, 1024, 1), db = mkdesc(a + 16384, 4096, 512, 2);
          wg_fence();
#pragma unroll
          for (int k = 0; k < 4; k++) wgmma_n160_nt(d, da + k * 2, db + k * 64, c | k);
          wg_commit();
          if (c > 0) { wg_wait<1>(); if (lane == 0 && (whole || c < nc - 1)) mbar_arrive(sb + EMPTY + ((it - 1) % NST) * 8); }
        }
        wg_wait<0>();
        if (lane == 0 && whole) mbar_arrive(sb + EMPTY + ((it - 1) % NST) * 8);
        TM(1);
        mbar_wait_long(sb + FREE + cw * 8, (nd & 1) ^ 1);
        TM(2);
        if (whole) {
          const uint32_t orow = w * 16 + (lane & 15), ob = sb + OST + cw * 24576 + orow * 64;
          float s1[2] = {0.f, 0.f}, s2[2] = {0.f, 0.f};
#pragma unroll
          for (int i2 = 0; i2 < 10; i2++) {
            uint32_t u[4];
#pragma unroll
            for (int e = 0; e < 4; e++) {
              const int i = 2 * i2 + (e >> 1);
              const uint32_t x = res[4 * i2 + e];
              u[e] = pack_bf16(d[4 * i + (e & 1) * 2] + __uint_as_float(x << 16), d[4 * i + (e & 1) * 2 + 1] + __uint_as_float(x & 0xFFFF0000u));
              const float lo = __uint_as_float(u[e] << 16), hi = __uint_as_float(u[e] & 0xFFFF0000u);
              s1[e & 1] += lo + hi; s2[e & 1] = fmaf(lo, lo, fmaf(hi, hi, s2[e & 1]));
            }
            stsm4(ob + (i2 >> 1) * 4096 + ((((i2 & 1) * 2 + (lane >> 4)) ^ ((orow >> 1) & 3)) << 4), u[0], u[1], u[2], u[3]);
          }
          fence_async();
          if (split(tk.rt) == 1)
#pragma unroll
          for (int e = 0; e < 2; e++) {
            s1[e] += __shfl_xor_sync(0xffffffffu, s1[e], 1); s2[e] += __shfl_xor_sync(0xffffffffu, s2[e], 1);
            s1[e] += __shfl_xor_sync(0xffffffffu, s1[e], 2); s2[e] += __shfl_xor_sync(0xffffffffu, s2[e], 2);
            if (t == 0) red_add2(&sy->rstat[tk.rt * 128 + cw * 64 + w * 16 + g + 8 * e], s1[e], s2[e]);
          }
        } else {
          bar_sync(3, 256);
          const uint32_t slot = (it - 2 + cw) % NST, a = sb + slot * STAGE + (w * 16 + g) * 128 + (t & 1) * 8;
#pragma unroll
          for (int i = 0; i < 20; i++) {
            const uint32_t o = a + (i >> 2) * 8192 + ((((i & 3) * 2 + (t >> 1)) ^ g) << 4);
            sts64(o, __float_as_uint(d[4 * i]), __float_as_uint(d[4 * i + 1])); sts64(o + 1024, __float_as_uint(d[4 * i + 2]), __float_as_uint(d[4 * i + 3]));
          }
          if (ct == cw * 128) sts32(sb + DSLOT + cw * 4, slot);
          fence_async();
        }
        if (ct == cw * 128) sts32(sb + DTASK + cw * 4, tid_);
        mbar_arrive(sb + DONE + cw * 8);
        nd++;
        TM(3);
      } else if (BSL && tk.type == T_F) {
        if (tk.rt == BKVZ && tk.b < 2) for (int i = ct; i < NH * BF * 6 / 8; i += 256) ((uint4*)g_bkv)[(tk.a * 2 + tk.b) * (NH * BF * 6 / 8) + i] = make_uint4(0, 0, 0, 0);
        if (PFF && tk.rt == PFF && tk.b < 2 && ct == 32) {
          const int q = tk.a * 2 + tk.b;
          for (int i = 0; i < 20; i++) asm volatile("cp.async.bulk.prefetch.L2.global [%0], 15360;" :: "l"((const char*)g_wb1 + (q * 20 + i) * 15360) : "memory");
          for (int i = 0; i < 8; i++) asm volatile("cp.async.bulk.prefetch.L2.global [%0], 12800;" :: "l"((const char*)g_wb2 + (q * 8 + i) * 12800) : "memory");
          asm volatile("cp.async.bulk.prefetch.L2.global [%0], 9600;" :: "l"((const char*)g_cs + q * 9600) : "memory");
        }
        constexpr int LPR = 256 / FROWS, NU = (20 + LPR - 1) / LPR;
        const int cq = opq(ct), rl = tk.b * FROWS + cq / LPR, q = cq % LPR, r = tk.rt * 128 + rl, c0 = tk.a * 160 + q * 8;
        if (ct == 0) { wait_count_t(&sy->wcnt[(tk.rt * 4 + tk.a) * 2 + tk.b * FROWS / 64], split(tk.rt), TIGHT == 1 && tk.rt >= 13); if (!FCGO) mbar_arrive(sb + CGO); }
        if (ct == 0 && tk.rt == FXT) XT(136 + tk.a * 4 + tk.b, 1);
        uint4 x[NU];
#pragma unroll
        for (int i = 0; i < NU; i++) x[i] = ldcg_if(xin + r * DM + c0 + i * LPR * 8, i * LPR + q < 20);
        bar_sync(3, 256);
        float a[NU][8];
#pragma unroll
        for (int i = 0; i < NU; i++) {
          a[i][0] = __uint_as_float(x[i].x << 16); a[i][1] = __uint_as_float(x[i].x & 0xFFFF0000u); a[i][2] = __uint_as_float(x[i].y << 16); a[i][3] = __uint_as_float(x[i].y & 0xFFFF0000u);
          a[i][4] = __uint_as_float(x[i].z << 16); a[i][5] = __uint_as_float(x[i].z & 0xFFFF0000u); a[i][6] = __uint_as_float(x[i].w << 16); a[i][7] = __uint_as_float(x[i].w & 0xFFFF0000u);
        }
        float y[NU][8];
#pragma unroll
        for (int i = 0; i < NU * 8; i++) y[i >> 3][i & 7] = 0.f;
        const bf16* sl = SLC ? g_sl + (size_t)((slice_of(tk.rt) * 4 + tk.a) * 2 + (rl >> 6)) * 10240 + (q >> 2) * 2048 + (rl & 63) * 32 + (((q & 3) ^ (rl >> 1 & 3)) << 3)
                             : g_sl + (size_t)(slice_of(tk.rt) * 128 + rl) * DM + c0;
        constexpr int US = SLC ? LPR / 4 * 2048 : LPR * 8;
        constexpr int SB = FROWS == 64 ? 4 : 8;
        for (int b0 = 0; b0 < split(tk.rt); b0 += SB) {
          uint4 u[SB][NU];
#pragma unroll
          for (int b = 0; b < SB; b++)
#pragma unroll
            for (int i = 0; i < NU; i++)
              if (FVOL) u[b][i] = ldcg_if(sl + (size_t)(b0 + b) * 128 * DM + i * US, b0 + b < split(tk.rt) && i * LPR + q < 20);
              else u[b][i] = b0 + b < split(tk.rt) && i * LPR + q < 20 ? __ldcg((const uint4*)(sl + (size_t)(b0 + b) * 128 * DM + i * US)) : make_uint4(0, 0, 0, 0);
          if (FVOL) sched_fence(layer >> 4);
#pragma unroll
          for (int b = 0; b < SB; b++)
#pragma unroll
            for (int i = 0; i < NU; i++) {
              y[i][0] += __uint_as_float(u[b][i].x << 16); y[i][1] += __uint_as_float(u[b][i].x & 0xFFFF0000u); y[i][2] += __uint_as_float(u[b][i].y << 16); y[i][3] += __uint_as_float(u[b][i].y & 0xFFFF0000u);
              y[i][4] += __uint_as_float(u[b][i].z << 16); y[i][5] += __uint_as_float(u[b][i].z & 0xFFFF0000u); y[i][6] += __uint_as_float(u[b][i].w << 16); y[i][7] += __uint_as_float(u[b][i].w & 0xFFFF0000u);
            }
        }
        if (FCGO && ct == 0) { loaded(__float_as_uint(y[0][0])); mbar_arrive(sb + CGO); }
        float s1 = 0.f, s2 = 0.f;
#pragma unroll
        for (int i = 0; i < NU; i++) {
          uint32_t z[4];
#pragma unroll
          for (int e = 0; e < 4; e++) {
            z[e] = pack_bf16(a[i][2 * e] + y[i][2 * e], a[i][2 * e + 1] + y[i][2 * e + 1]);
            const float lo = __uint_as_float(z[e] << 16), hi = __uint_as_float(z[e] & 0xFFFF0000u);
            s1 += lo + hi; s2 = fmaf(lo, lo, fmaf(hi, hi, s2));
          }
          asm volatile("{.reg .pred p; setp.ne.u32 p, %5, 0; @p st.global.v4.u32 [%0], {%1,%2,%3,%4};}"
                       :: "l"(g_xa + r * DM + c0 + i * LPR * 8), "r"(z[0]), "r"(z[1]), "r"(z[2]), "r"(z[3]), "r"((uint32_t)(i * LPR + q < 20)) : "memory");
        }
#pragma unroll
        for (int o = 1; o < LPR; o <<= 1) { s1 += __shfl_xor_sync(0xffffffffu, s1, o); s2 += __shfl_xor_sync(0xffffffffu, s2, o); }
        asm volatile("{.reg .pred p; setp.ne.u32 p, %3, 0; @p red.relaxed.gpu.global.add.v2.f32 [%0], {%1,%2};}"
                     :: "l"(&sy->rstat[r]), "f"(s1), "f"(s2), "r"((uint32_t)(q == 0)) : "memory");
        if (ct == 0 && tk.rt == FXT) XT(136 + tk.a * 4 + tk.b, 2);
        TM(0); TM(1); TM(2); TM(3);
      } else if (tk.type == T_F) {
        if (tk.rt == BKVZ) for (int i = ct; i < NH * BF * 6 / 8; i += 256) ((uint4*)g_bkv)[(tk.a * 2 + tk.b) * (NH * BF * 6 / 8) + i] = make_uint4(0, 0, 0, 0);
        if (PFF && tk.rt == PFF && ct == 32) {
          const int q = tk.a * 2 + tk.b;
          for (int i = 0; i < 20; i++) asm volatile("cp.async.bulk.prefetch.L2.global [%0], 15360;" :: "l"((const char*)g_wb1 + (q * 20 + i) * 15360) : "memory");
          for (int i = 0; i < 8; i++) asm volatile("cp.async.bulk.prefetch.L2.global [%0], 12800;" :: "l"((const char*)g_wb2 + (q * 8 + i) * 12800) : "memory");
          asm volatile("cp.async.bulk.prefetch.L2.global [%0], 9600;" :: "l"((const char*)g_cs + q * 9600) : "memory");
        }
        if (ct == 0) { wait_count(&sy->wcnt[(tk.rt * 4 + tk.a) * 2 + tk.b], split(tk.rt)); mbar_arrive(sb + CGO); }
        const int r = tk.rt * 128 + tk.b * 64 + (ct >> 2), c0 = tk.a * 160 + (ct & 3) * 4;
        uint2 x[10];
#pragma unroll
        for (int i = 0; i < 10; i++) x[i] = __ldg((const uint2*)(xin + r * DM + c0 + i * 16));
        bar_sync(3, 256);
        float4 a[10];
#pragma unroll
        for (int i = 0; i < 10; i++) a[i] = __ldcg((const float4*)(g_acc + (layer * ACC_ROWS + r - RT_SPLIT * 128) * DM + c0 + i * 16));
        float s1 = 0.f, s2 = 0.f;
#pragma unroll
        for (int i = 0; i < 10; i++) {
          const uint2 z = make_uint2(pack_bf16(a[i].x + __uint_as_float(x[i].x << 16), a[i].y + __uint_as_float(x[i].x & 0xFFFF0000u)),
                                     pack_bf16(a[i].z + __uint_as_float(x[i].y << 16), a[i].w + __uint_as_float(x[i].y & 0xFFFF0000u)));
          *(uint2*)(g_xa + r * DM + c0 + i * 16) = z;
          const float v0 = __uint_as_float(z.x << 16), v1 = __uint_as_float(z.x & 0xFFFF0000u), v2 = __uint_as_float(z.y << 16), v3 = __uint_as_float(z.y & 0xFFFF0000u);
          s1 += (v0 + v1) + (v2 + v3); s2 = fmaf(v0, v0, fmaf(v1, v1, fmaf(v2, v2, fmaf(v3, v3, s2))));
        }
        s1 += __shfl_xor_sync(0xffffffffu, s1, 1); s2 += __shfl_xor_sync(0xffffffffu, s2, 1);
        s1 += __shfl_xor_sync(0xffffffffu, s1, 2); s2 += __shfl_xor_sync(0xffffffffu, s2, 2);
        if ((ct & 3) == 0) red_add2(&sy->rstat[r], s1, s2);
        TM(0); TM(1); TM(2); TM(3);
      } else if (tk.a < NZ) {
        if (!BSL) for (int i = ct; i < ACC_ROWS * DM / 4 / NZ; i += 256) ((uint4*)(g_acc + layer * ACC_ROWS * DM))[tk.a * (ACC_ROWS * DM / 4 / NZ) + i] = make_uint4(0, 0, 0, 0);
        if (layer == 1) {
          if (ct == 0) wait_count(&sy->pro[0], NPRO);
          bar_sync(3, 256);
        }
        for (int i = tk.a * 256 + ct; i < (int)(sizeof(Sync) / 16); i += NZ * 256) ((uint4*)&g_sync[layer ^ 1])[i] = make_uint4(0, 0, 0, 0);
        bar_sync(3, 256);
        if (ct == 0) red_release(&sy->zeroed);
        __syncwarp();
      } else if (tk.a >= NZ + 80) {
        const int c = tk.a - NZ - 80, cq = opq(ct);
        uint4 u[20];
#pragma unroll
        for (int i = 0; i < 20; i++) u[i] = __ldg((const uint4*)(wo2 + c * 64 * DM) + i * 256 + cq);
#pragma unroll
        for (int i = 0; i < 20; i++) {
          const int p = i * 256 + cq, kr = p / 80, n8 = p % 80, gq = n8 / 10;
          g_wb2[(gq * 10 + c) * 640 + (n8 % 10 >> 1) * 128 + kr * 2 + ((n8 & 1) ^ (kr >> 2 & 1))] = u[i];
        }
      } else if (P1M) {
        const int gq = (tk.a - NZ) / 10, k0 = (tk.a - NZ) % 10 * 64;
        const uint32_t ln = opq(lane), gg = ln >> 2, tt = ln & 3, wi = opq(ct >> 5);
        const uint32_t T = sb + OST, stg = sb + (it % NST) * STAGE;
        mbar_wait_long(sb + FULL + (it % NST) * 8, (it / NST) & 1);
        uint32_t a0[4], a1[4], a0k[2], a1k;
        {
          const uint32_t pa = stg + 30720 + w * 800 + tt * 80 + gg * 2;
          auto pr = [&](int d, int f) { uint32_t lo, hi;
            asm volatile("ld.shared.u16 %0, [%1];" : "=r"(lo) : "r"(pa + d * 40 + f * 2) : "memory");
            asm volatile("ld.shared.u16 %0, [%1];" : "=r"(hi) : "r"(pa + d * 40 + 40 + f * 2) : "memory");
            return lo | hi << 16; };
          a0[0] = pr(0, 0); a0[1] = pr(0, 8); a0[2] = pr(8, 0); a0[3] = pr(8, 8);
          const int d2 = tt < 2 ? 16 : 0, f2 = gg < 4 ? 16 : 0;
          a0k[0] = pr(d2, 0); a0k[1] = pr(d2, 8);
          a1[0] = pr(0, f2); a1[2] = pr(8, f2); a1k = pr(d2, f2);
          a1[1] = a1[3] = 0;
          if (tt >= 2) a0k[0] = a0k[1] = a1k = 0;
          if (gg >= 4) a1[0] = a1[2] = a1k = 0;
        }
        float c[8][2][4];
        const uint32_t pb = stg + cw * 10240 + gg * 160 + w * 40 + tt * 4;
#pragma unroll
        for (int nt = 0; nt < 8; nt++) {
          const uint32_t b0 = lds32(pb + nt * 1280), b1 = lds32(pb + nt * 1280 + 16);
          uint32_t b2 = lds32(pb + nt * 1280 + (tt < 2 ? 32 : 0));
          if (tt >= 2) b2 = 0;
#pragma unroll
          for (int i = 0; i < 8; i++) c[nt][i >> 2][i & 3] = 0.f;
          mma16816(c[nt][0], a0, b0, b1); mma16816(c[nt][1], a1, b0, b1);
          mma1688(c[nt][0], a0k[0], a0k[1], b2); mma1688(c[nt][1], a1k, 0u, b2);
        }
        uint32_t v[3][4];
        const uint32_t pv = stg + 20480 + (wi * 8 + (ln & 7)) * 160 + (ln >> 3) * 16;
        ldsm4t(v[0], pv); ldsm4t(v[1], pv + 64); ldsm4t(v[2], pv + (ln >> 4 ? 96 : 128));
        mbar_wait_long(sb + FREE + cw * 8, (nd & 1) ^ 1);
        loaded(v[2][3]);
        bar_sync(3, 256);
        if (lane == 0) mbar_arrive(sb + EMPTY + (it % NST) * 8);
        it++;
        {
          const uint32_t n0 = cw * 80 + w * 2 + (gg >> 1) * 8 + (gg & 1);
#pragma unroll
          for (int q = 0; q < 3; q++) {
            const uint32_t n = n0 + q * 32, ro = T + n * 128 + tt * 4, sw = (n >> 3 & 3) * 2 + (n & 1);
            if (q < 2 || gg < 4)
#pragma unroll
              for (int nt = 0; nt < 8; nt++) sts32(ro + ((nt ^ sw) << 4), pack_bf16(c[nt][q >> 1][(q & 1) * 2], c[nt][q >> 1][(q & 1) * 2 + 1]));
          }
#pragma unroll
          for (int i = 0; i < 10; i++) sts32(T + (160 + i * 8 + gg) * 128 + ((wi ^ gg) << 4) + tt * 4, v[i >> 2][i & 3]);
        }
        bar_sync(3, 256);
        const int cq = opq(ct);
        for (int i = cq; i < 240 * 8; i += 256) {
          const uint32_t n = i >> 3, sw = n < 160 ? (n >> 3 & 3) * 2 + (n & 1) : n & 7;
          uint32_t u[4]; lds128(u, T + n * 128 + (((i & 7) ^ sw) << 4));
          *(uint4*)(g_wb1 + (gq * 240 + n) * DM + k0 + (i & 7) * 8) = make_uint4(u[0], u[1], u[2], u[3]);
        }
        if (cq < 240) {
          float cs = 0.f;
#pragma unroll
          for (int i = 0; i < 8; i++) {
            uint32_t u[4]; lds128(u, T + cq * 128 + (((i + cq) & 7) << 4));
#pragma unroll
            for (int e = 0; e < 4; e++) cs += __uint_as_float(u[e] << 16) + __uint_as_float(u[e] & 0xFFFF0000u);
          }
          g_cs[(k0 >> 6) * 3 * DM + gq * 240 + cq] = cs;
        }
        bar_sync(3, 256);
      } else {
        const int gq = (tk.a - NZ) / 10, k0 = (tk.a - NZ) % 10 * 64, r = ct & 63, hh = ct >> 6;
        bf16* T = (bf16*)(smraw + OST);
        float* ph = (float*)(smraw + OST + 30720);
        const uint32_t stg = sb + (it % NST) * STAGE;
        mbar_wait_long(sb + FULL + (it % NST) * 8, (it / NST) & 1);
        uint2 u[3][5];
#pragma unroll
        for (int i = 0; i < 15; i++) { const float2 v = lds64f(stg + (i / 5) * 10240 + r * 160 + hh * 40 + (i % 5) * 8); u[i / 5][i % 5] = make_uint2(__float_as_uint(v.x), __float_as_uint(v.y)); }
        uint32_t pv[4];
#pragma unroll
        for (int i = 0; i < 4; i++) pv[i] = lds32(stg + 30720 + min(ct + i * 256, 799) * 4);
        mbar_wait_long(sb + FREE + cw * 8, (nd & 1) ^ 1);
        loaded(u[2][4].x); loaded(pv[3]);
        bar_sync(3, 256);
        if (lane == 0) mbar_arrive(sb + EMPTY + (it % NST) * 8);
        it++;
#pragma unroll
        for (int i = 0; i < 4; i++) if (ct + i * 256 < 800) *(float2*)(ph + (ct + i * 256) * 2) = make_float2(__uint_as_float(pv[i] << 16), __uint_as_float(pv[i] & 0xFFFF0000u));
        bar_sync(3, 256);
#pragma unroll
        for (int part = 0; part < 2; part++) {
          float a[BDH];
#pragma unroll
          for (int i = 0; i < 5; i++) {
            a[4 * i] = __uint_as_float(u[part][i].x << 16); a[4 * i + 1] = __uint_as_float(u[part][i].x & 0xFFFF0000u);
            a[4 * i + 2] = __uint_as_float(u[part][i].y << 16); a[4 * i + 3] = __uint_as_float(u[part][i].y & 0xFFFF0000u);
          }
#pragma unroll 1
          for (int f4 = 0; f4 < 5; f4++) {
            float4 q = make_float4(0.f, 0.f, 0.f, 0.f);
#pragma unroll
            for (int dd = 0; dd < BDH; dd++) {
              const float4 p = *(const float4*)(ph + (hh * BDH + dd) * BDH + f4 * 4);
              q.x = fmaf(a[dd], p.x, q.x); q.y = fmaf(a[dd], p.y, q.y); q.z = fmaf(a[dd], p.z, q.z); q.w = fmaf(a[dd], p.w, q.w);
            }
            bf16* dst = T + (part * 80 + f4 * 16 + hh * 2) * 64 + r;
            dst[0] = __float2bfloat16(q.x); dst[64] = __float2bfloat16(q.y); dst[8 * 64] = __float2bfloat16(q.z); dst[9 * 64] = __float2bfloat16(q.w);
          }
        }
#pragma unroll
        for (int i = 0; i < 5; i++) {
          uint16_t* dst = (uint16_t*)T + (160 + hh * BDH + i * 4) * 64 + r;
          dst[0] = (uint16_t)u[2][i].x; dst[64] = (uint16_t)(u[2][i].x >> 16); dst[128] = (uint16_t)u[2][i].y; dst[192] = (uint16_t)(u[2][i].y >> 16);
        }
        bar_sync(3, 256);
        for (int i = ct; i < 240 * 8; i += 256) *(uint4*)(g_wb1 + (gq * 240 + (i >> 3)) * DM + k0 + (i & 7) * 8) = *(const uint4*)(T + i * 8);
        if (ct < 240) {
          float cs = 0.f;
#pragma unroll
          for (int i = 0; i < 8; i++) {
            const uint4 v = *(const uint4*)(T + ct * 64 + ((i + ct) & 7) * 8);
            const uint32_t vv[4] = {v.x, v.y, v.z, v.w};
#pragma unroll
            for (int e = 0; e < 4; e++) cs += __uint_as_float(vv[e] << 16) + __uint_as_float(vv[e] & 0xFFFF0000u);
          }
          g_cs[(k0 >> 6) * 3 * DM + gq * 240 + ct] = cs;
        }
        bar_sync(3, 256);
      }
    }
  }
  __syncwarp();
  if (CTAIL ? SENT && blockIdx.x == 0 : !__shfl_sync(0xffffffffu, early, 0)) asm volatile("griddepcontrol.wait;" ::: "memory");
}

#define KVREL 0
#define KVF 0
#define PFA_N 2
#define PFA_DELAY 500
#define PFA_LIMIT 30000
#define PFL 2
#define RESP 1
#define BTR 2
#define PFL_X 0
#define PFL_W2 4
#define PFL_C2 3
#define PFE 0
#define PFE_S 0
#define PFL_B 5
#define PFL_C 9
#define PFL_D 0
#define PFL_S 0
#define PFL_ORD 0x0312
#define PFB_KV 1
#define PFB_DELAY 2000
#define PFA_ORD 0x0312
#define PFA_SLEEP 0
#define BTPF 0
#define BHALF 0
#define LDL8 3
#define W2E 1
#define PREFETCH_A 0
namespace bk {
constexpr uint32_t STAGE = 47104, NST = 4;
constexpr uint32_t W2 = 0, A2 = 102400;
constexpr uint32_t PHI = 102400, VS = PHI + 128 * 336, KVS = PHI;
constexpr uint32_t OS = A2 + 65536;
constexpr uint32_t PHQ = NST * STAGE;
constexpr uint32_t CS = PHQ;
constexpr uint32_t MISC = PHQ + 128 * 336;
constexpr int NST2 = 7;
constexpr uint32_t FULL = MISC, EMPTY = MISC + 32, EMPTY2 = MISC + 64, BW2 = MISC + 128, BOK = MISC + 136, BKR = MISC + 144, BKV = MISC + 152, FULL2 = MISC + 160;
constexpr uint32_t SMEM = MISC + 256;
}
DEVI void feature_map(const float* d, uint32_t dst) {
#pragma unroll
  for (int r = 0; r < 2; r++) {
    const float l2e = 1.4426950408889634f;
    float mx = d[2 * r], mn = d[2 * r];
#pragma unroll
    for (int i = 1; i < 20; i++) { const float x = d[(i >> 1) * 4 + 2 * r + (i & 1)]; mx = fmaxf(mx, x); mn = fminf(mn, x); }
    mx *= l2e; mn *= l2e;
    float p[20], n[20], sp = 0.f, sn = 0.f;
#pragma unroll
    for (int i = 0; i < 20; i++) {
      const float x = d[(i >> 1) * 4 + 2 * r + (i & 1)];
      p[i] = ex2(fmaf(x, l2e, -mx)); n[i] = ex2(fmaf(x, -l2e, mn)); sp += p[i]; sn += n[i];
    }
    sp = rcp(sp); sn = rcp(sn);
#pragma unroll
    for (int i = 0; i < 5; i++)
      sts128(dst + r * 8 * 336 + i * 16, pack_bf16(p[4 * i] * sp, n[4 * i] * sn), pack_bf16(p[4 * i + 1] * sp, n[4 * i + 1] * sn),
             pack_bf16(p[4 * i + 2] * sp, n[4 * i + 2] * sn), pack_bf16(p[4 * i + 3] * sp, n[4 * i + 3] * sn));
  }
}

__global__ void __launch_bounds__(384, 1)
layerb_kernel(int layer, uint32_t nw2, Sync* sy, const bf16* __restrict__ xin, bf16* __restrict__ out, const void* wa0, const void* wa1, const void* wa2, const void* wa3,
              const __grid_constant__ CUtensorMap mx, const __grid_constant__ CUtensorMap mw1, const __grid_constant__ CUtensorMap mo,
              const __grid_constant__ CUtensorMap mos) {
  using namespace bk;
  extern __shared__ __align__(1024) uint8_t smraw[];
  const uint32_t sb = smem_u32(smraw);
  const int tid = threadIdx.x, lane = tid & 31;
  const int wg = __shfl_sync(0xffffffffu, tid >> 7, 0), w = __shfl_sync(0xffffffffu, (tid >> 5) & 3, 0);
  const int rt = CTAIL ? 15 - (blockIdx.x >> 3) : blockIdx.x >> 3, gq = blockIdx.x & 7;
  if (blockIdx.x >= 128) {
    asm volatile("griddepcontrol.launch_dependents;");
    if (BLN && tid >= 32) {
      asm volatile("griddepcontrol.wait;" ::: "memory");
      for (int i = (blockIdx.x - 128) * 352 + tid - 32; i < (NSEG - 1) * 24 * 32; i += (gridDim.x - 128) * 352) ((uint4*)g_ar)[(i >> 5) * 64 + (i & 31)] = make_uint4(0, 0, 0, 0);
    }
    if (tid == 0) {
      asm volatile("griddepcontrol.wait;" ::: "memory");
      const uint32_t t0 = clk32();
      __nanosleep(PFA_DELAY);
      const int nc = gridDim.x - 128;
      for (int i = blockIdx.x - 128; i < PFA_N * 480 && clk32() - t0 < PFA_LIMIT; i += nc) {
        const int m = PFA_ORD >> (i / 480 * 4) & 3;
        const char* p = (const char*)(m == 0 ? wa0 : m == 1 ? wa1 : m == 2 ? wa2 : wa3) + (size_t)(i % 480) * 16384;
        asm volatile("cp.async.bulk.prefetch.L2.global [%0], 16384;" :: "l"(p) : "memory");
        if (PFA_SLEEP) __nanosleep(PFA_SLEEP);
      }
    }
    return;
  }
  if (tid == 0) {
    for (int i = 0; i < NST; i++) { mbar_init(sb + FULL + i * 8, 1); mbar_init(sb + EMPTY + i * 8, 8); }
    for (int i = 0; i < NST2; i++) { mbar_init(sb + FULL2 + i * 8, 1); mbar_init(sb + EMPTY2 + i * 8, 8); }
    mbar_init(sb + BW2, 1); mbar_init(sb + BOK, 256); mbar_init(sb + BKV, 1); mbar_init(sb + BKR, 1);
    asm volatile("fence.mbarrier_init.release.cluster;" ::: "memory");
  }
  if (!LDL8) asm volatile("griddepcontrol.launch_dependents;");
  if (wg == 0) {
    asm volatile("setmaxnreg.dec.sync.aligned.u32 40;");
    bar_sync(0, 384);
    if (tid == 32 && layer == 0 && PREFETCH_A) {
      asm volatile("griddepcontrol.wait;" ::: "memory");
      __nanosleep(PFB_DELAY);
      for (int i = 0; i < 32; i++) {
        const char* p = (const char*)(PFB_KV ? (i < 16 ? wa2 : wa1) : (i < 16 ? wa3 : wa0)) + (size_t)blockIdx.x * 61440 + (i & 15) * 3840;
        asm volatile("cp.async.bulk.prefetch.L2.global [%0], 3840;" :: "l"(p) : "memory");
        __nanosleep(PREFETCH_A);
      }
    }
    if (PFL && w == 1 && !layer) {
      for (int c = PFL_C % NST; c <= PFL_C; c += NST) mbar_wait_long(sb + FULL + PFL_C % NST * 8, c / NST & 1);
      if (PFL_D) __nanosleep(PFL_D);
      uint32_t acc = 0;
#pragma unroll 1
      for (int i = 0; i < PFL * 15 / PFL_B - PFL_X; i++) {
        const int m = PFL_ORD >> (i / (15 / PFL_B) * 4) & 3;
        if (PFL_W2 && i == PFL_W2) mbar_wait_long(sb + FULL2 + PFL_C2 * 8, 0);
        const char* p = (const char*)(m == 0 ? wa0 : m == 1 ? wa1 : m == 2 ? wa2 : wa3) + (blockIdx.x * 15 + i % (15 / PFL_B) * PFL_B) * 4096 + lane * 128;
        uint32_t v[PFL_B];
#pragma unroll
        for (int n = 0; n < PFL_B; n++) asm volatile("ld.global.cg.L2::128B.u32 %0, [%1];" : "=r"(v[n]) : "l"(p + n * 4096) : "memory");
#pragma unroll
        for (int n = 0; n < PFL_B; n++) acc |= v[n];
        if (PFL_S) __nanosleep(PFL_S);
        loaded(acc);
      }
    }
    if (PFE && tid == 96 && !layer && blockIdx.x < 32) {
#pragma unroll 1
      for (int i = 0; i < PFE * 15; i++) {
        const int m = PFL_ORD >> (i / 15 * 4) & 3;
        const char* p = (const char*)(m == 0 ? wa0 : m == 1 ? wa1 : m == 2 ? wa2 : wa3) + (blockIdx.x * 15 + i % 15) * 16384;
        asm volatile("cp.async.bulk.prefetch.L2.global [%0], 16384;" :: "l"(p) : "memory");
        if (PFE_S) __nanosleep(PFE_S);
      }
    }
    if (BLN && w == 3 && layer) {
      asm volatile("griddepcontrol.wait;" ::: "memory");
      uint4* p = (uint4*)g_bst + blockIdx.x * 64 + lane;
      p[0] = p[32] = make_uint4(0, 0, 0, 0);
    }
    if (w == 2) {
      bar_sync(4, 288);
      if (lane == 0) {
        if (KVREL) red_release(&sy->bkv_cnt[gq]);
        spin_count(&sy->bkv_cnt[gq], 16);
        mbar_arrive(sb + BKR);
      }
    }
    if (tid == 0) {
      if (BTPF) {
        asm volatile("prefetch.tensormap [%0];" :: "l"(&mx) : "memory"); asm volatile("prefetch.tensormap [%0];" :: "l"(&mw1) : "memory");
        asm volatile("prefetch.tensormap [%0];" :: "l"(&mos) : "memory"); asm volatile("prefetch.tensormap [%0];" :: "l"(&mo) : "memory");
      }
      if (BFL) { wait_count(&sy->pad1[0], nw2); asm volatile("fence.proxy.async.global;" ::: "memory"); }
      else asm volatile("griddepcontrol.wait;" ::: "memory");
      GT(2, 0);
      const int npre = BFL && rt >= tl::RT0 ? NST : 0;
      if (npre) {
#pragma unroll 1
        for (int c = 0; c < (int)NST; c++) { mbar_expect(sb + FULL + c * 8, STAGE); tma2d(sb + c * STAGE + 16384, &mw1, c * 64, gq * 240, sb + FULL + c * 8); }
        spin_count(&sy->pro[1 + rt - tl::RT0], 64);
        asm volatile("fence.proxy.async.global;" ::: "memory");
      }
#pragma unroll 1
      for (int c = 0; c < 10; c++) {
        const uint32_t st = c % NST, a = sb + st * STAGE, fb = sb + FULL + st * 8;
        if (c >= npre) {
          mbar_wait_long(sb + EMPTY + st * 8, ((c / NST) & 1) ^ 1);
          mbar_expect(fb, STAGE - (BHALF & 1) * 8192);
        }
        tma2d(a, &mx, c * 64, rt * 128, fb);
        if (c >= npre) tma2d(a + 16384, &mw1, c * 64, gq * 240, fb);
      }
      mbar_wait_long(sb + BKV, 0);
      mbar_expect(sb + BW2, 102400);
      PT(1, 0);
      for (int c = 0; c < 2; c++) bulk_load_plain(sb + W2 + c * 51200, g_wb2 + gq * 6400 + c * 3200, 51200, sb + BW2);
      mbar_wait_long(sb + BOK, 0);
      asm volatile("cp.async.bulk.tensor.2d.global.shared::cta.bulk_group [%0, {%2, %3}], [%1];" :: "l"(&mos), "r"(sb + OS), "r"(gq * 80), "r"(rt * 128) : "memory");
      asm volatile("cp.async.bulk.commit_group; cp.async.bulk.wait_group 0;" ::: "memory");
      publish_bulk<WFEN>(&sy->bo_cnt[rt]);
      spin_count(&sy->bo_cnt[rt], 8);
      fence_flag_to_bulk();
#pragma unroll 1
      for (int c = 0; c < 10; c++) {
        const uint32_t st = c < NST2 ? c : c - NST2, fb = sb + FULL2 + st * 8;
        if (c >= NST2) mbar_wait_long(sb + EMPTY2 + st * 8, 0);
        mbar_expect(fb, 16384 - (BHALF >> 1 & 1) * 8192);
        tma2d(sb + A2 + st * 16384, &mo, c * 64, rt * 128, fb);
      }
    }
  } else {
    asm volatile("setmaxnreg.inc.sync.aligned.u32 232;");
    bar_sync(0, 384);
    if (!BFL) asm volatile("griddepcontrol.wait;" ::: "memory");
    const int cw = wg - 1, g = lane >> 2, t = lane & 3, ct = tid - 128;
    const int row = cw * 64 + w * 16 + g;
    float rs[2], ms[2], cv[10];
    if (BFL) {
      mbar_wait_long(sb + FULL, 0);
#pragma unroll
      for (int e = 0; e < 2; e++) asm volatile("ld.global.cg.v2.f32 {%0,%1}, [%2];" : "=f"(ms[e]), "=f"(rs[e]) : "l"(&sy->rstat[rt * 128 + row + 8 * e]) : "memory");
#pragma unroll
      for (int i = 0; i < 10; i++) asm volatile("ld.global.cg.f32 %0, [%1];" : "=f"(cv[i]) : "l"(g_cs + i * 3 * DM + gq * 240 + min(ct, 239)) : "memory");
    } else {
      float cs = 0.f;
      if (ct < 240) {
#pragma unroll
        for (int i = 0; i < 10; i++) cs += __ldcg(g_cs + i * 3 * DM + gq * 240 + ct);
      }
      if (!CTAIL)
#pragma unroll
      for (int e = 0; e < 2; e++) {
        const float2 st = __ldcg(&sy->rstat[rt * 128 + row + 8 * e]);
        const float m = st.x * (1.0f / DM);
        rs[e] = rsqrtf(fmaxf(st.y * (1.0f / DM) - m * m, 0.f) + 1e-5f);
        ms[e] = -m * rs[e];
      }
      if (ct < 240) sts32(sb + CS + ct * 4, __float_as_uint(cs));
      bar_sync(3, 256);
      if (CTAIL) {
        mbar_wait_long(sb + FULL, 0);
#pragma unroll
        for (int e = 0; e < 2; e++) asm volatile("ld.global.cg.v2.f32 {%0,%1}, [%2];" : "=f"(ms[e]), "=f"(rs[e]) : "l"(&sy->rstat[rt * 128 + row + 8 * e]) : "memory");
      }
    }
    uint32_t res[20];
    const int off = (rt * 128 + row) * DM + gq * 80 + 2 * t;
    {
      float d[120];
#pragma unroll
      for (int i = 0; i < 120; i++) d[i] = 0.f;
      for (int c = 0; c < 10; c++) {
        const uint32_t st = c % NST, a = sb + st * STAGE;
        mbar_wait_long(sb + FULL + st * 8, (c / NST) & 1);
        if (c == 0 && ct == 0) PT(1, 15);
        const uint64_t da = mkdesc(a + cw * 8192, 16, 1024, 1), db = mkdesc(a + 16384, 16, 1024, 1);
        wg_fence();
#pragma unroll
        for (int k = 0; k < 4; k++) wgmma_n240_nn(d, da + k * 2, db + k * 2, c | k);
        wg_commit();
        if (c > 0) { wg_wait<1>(); if (lane == 0) mbar_arrive(sb + EMPTY + ((c - 1) % NST) * 8); }
        if (BFL && c == 8) {
          float cs = 0.f;
#pragma unroll
          for (int i = 0; i < 10; i++) cs += cv[i];
          if (ct < 240) sts32(sb + CS + ct * 4, __float_as_uint(cs));
        }
      }
      if (BFL) bar_sync(3, 256);
      wg_wait<0>();
      if (lane == 0) mbar_arrive(sb + EMPTY + (9 % NST) * 8);
      if (ct == 0) PT(1, 2);
      if (CTAIL)
#pragma unroll
      for (int e = 0; e < 2; e++) {
        const float m = ms[e] * (1.0f / DM);
        rs[e] = rsqrtf(fmaxf(rs[e] * (1.0f / DM) - m * m, 0.f) + 1e-5f);
        ms[e] = -m * rs[e];
      }
#pragma unroll
      for (int i = 0; i < 30; i++) {
        const float2 c = lds64f(sb + CS + (8 * i + 2 * t) * 4);
        d[4 * i] = fmaf(c.x, ms[0], d[4 * i] * rs[0]); d[4 * i + 1] = fmaf(c.y, ms[0], d[4 * i + 1] * rs[0]);
        d[4 * i + 2] = fmaf(c.x, ms[1], d[4 * i + 2] * rs[1]); d[4 * i + 3] = fmaf(c.y, ms[1], d[4 * i + 3] * rs[1]);
      }
      if (ct == 0) PT(1, 11);
      bar_sync(3, 256);
      if (W2E && ct == 0) mbar_arrive(sb + BKV);
      feature_map(&d[40], sb + PHI + row * 336 + t * 80);
      if (ct == 0) PT(1, 12);
#pragma unroll
      for (int i = 0; i < 10; i++) {
        const int c = i * 8 + 2 * t;
        const uint32_t a = sb + VS + row * 208 + (c / 20) * 48 + (c % 20) * 2;
        sts32(a, pack_bf16(d[80 + 4 * i], d[81 + 4 * i])); sts32(a + 8 * 208, pack_bf16(d[82 + 4 * i], d[83 + 4 * i]));
      }
      { const uint32_t a = sb + VS + row * 208 + t * 48 + 40; sts64(a, 0x3F80u, 0u); sts64(a + 8 * 208, 0x3F80u, 0u); }
      bar_sync(3, 256);
      if (ct == 0) PT(1, 13);
      {
        float kv[5][4];
#pragma unroll
        for (int i = 0; i < 20; i++) kv[i >> 2][i & 3] = 0.f;
        const uint32_t pa = sb + PHI + ((lane >> 4) * 8 + (lane & 7)) * 336 + w * 80 + ((lane >> 3) & 1) * 16;
        const uint32_t va = sb + VS + lane * 208 + w * 48;
#pragma unroll
        for (int k2 = 0; k2 < 4; k2++) {
          uint32_t b[3][4];
#pragma unroll
          for (int n = 0; n < 3; n++) ldsm4t(b[n], va + k2 * 32 * 208 + n * 16);
#pragma unroll
          for (int kk = 0; kk < 2; kk++) {
            uint32_t a[4], a2[4];
            ldsm4t(a, pa + (k2 * 32 + kk * 16) * 336 + cw * 32);
            ldsm4t(a2, pa + (k2 * 32 + kk * 16) * 336 + 64);
#pragma unroll
            for (int n = 0; n < 3; n++) mma16816(kv[n], a, b[n][2 * kk], b[n][2 * kk + 1]);
            if (cw == 0) { mma16816(kv[3], a2, b[0][2 * kk], b[0][2 * kk + 1]); mma16816(kv[4], a2, b[1][2 * kk], b[1][2 * kk + 1]); }
            else mma16816(kv[3], a2, b[2][2 * kk], b[2][2 * kk + 1]);
          }
        }
        float* p = g_bkv + ((gq * 4 + w) * BF + g) * 24 + 2 * t;
        PINF(kv[0][0]); PINF(kv[3][0]);
        if (ct == 0) PT(1, 14);
#pragma unroll
        for (int n = 0; n < 3; n++) {
          asm volatile("red.relaxed.gpu.global.add.v2.f32 [%0], {%1,%2};" :: "l"(p + cw * 16 * 24 + n * 8), "f"(kv[n][0]), "f"(kv[n][1]) : "memory");
          asm volatile("red.relaxed.gpu.global.add.v2.f32 [%0], {%1,%2};" :: "l"(p + (cw * 16 + 8) * 24 + n * 8), "f"(kv[n][2]), "f"(kv[n][3]) : "memory");
        }
        asm volatile("red.relaxed.gpu.global.add.v2.f32 [%0], {%1,%2};" :: "l"(p + 32 * 24 + cw * 16), "f"(kv[3][0]), "f"(kv[3][1]) : "memory");
        if (cw == 0) asm volatile("red.relaxed.gpu.global.add.v2.f32 [%0], {%1,%2};" :: "l"(p + 32 * 24 + 8), "f"(kv[4][0]), "f"(kv[4][1]) : "memory");
      }
      if (ct == 0) PT(1, 3);
      if (LDL8 == 4) asm volatile("griddepcontrol.launch_dependents;");
      if (KVF == 1) __threadfence();
      bar_sync(4, 288);
      if (!KVREL) { if (ct == 0) red_release(&sy->bkv_cnt[gq]); __syncwarp(); }
      if (ct == 0) PT(1, 9);
      if (!W2E && ct == 0) mbar_arrive(sb + BKV);
      feature_map(&d[0], sb + PHQ + row * 336 + t * 80);
    }
    if (ct == 0) PT(1, 4);
    const int tw = (rt * 128 + cw * 64 + w * 16) * DM + gq * 80, to0 = tw + (lane >> 3) * DM + (lane & 7) * 8, to4 = tw + (lane >> 1) * DM + 64 + (lane & 1) * 8;
    auto load_res = [&]() {
      if (BTR == 2) {
#pragma unroll
        for (int i = 0; i < 5; i++) ldcg128(*(uint32_t(*)[4])&res[4 * i], g_xa + (i < 4 ? to0 + i * 4 * DM : to4));
      } else {
#pragma unroll
        for (int i = 0; i < 10; i++) { res[2 * i] = __ldcg((const uint32_t*)(g_xa + off + i * 8)); res[2 * i + 1] = __ldcg((const uint32_t*)(g_xa + off + i * 8 + 8 * DM)); }
      }
    };
    if (RESP == 0) load_res();
    mbar_wait_long(sb + BKR, 0);
    if (LDL8 == 1) asm volatile("griddepcontrol.launch_dependents;");
    if (KVF == 2) __threadfence();
    if (KVF == 3) __nanosleep(1500);
    if (ct == 0) PT(1, 5);
    {
      float4 a[4];
#pragma unroll
      for (int i = 0; i < 4; i++) a[i] = __ldcg((const float4*)(g_bkv + gq * 4 * BF * 24) + min(ct + i * 256, 4 * BF * 6 - 1));
#pragma unroll
      for (int i = 0; i < 4; i++) if (ct + i * 256 < 4 * BF * 6) sts64(sb + KVS + (ct + i * 256) * 8, pack_bf16(a[i].x, a[i].y), pack_bf16(a[i].z, a[i].w));
    }
    if (RESP == 2) load_res();
    bar_sync(3, 256);
    {
      float o[4][3][4];
#pragma unroll
      for (int hh = 0; hh < 4; hh++) {
        uint32_t a0[4], a1[4], a2[2], c[4];
        const uint32_t qa = sb + PHQ + (cw * 64 + w * 16 + (lane & 15)) * 336 + hh * 80;
        ldsm4(a0, qa + (lane >> 4) * 16); ldsm4(a1, qa + 32 + (lane >> 4) * 16); ldsm2(a2, qa + 64);
        ldsm4t(c, sb + KVS + hh * 1920 + (32 + (lane & 7)) * 48 + min(lane >> 3, 2) * 16);
#pragma unroll
        for (int n = 0; n < 3; n++) {
          uint32_t b[4];
          ldsm4t(b, sb + KVS + hh * 1920 + lane * 48 + n * 16);
          o[hh][n][0] = o[hh][n][1] = o[hh][n][2] = o[hh][n][3] = 0.f;
          mma16816(o[hh][n], a0, b[0], b[1]); mma16816(o[hh][n], a1, b[2], b[3]); mma1688(o[hh][n], a2[0], a2[1], c[n]);
        }
      }
      const uint32_t oa = sb + OS + row * 160 + t * 4;
#pragma unroll
      for (int hh = 0; hh < 4; hh++) {
        const float i0 = __fdividef(1.0f, __shfl_sync(0xffffffffu, o[hh][2][0], (lane & 28) + 2) + 1e-6f);
        const float i1 = __fdividef(1.0f, __shfl_sync(0xffffffffu, o[hh][2][2], (lane & 28) + 2) + 1e-6f);
#pragma unroll
        for (int n = 0; n < 3; n++)
          if (n < 2 || t < 2) {
            sts32(oa + hh * 40 + n * 16, pack_bf16(o[hh][n][0] * i0, o[hh][n][1] * i0));
            sts32(oa + hh * 40 + n * 16 + 8 * 160, pack_bf16(o[hh][n][2] * i1, o[hh][n][3] * i1));
          }
      }
      fence_async();
    }
    if (ct == 0) PT(1, 6);
    mbar_arrive(sb + BOK);
    if (RESP == 1) load_res();
    if (LDL8 == 2) asm volatile("griddepcontrol.launch_dependents;");
    float d[40];
#pragma unroll
    for (int i = 0; i < 40; i++) d[i] = 0.f;
    mbar_wait_long(sb + BW2, 0);
    for (int c = 0; c < 10; c++) {
      const uint32_t st = c % NST2;
      mbar_wait_long(sb + FULL2 + st * 8, c / NST2);
      if (ct == 0 && c == 0) PT(1, 7);
      if (LDL8 == 3 && c == 0) asm volatile("griddepcontrol.launch_dependents;");
      const uint64_t da = mkdesc(sb + A2 + st * 16384 + cw * 8192, 16, 1024, 1), db = mkdesc(sb + W2 + c * 10240, 2048, 256, 3);
      wg_fence();
#pragma unroll
      for (int k = 0; k < 4; k++) wgmma_n80_nt(d, da + k * 2, db + k * 32, c | k);
      wg_commit();
      if (c > 0 && c <= 10 - NST2) { wg_wait<1>(); if (lane == 0) mbar_arrive(sb + EMPTY2 + (c - 1) * 8); }
    }
    wg_wait<0>();
    if (ct == 0) PT(1, 10);
    if (BTR == 2) {
      const uint32_t tb = sb + A2 + (w >> 1) * 16384 + cw * 8192 + (w & 1) * 3072;
      bar_sync(5 + cw, 128);
#pragma unroll
      for (int i = 0; i < 5; i++)
        stsm4(tb + (lane & 15) * 176 + (2 * i + (lane >> 4)) * 16, pack_bf16(d[8 * i], d[8 * i + 1]), pack_bf16(d[8 * i + 2], d[8 * i + 3]), pack_bf16(d[8 * i + 4], d[8 * i + 5]), pack_bf16(d[8 * i + 6], d[8 * i + 7]));
      __syncwarp();
      float a[5][2];
#pragma unroll
      for (int i = 0; i < 5; i++) {
        uint32_t y[4];
        lds128(y, tb + (i < 4 ? (i * 4 + (lane >> 3)) * 176 + (lane & 7) * 16 : (lane >> 1) * 176 + 128 + (lane & 1) * 16));
        a[i][0] = a[i][1] = 0.f;
#pragma unroll
        for (int e = 0; e < 4; e++) {
          const uint32_t x = res[4 * i + e];
          const uint32_t z = res[4 * i + e] = pack_bf16(__uint_as_float(y[e] << 16) + __uint_as_float(x << 16), __uint_as_float(y[e] & 0xFFFF0000u) + __uint_as_float(x & 0xFFFF0000u));
          const float lo = __uint_as_float(z << 16), hi = __uint_as_float(z & 0xFFFF0000u);
          a[i][0] += lo + hi; a[i][1] = fmaf(lo, lo, fmaf(hi, hi, a[i][1]));
        }
        if (!BLN || layer) *(uint4*)(out + (i < 4 ? to0 + i * 4 * DM : to4)) = make_uint4(res[4 * i], res[4 * i + 1], res[4 * i + 2], res[4 * i + 3]);
      }
      if (BLN && !layer) {
        float2* bst = g_bst + (rt * 128 + cw * 64 + w * 16) * 8;
        const bool b0 = lane & 1, b1 = lane & 2;
        const int r = (lane & 3) * 4 + (lane >> 3);
        float s[2];
#pragma unroll
        for (int m = 0; m < 2; m++) {
          const float u0 = (b0 ? a[1][m] : a[0][m]) + __shfl_xor_sync(0xffffffffu, b0 ? a[0][m] : a[1][m], 1);
          const float u1 = (b0 ? a[3][m] : a[2][m]) + __shfl_xor_sync(0xffffffffu, b0 ? a[2][m] : a[3][m], 1);
          const float e = a[4][m] + __shfl_xor_sync(0xffffffffu, a[4][m], 1);
          s[m] = (b1 ? u1 : u0) + __shfl_xor_sync(0xffffffffu, b1 ? u0 : u1, 2);
          s[m] += __shfl_xor_sync(0xffffffffu, s[m], 4) + __shfl_sync(0xffffffffu, e, 2 * r);
        }
        asm volatile("{.reg .pred p; .reg .b64 v; setp.eq.u32 p, %3, 0; mov.b64 v, {%1,%2}; @p st.relaxed.gpu.global.b64 [%0], v;}"
                     :: "l"(bst + r * 8 + gq), "r"(__float_as_uint(s[0])), "r"(__float_as_uint(s[1]) | 0x80000000u), "r"(lane & 4) : "memory");
#pragma unroll
        for (int i = 0; i < 5; i++) *(uint4*)(out + (i < 4 ? to0 + i * 4 * DM : to4)) = make_uint4(res[4 * i], res[4 * i + 1], res[4 * i + 2], res[4 * i + 3]);
        if (ct == 0) PT(1, 8);
        uint32_t u[2][4];
        for (int n = 0; n < 4000000; n++) {
#pragma unroll
          for (int e = 0; e < 2; e++)
            asm volatile("{.reg .b64 a, b; ld.relaxed.gpu.global.v2.b64 {a, b}, [%4]; mov.b64 {%0,%1}, a; mov.b64 {%2,%3}, b;}"
                         : "=r"(u[e][0]), "=r"(u[e][1]), "=r"(u[e][2]), "=r"(u[e][3]) : "l"(bst + lane * 4 + e * 2) : "memory");
          if (__all_sync(0xffffffffu, (int)(u[0][1] & u[0][3] & u[1][1] & u[1][3]) < 0)) break;
        }
        float s1 = __uint_as_float(u[0][0]) + __uint_as_float(u[0][2]) + (__uint_as_float(u[1][0]) + __uint_as_float(u[1][2]));
        float s2 = __uint_as_float(u[0][1]) + __uint_as_float(u[0][3]) + (__uint_as_float(u[1][1]) + __uint_as_float(u[1][3]));
        s1 += __shfl_xor_sync(0xffffffffu, s1, 1); s2 += __shfl_xor_sync(0xffffffffu, s2, 1);
        const float m = s1 * (1.0f / DM), sc = rsqrtf(fmaxf(s2 * (-1.0f / DM) - m * m, 0.f) + 1e-5f), sh = -m * sc;
#pragma unroll
        for (int i = 0; i < 5; i++) {
          const float c = i < 4 ? __shfl_sync(0xffffffffu, sc, i * 8 + (lane >> 3) * 2) : sc, h = i < 4 ? __shfl_sync(0xffffffffu, sh, i * 8 + (lane >> 3) * 2) : sh;
          uint32_t z[4];
#pragma unroll
          for (int e = 0; e < 4; e++) z[e] = pack_bf16(fmaf(__uint_as_float(res[4 * i + e] << 16), c, h), fmaf(__uint_as_float(res[4 * i + e] & 0xFFFF0000u), c, h));
          *(uint4*)(g_xn + (i < 4 ? to0 + i * 4 * DM : to4)) = make_uint4(z[0], z[1], z[2], z[3]);
        }
      } else if (ct == 0) PT(1, 8);
    } else {
#pragma unroll
    for (int i = 0; i < 20; i++) res[i] = pack_bf16(d[2 * i] + __uint_as_float(res[i] << 16), d[2 * i + 1] + __uint_as_float(res[i] & 0xFFFF0000u));
    float2* bst = g_bst + (rt * 128 + row) * 8;
    if (BLN && !layer) {
      float a[4] = {0.f, 0.f, 0.f, 0.f};
#pragma unroll
      for (int i = 0; i < 20; i++) {
        const float lo = __uint_as_float(res[i] << 16), hi = __uint_as_float(res[i] & 0xFFFF0000u);
        a[(i & 1) * 2] += lo + hi; a[(i & 1) * 2 + 1] = fmaf(lo, lo, fmaf(hi, hi, a[(i & 1) * 2 + 1]));
      }
      const bool odd = t & 1;
      float s1 = (odd ? a[2] : a[0]) + __shfl_xor_sync(0xffffffffu, odd ? a[0] : a[2], 1), s2 = (odd ? a[3] : a[1]) + __shfl_xor_sync(0xffffffffu, odd ? a[1] : a[3], 1);
      s1 += __shfl_xor_sync(0xffffffffu, s1, 2); s2 += __shfl_xor_sync(0xffffffffu, s2, 2);
      asm volatile("{.reg .pred p; .reg .b64 v; setp.lt.u32 p, %3, 2; mov.b64 v, {%1,%2}; @p st.relaxed.gpu.global.b64 [%0], v;}"
                   :: "l"(bst + (t & 1) * 64 + gq), "r"(__float_as_uint(s1)), "r"(__float_as_uint(s2) | 0x80000000u), "r"(t) : "memory");
    }
    const uint32_t tb = sb + A2 + (w >> 1) * 16384 + cw * 8192 + (w & 1) * 3072;
    int go[5];
    if (BTR) {
      bar_sync(5 + cw, 128);
#pragma unroll
      for (int i = 0; i < 5; i++) stsm4(tb + (lane & 15) * 176 + (2 * i + (lane >> 4)) * 16, res[4 * i], res[4 * i + 1], res[4 * i + 2], res[4 * i + 3]);
      __syncwarp();
#pragma unroll
      for (int i = 0; i < 5; i++) {
        const int n = i * 32 + lane, r = n * 205 >> 11;
        lds128(*(uint32_t(*)[4])&res[4 * i], tb + n * 16 + r * 16);
        go[i] = (rt * 128 + cw * 64 + w * 16) * DM + gq * 80 + n * 8 + r * (DM - 80);
      }
#pragma unroll
      for (int i = 0; i < 5; i++) *(uint4*)(out + go[i]) = make_uint4(res[4 * i], res[4 * i + 1], res[4 * i + 2], res[4 * i + 3]);
    } else {
#pragma unroll
      for (int i = 0; i < 20; i++) *(uint32_t*)(out + off + (i >> 1) * 8 + (i & 1) * 8 * DM) = res[i];
    }
    if (ct == 0) PT(1, 8);
    if (BLN && !layer) {
      uint32_t u[2][4];
      for (int n = 0; n < 4000000; n++) {
#pragma unroll
        for (int e = 0; e < 2; e++)
          asm volatile("{.reg .b64 a, b; ld.relaxed.gpu.global.v2.b64 {a, b}, [%4]; mov.b64 {%0,%1}, a; mov.b64 {%2,%3}, b;}"
                       : "=r"(u[e][0]), "=r"(u[e][1]), "=r"(u[e][2]), "=r"(u[e][3]) : "l"(bst + e * 64 + 2 * t) : "memory");
        if (__all_sync(0xffffffffu, (int)(u[0][1] & u[0][3] & u[1][1] & u[1][3]) < 0)) break;
      }
#pragma unroll
      for (int e = 0; e < 2; e++) {
        float s1 = __uint_as_float(u[e][0]) + __uint_as_float(u[e][2]), s2 = __uint_as_float(u[e][1]) + __uint_as_float(u[e][3]);
#pragma unroll
        for (int o = 1; o < 4; o <<= 1) { s1 += __shfl_xor_sync(0xffffffffu, s1, o); s2 += __shfl_xor_sync(0xffffffffu, s2, o); }
        const float m = s1 * (1.0f / DM);
        rs[e] = rsqrtf(fmaxf(s2 * (-1.0f / DM) - m * m, 0.f) + 1e-5f);
        ms[e] = -m * rs[e];
      }
      if (BTR) {
        if (t < 2) sts64(tb + 2816 + (g + 8 * t) * 8, __float_as_uint(t ? rs[1] : rs[0]), __float_as_uint(t ? ms[1] : ms[0]));
        __syncwarp();
#pragma unroll
        for (int i = 0; i < 5; i++) {
          const float2 c = lds64f(tb + 2816 + ((i * 32 + lane) * 205 >> 11) * 8);
          uint32_t z[4];
#pragma unroll
          for (int e = 0; e < 4; e++) z[e] = pack_bf16(fmaf(__uint_as_float(res[4 * i + e] << 16), c.x, c.y), fmaf(__uint_as_float(res[4 * i + e] & 0xFFFF0000u), c.x, c.y));
          *(uint4*)(g_xn + go[i]) = make_uint4(z[0], z[1], z[2], z[3]);
        }
      } else
#pragma unroll
      for (int i = 0; i < 20; i++)
        *(uint32_t*)(g_xn + off + (i >> 1) * 8 + (i & 1) * 8 * DM) = pack_bf16(fmaf(__uint_as_float(res[i] << 16), rs[i & 1], ms[i & 1]), fmaf(__uint_as_float(res[i] & 0xFFFF0000u), rs[i & 1], ms[i & 1]));
    }
    }
    if (ct == 0) GT(2, 1);
  }
}

typedef CUresult (*EncodeFn)(CUtensorMap*, CUtensorMapDataType, cuuint32_t, void*, const cuuint64_t*, const cuuint64_t*, const cuuint32_t*,
                             const cuuint32_t*, CUtensorMapInterleave, CUtensorMapSwizzle, CUtensorMapL2promotion, CUtensorMapFloatOOBfill);
static EncodeFn g_enc = nullptr;
#define P128 1
static void make_map(CUtensorMap* m, const void* p, uint64_t cols, uint64_t rows, uint32_t bc, uint32_t br, bool swz = true, bool p128 = false) {
  cuuint64_t dims[2] = {cols, rows}; cuuint64_t strides[1] = {cols * 2}; cuuint32_t box[2] = {bc, br}; cuuint32_t es[2] = {1, 1};
  g_enc(m, CU_TENSOR_MAP_DATA_TYPE_BFLOAT16, 2, (void*)p, dims, strides, box, es, CU_TENSOR_MAP_INTERLEAVE_NONE, swz ? CU_TENSOR_MAP_SWIZZLE_128B : CU_TENSOR_MAP_SWIZZLE_NONE,
        p128 ? CU_TENSOR_MAP_L2_PROMOTION_L2_128B : CU_TENSOR_MAP_L2_PROMOTION_L2_256B, CU_TENSOR_MAP_FLOAT_OOB_FILL_NONE);
}
static void make_map3(CUtensorMap* m, const void* p, uint64_t cols, uint64_t rows, uint32_t cw, uint32_t br, uint32_t bch) {
  cuuint64_t dims[3] = {cw, rows, cols / cw}; cuuint64_t strides[2] = {cols * 2, cw * 2}; cuuint32_t box[3] = {cw, br, bch}; cuuint32_t es[3] = {1, 1, 1};
  g_enc(m, CU_TENSOR_MAP_DATA_TYPE_BFLOAT16, 3, (void*)p, dims, strides, box, es, CU_TENSOR_MAP_INTERLEAVE_NONE,
        cw == 64 ? CU_TENSOR_MAP_SWIZZLE_128B : cw == 32 ? CU_TENSOR_MAP_SWIZZLE_64B : CU_TENSOR_MAP_SWIZZLE_32B, CU_TENSOR_MAP_L2_PROMOTION_L2_256B, CU_TENSOR_MAP_FLOAT_OOB_FILL_NONE);
}
template <typename T> static void* sym(T& s) { void* p = nullptr; cudaGetSymbolAddress(&p, s); return p; }
template <typename... KA, typename... A>
static void launch(void (*k)(KA...), int grid, int smem, bool pdl, A... a) {
  cudaLaunchConfig_t cfg = {};
  cfg.gridDim = dim3(grid); cfg.blockDim = dim3(384); cfg.dynamicSmemBytes = smem; cfg.stream = cudaStreamPerThread;
  cudaLaunchAttribute at[1]; at[0].id = cudaLaunchAttributeProgrammaticStreamSerialization; at[0].val.programmaticStreamSerializationAllowed = 1;
  cfg.attrs = at; cfg.numAttrs = pdl ? 1 : 0;
  cudaLaunchKernelEx(&cfg, k, a...);
}

constexpr int dev_layers = 2, dev_pdl = 1;
#define EV(i)
extern "C" void kernel_launch(void* const* d_in, const int* in_sizes, int n_in, void* d_out, int out_size) {
  static int nsm = 0;
  if (!g_enc) {
    void* fn = nullptr; cudaDriverEntryPointQueryResult st;
    cudaGetDriverEntryPoint("cuTensorMapEncodeTiled", &fn, cudaEnableDefault, &st);
    g_enc = (EncodeFn)fn;
    cudaFuncSetAttribute(chain_kernel, cudaFuncAttributeMaxDynamicSharedMemorySize, ch::SMEM);
    cudaFuncSetAttribute(worker_kernel, cudaFuncAttributeMaxDynamicSharedMemorySize, wk::SMEM);
    cudaFuncSetAttribute(layerb_kernel, cudaFuncAttributeMaxDynamicSharedMemorySize, bk::SMEM);
    cudaDeviceGetAttribute(&nsm, cudaDevAttrMultiProcessorCount, 0);
  }
  CUtensorMap mq, mk, mv, mo, mx, wx, wq, woa, wos, wwo, wxa, wacc, wwb, bx, bw1, bo, bos;
  make_map(&mq, d_in[2], HD, DM, 64, 128, true, P128); make_map(&mk, d_in[3], HD, DM, 64, 128, true, P128); make_map(&mv, d_in[4], HD, DM, 64, 128, true, P128);
  make_map(&mo, d_in[5], DM, HD, 64, 192, true, P128); make_map3(&mx, sym(g_xn), DM, S_LEN, 64, 32, 5);
  make_map(&wx, sym(g_xn), DM, S_LEN, 64, 128); make_map3(&wq, d_in[2], HD, DM, 64, 64, 3);
  make_map(&woa, sym(g_o), HD, S_LEN, 64, 128); make_map3(&wos, sym(g_o), HD, S_LEN, 64, 64, 3); make_map3(&wwo, d_in[5], DM, HD, 32, 64, 5);
  CUtensorMap toa;
  make_map(&toa, sym(g_o), HD, S_LEN, 64, 64);
  make_map3(&wxa, sym(g_xa), DM, S_LEN, 32, 64, 5);
  if (BSL) make_map3(&wacc, sym(g_sl), DM, NSL * 128, 32, 64, 5);
  else {
    cuuint64_t dims[3] = {32, 2 * ACC_ROWS, DM / 32}, strides[2] = {DM * 4, 128}; cuuint32_t box[3] = {32, 64, 5}, es[3] = {1, 1, 1};
    g_enc(&wacc, CU_TENSOR_MAP_DATA_TYPE_FLOAT32, 3, sym(g_acc), dims, strides, box, es, CU_TENSOR_MAP_INTERLEAVE_NONE, CU_TENSOR_MAP_SWIZZLE_128B,
          CU_TENSOR_MAP_L2_PROMOTION_NONE, CU_TENSOR_MAP_FLOAT_OOB_FILL_NONE);
  }
  make_map(&wwb, d_in[8], 3 * DM, DM, 80, 64, false);
  make_map(&bx, sym(g_xa), DM, S_LEN, 64, (BHALF & 1) ? 64 : 128); make_map(&bw1, sym(g_wb1), DM, 3 * DM, 64, 240);
  make_map(&bo, sym(g_bo), DM, S_LEN, 64, (BHALF & 2) ? 64 : 128); make_map(&bos, sym(g_bo), DM, S_LEN, 80, 128, false);
  cudaStream_t st = cudaStreamPerThread;
  for (int layer = 0; layer < dev_layers; layer++) {
    const bf16* x = layer == 0 ? (const bf16*)d_in[0] : (const bf16*)sym(g_xb);
    Sync* sy = (Sync*)sym(g_sync) + layer;
    EV(layer * 5);
    EV(layer * 5 + 1);
    launch(chain_kernel, 96, ch::SMEM, dev_pdl && layer, mq, mk, mv, mo, mx, (const bf16*)d_in[1], x, 0u, layer, toa, wwo);
    EV(layer * 5 + 2);
    launch(worker_kernel, WGRID ? WGRID : CTAIL ? nsm - 96 : nsm, wk::SMEM, dev_pdl, layer, sy, x, (const bf16*)d_in[9], (const bf16*)d_in[10], wx, wq, woa, wos, wwo, wxa, wacc, wwb);
    EV(layer * 5 + 3);
    launch(layerb_kernel, layer ? 128 : BLN ? 132 : PFA_N ? max(128, min(nsm, 132)) : 128, bk::SMEM, dev_pdl, layer, 2u * (nsm - 96), sy, x, layer == 0 ? (bf16*)sym(g_xb) : (bf16*)d_out,
           (const void*)d_in[2], (const void*)d_in[3], (const void*)d_in[4], (const void*)d_in[5], bx, bw1, bo, bos);
    EV(layer * 5 + 4);
  }
}
```

```cpp
#include <cuda_runtime.h>
#include <cuda_bf16.h>
#include <cuda_fp16.h>
#include <cuda.h>
#include <stdint.h>

typedef __nv_bfloat16 bf16;

constexpr int S_LEN = 2048, DM = 640, NH = 32, DH = 192, NMEM = 8, SEG = 32, NSEG = 64;
constexpr int HD = NH * DH;
constexpr int NKEY = NMEM + SEG;
constexpr int SLAB = 64 * NKEY * 2;
constexpr int AR_STEP_BYTES = 24 * 1024;
constexpr int BDH = 20, BF = 40;

__device__ __align__(1024) bf16 g_xn[S_LEN * DM];
__device__ __align__(1024) bf16 g_kv[(size_t)NSEG * NH * 2 * DH * NKEY];
__device__ __align__(1024) bf16 g_o[(size_t)S_LEN * HD];
__device__ __align__(1024) bf16 g_xa[S_LEN * DM];
__device__ __align__(1024) bf16 g_xb[S_LEN * DM];
__device__ __align__(32768) uint32_t g_ar[NSEG * AR_STEP_BYTES / 4];
#define RTS 10
constexpr int RT_SPLIT = RTS;
constexpr int ACC_ROWS = (16 - RT_SPLIT) * 128;
#define BSL 1
#define FROWS 32
__device__ __align__(1024) float g_acc[BSL ? 256 : 2 * ACC_ROWS * DM];
#define BFL 0
#define CTAIL 1
constexpr int NSL = 48;
__device__ __align__(1024) bf16 g_sl[BSL ? NSL * 128 * DM : 512];
__device__ __align__(1024) float g_cs[10 * 3 * DM];
__device__ __align__(1024) bf16 g_wb1[3 * DM * DM];
__device__ __align__(1024) uint4 g_wb2[DM * DM / 8];
__device__ __align__(1024) bf16 g_bo[S_LEN * DM];
__device__ __align__(1024) uint4 g_qf[16 * NH * 12 * 256];
struct __align__(1024) Sync {
  uint32_t kv[NSEG * NH];
  uint32_t o[16 * 16];
  uint32_t bkv_cnt[8], bo_cnt[16];
  uint32_t pro[4];
  uint32_t wmax[96];
  uint32_t pad1[4];
  uint32_t head, pad0[31];
  uint32_t zeroed, pad[31];
  uint32_t gst[16 * NH];
  uint32_t wcnt[16 * 8];
  float2 rstat[S_LEN];
};
__device__ __align__(1024) Sync g_sync[2];
#define BLN 0
#define WREL 0
#define WLN 2
static_assert(!(BLN && WLN), "layer norm");
#define NPRO ((WLN >> layer & 1) ? 128 : 96)
__device__ __align__(1024) float2 g_bst[BLN ? 2048 * 8 : 2];
__device__ uint32_t g_kw;
__device__ __align__(1024) float g_bkv[NH * BF * 24];

#define GT(k, e)
#define WS(e_, v_)
#undef TLOG
#undef TM
#undef PT
#undef XT
#define XT(i, e)
#define TLOG(id, ta)
#define TM(i)
#define PT(k, e)
#define DEVI __device__ __forceinline__
constexpr int SPIN_LIMIT = 20000;
DEVI uint32_t smem_u32(const void* p) { return (uint32_t)__cvta_generic_to_shared(p); }
DEVI uint32_t clk32() { uint64_t c; asm volatile("mov.u64 %0, %%clock64;" : "=l"(c)); return (uint32_t)c; }
DEVI uint32_t mapa(uint32_t a, uint32_t r) { uint32_t o; asm("mapa.shared::cluster.u32 %0, %1, %2;" : "=r"(o) : "r"(a), "r"(r)); return o; }
DEVI void mbar_init(uint32_t bar, uint32_t cnt) { asm volatile("mbarrier.init.shared::cta.b64 [%0], %1;" :: "r"(bar), "r"(cnt) : "memory"); }
DEVI void mbar_expect(uint32_t bar, uint32_t bytes) { asm volatile("mbarrier.arrive.expect_tx.shared::cta.b64 _, [%0], %1;" :: "r"(bar), "r"(bytes) : "memory"); }
DEVI void mbar_arrive(uint32_t bar) { asm volatile("mbarrier.arrive.shared::cta.b64 _, [%0];" :: "r"(bar) : "memory"); }
DEVI void mbar_arrive_cluster(uint32_t rbar) { asm volatile("mbarrier.arrive.relaxed.cluster.shared::cluster.b64 _, [%0];" :: "r"(rbar) : "memory"); }
DEVI bool mbar_try(uint32_t bar, uint32_t par) {
  uint32_t ok;
  asm volatile("{.reg .pred p; mbarrier.try_wait.parity.shared::cta.b64 p, [%1], %2; selp.u32 %0, 1, 0, p;}" : "=r"(ok) : "r"(bar), "r"(par) : "memory");
  return ok;
}
DEVI void mbar_wait(uint32_t bar, uint32_t par) {
  int n = 0;
  while (!mbar_try(bar, par) && ++n < SPIN_LIMIT) {}
}
DEVI void bar_sync(int id, int n) { asm volatile("bar.sync %0, %1;" :: "r"(id), "r"(n) : "memory"); }
DEVI void bar_arrive(int id, int n) { asm volatile("bar.arrive %0, %1;" :: "r"(id), "r"(n) : "memory"); }
DEVI void fence_async() { asm volatile("fence.proxy.async.shared::cta;" ::: "memory"); }
#define RFEN 2
#define CEND 1
#define XFEN 1
#define WFEN 2
template <int M> DEVI void publish_bulk(uint32_t* flag) {
  if (M == 1) asm volatile("fence.proxy.async;" ::: "memory");
  if (M == 2) asm volatile("red.release.gpu.global.add.u32 [%0], 1;" :: "l"(flag) : "memory");
  else asm volatile("red.relaxed.gpu.global.add.u32 [%0], 1;" :: "l"(flag) : "memory");
}
DEVI void fence_flag_to_bulk() {
  if (RFEN == 0) asm volatile("fence.proxy.async;" ::: "memory");
  if (RFEN == 1) asm volatile("fence.proxy.async.global;" ::: "memory");
}
DEVI void cluster_sync_full() { asm volatile("barrier.cluster.arrive.release.aligned; barrier.cluster.wait.acquire.aligned;" ::: "memory"); }
DEVI void tma2d(uint32_t dst, const CUtensorMap* m, int c0, int c1, uint32_t bar) {
  asm volatile("cp.async.bulk.tensor.2d.shared::cluster.global.mbarrier::complete_tx::bytes [%0], [%1, {%3, %4}], [%2];"
               :: "r"(dst), "l"(m), "r"(bar), "r"(c0), "r"(c1) : "memory");
}
DEVI void tma3d(uint32_t dst, const CUtensorMap* m, int c0, int c1, int c2, uint32_t bar) {
  asm volatile("cp.async.bulk.tensor.3d.shared::cluster.global.mbarrier::complete_tx::bytes [%0], [%1, {%3, %4, %5}], [%2];"
               :: "r"(dst), "l"(m), "r"(bar), "r"(c0), "r"(c1), "r"(c2) : "memory");
}
DEVI void tma3d_mc(uint32_t dst, const CUtensorMap* m, int c0, int c1, int c2, uint32_t bar, uint16_t mask) {
  asm volatile("cp.async.bulk.tensor.3d.shared::cluster.global.mbarrier::complete_tx::bytes.multicast::cluster [%0], [%1, {%3, %4, %5}], [%2], %6;"
               :: "r"(dst), "l"(m), "r"(bar), "r"(c0), "r"(c1), "r"(c2), "h"(mask) : "memory");
}
DEVI void tma3d_prefetch(const CUtensorMap* m, int c0, int c1, int c2) {
  asm volatile("cp.async.bulk.prefetch.tensor.3d.L2.global [%0, {%1, %2, %3}];" :: "l"(m), "r"(c0), "r"(c1), "r"(c2) : "memory");
}
DEVI void tma2d_prefetch(const CUtensorMap* m, int c0, int c1) {
  asm volatile("cp.async.bulk.prefetch.tensor.2d.L2.global [%0, {%1, %2}];" :: "l"(m), "r"(c0), "r"(c1) : "memory");
}
#define EVF 7
DEVI uint64_t stream_policy() { uint64_t p; asm("createpolicy.fractional.L2::evict_first.b64 %0, 1.0;" : "=l"(p)); return p; }
DEVI void bulk_store(void* g, uint32_t s, uint32_t bytes) {
  if (EVF & 1) asm volatile("cp.async.bulk.global.shared::cta.bulk_group.L2::cache_hint [%0], [%1], %2, %3;" :: "l"(g), "r"(s), "r"(bytes), "l"(stream_policy()) : "memory");
  else asm volatile("cp.async.bulk.global.shared::cta.bulk_group [%0], [%1], %2;" :: "l"(g), "r"(s), "r"(bytes) : "memory");
}
DEVI void ldsm4(uint32_t (&r)[4], uint32_t a) {
  asm volatile("ldmatrix.sync.aligned.m8n8.x4.shared.b16 {%0,%1,%2,%3}, [%4];" : "=r"(r[0]), "=r"(r[1]), "=r"(r[2]), "=r"(r[3]) : "r"(a) : "memory");
}
DEVI void ldsm4t(uint32_t (&r)[4], uint32_t a) {
  asm volatile("ldmatrix.sync.aligned.m8n8.x4.trans.shared.b16 {%0,%1,%2,%3}, [%4];" : "=r"(r[0]), "=r"(r[1]), "=r"(r[2]), "=r"(r[3]) : "r"(a) : "memory");
}
DEVI void ldsm4t_p(uint32_t* r, uint32_t a) {
  asm volatile("ldmatrix.sync.aligned.m8n8.x4.trans.shared.b16 {%0,%1,%2,%3}, [%4];" : "=r"(r[0]), "=r"(r[1]), "=r"(r[2]), "=r"(r[3]) : "r"(a) : "memory");
}
DEVI void ldsm2(uint32_t (&r)[2], uint32_t a) {
  asm volatile("ldmatrix.sync.aligned.m8n8.x2.shared.b16 {%0,%1}, [%2];" : "=r"(r[0]), "=r"(r[1]) : "r"(a) : "memory");
}
DEVI void stsm4(uint32_t a, uint32_t r0, uint32_t r1, uint32_t r2, uint32_t r3) {
  asm volatile("stmatrix.sync.aligned.m8n8.x4.shared.b16 [%0], {%1,%2,%3,%4};" :: "r"(a), "r"(r0), "r"(r1), "r"(r2), "r"(r3) : "memory");
}
DEVI void mma16816(float (&d)[4], const uint32_t* a, uint32_t b0, uint32_t b1) {
  asm volatile("mma.sync.aligned.m16n8k16.row.col.f32.bf16.bf16.f32 {%0,%1,%2,%3}, {%4,%5,%6,%7}, {%8,%9}, {%0,%1,%2,%3};"
               : "+f"(d[0]), "+f"(d[1]), "+f"(d[2]), "+f"(d[3]) : "r"(a[0]), "r"(a[1]), "r"(a[2]), "r"(a[3]), "r"(b0), "r"(b1));
}
DEVI void mma1688(float (&d)[4], uint32_t a0, uint32_t a1, uint32_t b0) {
  asm volatile("mma.sync.aligned.m16n8k8.row.col.f32.bf16.bf16.f32 {%0,%1,%2,%3}, {%4,%5}, {%6}, {%0,%1,%2,%3};"
               : "+f"(d[0]), "+f"(d[1]), "+f"(d[2]), "+f"(d[3]) : "r"(a0), "r"(a1), "r"(b0));
}
DEVI uint32_t pack_bf16(float lo, float hi) { uint32_t r; asm("cvt.rn.bf16x2.f32 %0, %1, %2;" : "=r"(r) : "f"(hi), "f"(lo)); return r; }
DEVI uint32_t pack_f16(float lo, float hi) { uint32_t r; asm("cvt.rn.f16x2.f32 %0, %1, %2;" : "=r"(r) : "f"(hi), "f"(lo)); return r; }
DEVI uint32_t f16x2_to_bf16x2(uint32_t h) { float2 f = __half22float2(*reinterpret_cast<__half2*>(&h)); return pack_bf16(f.x, f.y); }
DEVI void sts32(uint32_t a, uint32_t v) { asm volatile("st.shared.u32 [%0], %1;" :: "r"(a), "r"(v) : "memory"); }
DEVI void sts64(uint32_t a, uint32_t v0, uint32_t v1) { asm volatile("st.shared.v2.u32 [%0], {%1,%2};" :: "r"(a), "r"(v0), "r"(v1) : "memory"); }
DEVI void sts128(uint32_t a, uint32_t v0, uint32_t v1, uint32_t v2, uint32_t v3) { asm volatile("st.shared.v4.u32 [%0], {%1,%2,%3,%4};" :: "r"(a), "r"(v0), "r"(v1), "r"(v2), "r"(v3) : "memory"); }
DEVI uint32_t lds32(uint32_t a) { uint32_t v; asm volatile("ld.shared.u32 %0, [%1];" : "=r"(v) : "r"(a) : "memory"); return v; }
DEVI float2 lds64f(uint32_t a) { float2 v; asm volatile("ld.shared.v2.f32 {%0,%1}, [%2];" : "=f"(v.x), "=f"(v.y) : "r"(a) : "memory"); return v; }
DEVI void lds128(uint32_t (&r)[4], uint32_t a) { asm volatile("ld.shared.v4.u32 {%0,%1,%2,%3}, [%4];" : "=r"(r[0]), "=r"(r[1]), "=r"(r[2]), "=r"(r[3]) : "r"(a) : "memory"); }
DEVI void st_async64(uint32_t a, float x, float y, uint32_t bar) {
  asm volatile("st.async.weak.shared::cluster.mbarrier::complete_tx::bytes.v2.f32 [%0], {%1,%2}, [%3];" :: "r"(a), "f"(x), "f"(y), "r"(bar) : "memory");
}
DEVI void st_async32(uint32_t a, uint32_t x, uint32_t bar) {
  asm volatile("st.async.weak.shared::cluster.mbarrier::complete_tx::bytes.b32 [%0], %1, [%2];" :: "r"(a), "r"(x), "r"(bar) : "memory");
}
DEVI void ld_relaxed128(uint32_t (&r)[4], const void* p) {
  asm volatile("ld.relaxed.gpu.global.v4.u32 {%0,%1,%2,%3}, [%4];" : "=r"(r[0]), "=r"(r[1]), "=r"(r[2]), "=r"(r[3]) : "l"(p) : "memory");
}
DEVI void red_f16x2(void* p, uint32_t v) { asm volatile("red.relaxed.gpu.global.add.noftz.f16x2 [%0], %1;" :: "l"(p), "r"(v) : "memory"); }
DEVI void red_f16x2_v4(void* p, uint32_t a, uint32_t b, uint32_t c, uint32_t d) {
  asm volatile("red.relaxed.gpu.global.add.noftz.v4.f16x2 [%0], {%1,%2,%3,%4};" :: "l"(p), "r"(a), "r"(b), "r"(c), "r"(d) : "memory");
}
DEVI void red_add2(float2* p, float a, float b) { asm volatile("red.relaxed.gpu.global.add.v2.f32 [%0], {%1,%2};" :: "l"(p), "f"(a), "f"(b) : "memory"); }
DEVI float rcp(float x) { float y; asm("rcp.approx.ftz.f32 %0, %1;" : "=f"(y) : "f"(x)); return y; }
DEVI float ex2(float x) { float y; asm("ex2.approx.ftz.f32 %0, %1;" : "=f"(y) : "f"(x)); return y; }
DEVI uint64_t mkdesc(uint32_t addr, uint32_t lbo, uint32_t sbo, uint32_t swz) {
  return (uint64_t)((addr & 0x3FFFF) >> 4) | ((uint64_t)(lbo >> 4) << 16) | ((uint64_t)(sbo >> 4) << 32) | ((uint64_t)swz << 62);
}
DEVI void wg_fence() { asm volatile("wgmma.fence.sync.aligned;" ::: "memory"); }
DEVI void wg_commit() { asm volatile("wgmma.commit_group.sync.aligned;" ::: "memory"); }
template <int N> DEVI void wg_wait() { asm volatile("wgmma.wait_group.sync.aligned %0;" :: "n"(N) : "memory"); }
#define ACC4(d, o) "+f"(d[o]), "+f"(d[o + 1]), "+f"(d[o + 2]), "+f"(d[o + 3])
constexpr uint32_t DHI_SW128 = (1024u >> 4) | (1u << 30);
DEVI uint32_t desc_lo(uint32_t addr, uint32_t lbo) { return ((addr & 0x3FFFF) >> 4) | ((lbo >> 4) << 16); }
template <int OB_, int ACC> DEVI void wgmma_rs_n32(float (&d)[16], const uint32_t* a, uint32_t b) {
  asm volatile("{.reg .b64 db; .reg .b32 tb; add.u32 tb, %20, %21; mov.b64 db, {tb, %22};\n"
               "wgmma.mma_async.sync.aligned.m64n32k16.f32.bf16.bf16 {%0,%1,%2,%3,%4,%5,%6,%7,%8,%9,%10,%11,%12,%13,%14,%15}, {%16,%17,%18,%19}, db, %23, 1, 1, 0;}"
               : ACC4(d, 0), ACC4(d, 4), ACC4(d, 8), ACC4(d, 12) : "r"(a[0]), "r"(a[1]), "r"(a[2]), "r"(a[3]), "r"(b), "n"(OB_ >> 4), "n"(DHI_SW128), "n"(ACC));
}
template <int K0, int K1, int ACC = 1> struct Unroll {
  static DEVI void kbulk(float (&d)[16], const uint32_t* W, uint32_t x) { wgmma_rs_n32<(K0 >> 2) * 4096 + (K0 & 3) * 32, ACC>(d, W + K0 * 4, x); Unroll<K0 + 1, K1>::kbulk(d, W, x); }
};
template <int K1> struct Unroll<K1, K1, 1> {
  static DEVI void kbulk(float (&)[16], const uint32_t*, uint32_t) {}
};

DEVI void wgmma_n192_nt(float (&d)[96], uint64_t a, uint64_t b, int acc) {
  asm volatile("{.reg .pred p; setp.ne.b32 p, %98, 0;\n"
               "wgmma.mma_async.sync.aligned.m64n192k16.f32.bf16.bf16 {%0,%1,%2,%3,%4,%5,%6,%7,%8,%9,%10,%11,%12,%13,%14,%15,%16,%17,%18,%19,%20,%21,%22,%23,%24,%25,%26,%27,%28,%29,%30,%31,%32,%33,%34,%35,%36,%37,%38,%39,%40,%41,%42,%43,%44,%45,%46,%47,%48,%49,%50,%51,%52,%53,%54,%55,%56,%57,%58,%59,%60,%61,%62,%63,%64,%65,%66,%67,%68,%69,%70,%71,%72,%73,%74,%75,%76,%77,%78,%79,%80,%81,%82,%83,%84,%85,%86,%87,%88,%89,%90,%91,%92,%93,%94,%95}, %96, %97, p, 1, 1, 0, 1;}"
               : ACC4(d, 0), ACC4(d, 4), ACC4(d, 8), ACC4(d, 12), ACC4(d, 16), ACC4(d, 20), ACC4(d, 24), ACC4(d, 28), ACC4(d, 32), ACC4(d, 36), ACC4(d, 40), ACC4(d, 44), ACC4(d, 48), ACC4(d, 52), ACC4(d, 56), ACC4(d, 60), ACC4(d, 64), ACC4(d, 68), ACC4(d, 72), ACC4(d, 76), ACC4(d, 80), ACC4(d, 84), ACC4(d, 88), ACC4(d, 92) : "l"(a), "l"(b), "r"(acc));
}
DEVI void wgmma_n160_nt(float (&d)[80], uint64_t a, uint64_t b, int acc) {
  asm volatile("{.reg .pred p; setp.ne.b32 p, %82, 0;\n"
               "wgmma.mma_async.sync.aligned.m64n160k16.f32.bf16.bf16 {%0,%1,%2,%3,%4,%5,%6,%7,%8,%9,%10,%11,%12,%13,%14,%15,%16,%17,%18,%19,%20,%21,%22,%23,%24,%25,%26,%27,%28,%29,%30,%31,%32,%33,%34,%35,%36,%37,%38,%39,%40,%41,%42,%43,%44,%45,%46,%47,%48,%49,%50,%51,%52,%53,%54,%55,%56,%57,%58,%59,%60,%61,%62,%63,%64,%65,%66,%67,%68,%69,%70,%71,%72,%73,%74,%75,%76,%77,%78,%79}, %80, %81, p, 1, 1, 0, 1;}"
               : ACC4(d, 0), ACC4(d, 4), ACC4(d, 8), ACC4(d, 12), ACC4(d, 16), ACC4(d, 20), ACC4(d, 24), ACC4(d, 28), ACC4(d, 32), ACC4(d, 36), ACC4(d, 40), ACC4(d, 44), ACC4(d, 48), ACC4(d, 52), ACC4(d, 56), ACC4(d, 60), ACC4(d, 64), ACC4(d, 68), ACC4(d, 72), ACC4(d, 76) : "l"(a), "l"(b), "r"(acc));
}
DEVI void wgmma_n240_nn(float (&d)[120], uint64_t a, uint64_t b, int acc) {
  asm volatile("{.reg .pred p; setp.ne.b32 p, %122, 0;\n"
               "wgmma.mma_async.sync.aligned.m64n240k16.f32.bf16.bf16 {%0,%1,%2,%3,%4,%5,%6,%7,%8,%9,%10,%11,%12,%13,%14,%15,%16,%17,%18,%19,%20,%21,%22,%23,%24,%25,%26,%27,%28,%29,%30,%31,%32,%33,%34,%35,%36,%37,%38,%39,%40,%41,%42,%43,%44,%45,%46,%47,%48,%49,%50,%51,%52,%53,%54,%55,%56,%57,%58,%59,%60,%61,%62,%63,%64,%65,%66,%67,%68,%69,%70,%71,%72,%73,%74,%75,%76,%77,%78,%79,%80,%81,%82,%83,%84,%85,%86,%87,%88,%89,%90,%91,%92,%93,%94,%95,%96,%97,%98,%99,%100,%101,%102,%103,%104,%105,%106,%107,%108,%109,%110,%111,%112,%113,%114,%115,%116,%117,%118,%119}, %120, %121, p, 1, 1, 0, 0;}"
               : ACC4(d, 0), ACC4(d, 4), ACC4(d, 8), ACC4(d, 12), ACC4(d, 16), ACC4(d, 20), ACC4(d, 24), ACC4(d, 28), ACC4(d, 32), ACC4(d, 36), ACC4(d, 40), ACC4(d, 44), ACC4(d, 48), ACC4(d, 52), ACC4(d, 56), ACC4(d, 60), ACC4(d, 64), ACC4(d, 68), ACC4(d, 72), ACC4(d, 76), ACC4(d, 80), ACC4(d, 84), ACC4(d, 88), ACC4(d, 92), ACC4(d, 96), ACC4(d, 100), ACC4(d, 104), ACC4(d, 108), ACC4(d, 112), ACC4(d, 116) : "l"(a), "l"(b), "r"(acc));
}
DEVI void wgmma_n80_nt(float (&d)[40], uint64_t a, uint64_t b, int acc) {
  asm volatile("{.reg .pred p; setp.ne.b32 p, %42, 0;\n"
               "wgmma.mma_async.sync.aligned.m64n80k16.f32.bf16.bf16 {%0,%1,%2,%3,%4,%5,%6,%7,%8,%9,%10,%11,%12,%13,%14,%15,%16,%17,%18,%19,%20,%21,%22,%23,%24,%25,%26,%27,%28,%29,%30,%31,%32,%33,%34,%35,%36,%37,%38,%39}, %40, %41, p, 1, 1, 0, 1;}"
               : ACC4(d, 0), ACC4(d, 4), ACC4(d, 8), ACC4(d, 12), ACC4(d, 16), ACC4(d, 20), ACC4(d, 24), ACC4(d, 28), ACC4(d, 32), ACC4(d, 36) : "l"(a), "l"(b), "r"(acc));
}

#define ACQ 0
DEVI uint32_t ld_acquire(const uint32_t* p) {
  uint32_t v;
  if (ACQ) asm volatile("ld.acquire.gpu.global.u32 %0, [%1];" : "=r"(v) : "l"(p) : "memory");
  else asm volatile("ld.relaxed.gpu.global.u32 %0, [%1];" : "=r"(v) : "l"(p) : "memory");
  return v;
}
DEVI uint4 ldcg_if(const void* p, bool on) {
  uint4 v;
  asm volatile("{.reg .pred p; setp.ne.u32 p, %5, 0; mov.u32 %0, 0; mov.u32 %1, 0; mov.u32 %2, 0; mov.u32 %3, 0;\n"
               "@p ld.global.cg.v4.u32 {%0,%1,%2,%3}, [%4];}" : "=&r"(v.x), "=&r"(v.y), "=&r"(v.z), "=&r"(v.w) : "l"(p), "r"((uint32_t)on) : "memory");
  return v;
}
DEVI void red_release(uint32_t* p) { asm volatile("red.release.gpu.global.add.u32 [%0], 1;" :: "l"(p) : "memory"); }
#define TIGHT 1
DEVI void wait_count_t(const uint32_t* p, uint32_t n, bool tight) {
  for (int i = 0; i < 4000000 && ld_acquire(p) < n; i++) if (!(TIGHT && tight)) __nanosleep(100);
}
DEVI void wait_count(const uint32_t* p, uint32_t n) {
  for (int i = 0; i < 4000000 && ld_acquire(p) < n; i++) __nanosleep(100);
}
DEVI void spin_count(const uint32_t* p, uint32_t n) { for (int i = 0; i < 4000000 && ld_acquire(p) < n; i++) {} }
DEVI void mbar_wait_long(uint32_t bar, uint32_t par) { for (int n = 0; n < 4000000 && !mbar_try(bar, par); n++) {} }
DEVI void ln_row(float (&v)[20], bf16* y, int lane) {
  float s = 0.f;
#pragma unroll
  for (int i = 0; i < 20; i++) s += v[i];
#pragma unroll
  for (int o = 16; o; o >>= 1) s += __shfl_xor_sync(0xffffffffu, s, o);
  const float m = s * (1.0f / DM); float q = 0.f;
#pragma unroll
  for (int i = 0; i < 20; i++) { v[i] -= m; q += v[i] * v[i]; }
#pragma unroll
  for (int o = 16; o; o >>= 1) q += __shfl_xor_sync(0xffffffffu, q, o);
  const float r = rsqrtf(q * (1.0f / DM) + 1e-5f);
#pragma unroll
  for (int i = 0; i < 5; i++) *(uint2*)(y + i * 128 + lane * 4) = make_uint2(pack_bf16(v[4 * i] * r, v[4 * i + 1] * r), pack_bf16(v[4 * i + 2] * r, v[4 * i + 3] * r));
}

DEVI uint32_t mag4(uint32_t m, const uint32_t* f) {
  return __vmaxu2(__vmaxu2(m, __vmaxu2(f[0] & 0x7FFF7FFFu, f[1] & 0x7FFF7FFFu)), __vmaxu2(f[2] & 0x7FFF7FFFu, f[3] & 0x7FFF7FFFu));
}
DEVI void publish_max(uint32_t a, uint32_t m) {
  m = __reduce_max_sync(0xffffffffu, max(m & 0xFFFFu, m >> 16));
  if ((threadIdx.x & 31) == 0) asm volatile("red.shared.max.u32 [%0], %1;" :: "r"(a), "r"(m) : "memory");
}

namespace ch {
constexpr uint32_t WQ = 0;
constexpr uint32_t WOF2 = 81920;
constexpr uint32_t WOF = 106496;
constexpr uint32_t XB = 143360;
constexpr uint32_t MEMB = 184320;
constexpr uint32_t KT = 194560;
constexpr uint32_t VT = 199680;
constexpr uint32_t PK = 204800;
constexpr uint32_t QS = 212992;
constexpr uint32_t KP = 215040;
constexpr uint32_t EX = 217088;
constexpr uint32_t OB = 221184;
constexpr uint32_t SX = 224256;
constexpr uint32_t WOF3 = 226176;
constexpr uint32_t WOSTAGE = 143360;
constexpr uint32_t PB = OB;
constexpr uint32_t WMX = OB + 128;
constexpr uint32_t MISC = 228224;
constexpr uint32_t BAR_XF = MISC + 56;
constexpr uint32_t BAR_WK = MISC + 48, BAR_W1 = MISC, BAR_W2 = MISC + 8, BAR_X0 = MISC + 16, BAR_X1 = MISC + 24, BAR_S = MISC + 32, BAR_O = MISC + 40;
constexpr uint32_t MX = MISC + 64;
constexpr uint32_t INV = MX + 32;
#define PD_ 550
#define XD_ 150
#define X1D_ 0
#define PFW 0
constexpr uint32_t SMEM = 228352;
}

#define TS(e)
#define TSV(e, v)
#define TSX(x)
#define TSD(e, x)

#define SS(e)
#define E1(id, x)
#define PIN(x) asm volatile("" : "+r"(x))
#define PINF(x) asm volatile("" : "+f"(x))
#define PINL(x) asm volatile("" : "+l"(x))

DEVI uint32_t ar_line_off(uint32_t l) { return (l >> 2) * 1024 + (l & 3) * 128; }
DEVI uint32_t ar_tile_off(int T) { return (T >> 1) * 1024 + (T & 1) * 256; }
DEVI uint32_t ar_extra_off(uint32_t T) { return ar_line_off(80 + (T >> 2)) + (T & 3) * 32; }

DEVI void wo_red(const char* p, uint32_t w0, uint32_t w1, bool last) {
  red_f16x2((void*)p, last ? 0x3C00u : w0);
  red_f16x2((void*)(p + 128), last ? 0x3C00u : w1);
}
DEVI void wo_red_extra_p(const char* px, uint32_t w0, uint32_t w1, uint32_t ln) {
  asm volatile("{.reg .pred p; setp.eq.u32 p, %5, 31; @p red.relaxed.gpu.global.add.noftz.v4.f16x2 [%0], {%1,%2,%3,%4};}"
               :: "l"(px), "r"(w0), "r"(w1), "r"(0u), "r"(0x3C00u), "r"(ln) : "memory");
}

#define ARH 2
DEVI void sched_fence(uint32_t zero) {
#pragma unroll 1
  for (uint32_t i = 0; i < zero; i++) asm volatile("nanosleep.u32 0;" ::: "memory");
}
template <int N> DEVI void code_pad(uint32_t zero) {
  if (N > 0) {
#pragma unroll 1
    for (uint32_t i = 0; i < zero; i++) {
#pragma unroll
      for (int k = 0; k < N; k++) asm volatile("nanosleep.u32 0;" ::: "memory");
    }
  }
}
#define PAD1 0
#define PAD0 0
DEVI void loaded(uint32_t x) { asm volatile("{.reg .pred p; setp.eq.u32 p, %0, 0xdeadbeef; @p nanosleep.u32 0;}" :: "r"(x) : "memory"); }
DEVI uint32_t opq(uint32_t x) { asm volatile("" : "+r"(x)); return x; }

DEVI uint32_t ar_read(const char* arb, uint32_t sb, int w, uint32_t lane_, uint32_t zero, uint32_t tref, int dly, int s) {
  const int wg = 2; (void)wg; (void)s;
  const uint32_t lane = opq(lane_);
  const int b0 = (w >> 1) * 10 + (w & 1);
  const uint32_t e = min(lane, 9u), T = 2 * b0 + 4 * (e >> 1) + (e & 1);
  const char* p0 = arb + b0 * 1024 + lane * 16;
  const char* p2 = arb + ar_extra_off(T);
  uint32_t dst = sb + ch::MEMB + b0 * 512 + lane * 16, dst2 = sb + ch::MEMB + (16 * T + 7) * 16 + 12;
  uint32_t v[6][4];
  PINL(p0); PINL(p2); PIN(dst); PIN(dst2);
  while ((int)(clk32() - tref) < dly) {}
#pragma unroll
  for (int i = 0; i < 5; i++) ld_relaxed128(v[i], p0 + i * 2048);
  ld_relaxed128(v[5], p2);
  sched_fence(zero);
  TS(4);
  uint32_t bad = 0;
#pragma unroll
  for (int i = 0; i < 5; i++) bad |= v[i][3] ^ 0x5000u;
  if ((lane & 7) != 7) bad = 0;
  bad |= v[5][3] ^ 0x5000u;
  TSD(5, bad);
  E1(6, bad);
  int n = 0;
  if (__any_sync(0xffffffffu, bad != 0)) {
    if (lane == 0) sts32(sb + ch::MX + 20, 1u);
    while (true) {
      bad = 0;
#pragma unroll
      for (int i = 0; i < 6; i++) if ((i == 5 || (lane & 7) == 7) && v[i][3] != 0x5000u) bad |= 1u << i;
      bad = __reduce_or_sync(0xffffffffu, bad);
      if (!bad || ++n > SPIN_LIMIT) break;
#pragma unroll
      for (int i = 0; i < 6; i++) if (bad >> i & 1) ld_relaxed128(v[i], i < 5 ? p0 + i * 2048 : p2);
    }
  }
  TSV(6, n);
  const uint32_t x0 = f16x2_to_bf16x2(v[5][0]), x1 = f16x2_to_bf16x2(v[5][1]);
#pragma unroll
  for (int i = 0; i < 5; i++) {
    sts128(dst + i * 1024, f16x2_to_bf16x2(v[i][0]), f16x2_to_bf16x2(v[i][1]), f16x2_to_bf16x2(v[i][2]), f16x2_to_bf16x2(v[i][3]));
    if (i == ARH - 1 || i == 4) {
      __syncwarp();
      sts32(dst2, x0); sts32(dst2 + 128, x1);
      if (i < 4) { TS(7); bar_arrive(1, 384); sched_fence(zero); } else { TSX(TS(1)); bar_sync(3, 384); }
    }
  }
  const uint32_t keep = (lane & 7) == 7 ? 0u : 0x7FFF7FFFu;
  uint32_t m = __vmaxu2(v[5][0] & 0x7FFF7FFFu, v[5][1] & 0x7FFF7FFFu);
#pragma unroll
  for (int i = 0; i < 5; i++) m = __vmaxu2(__vmaxu2(m, __vmaxu2(v[i][0] & 0x7FFF7FFFu, v[i][1] & 0x7FFF7FFFu)), __vmaxu2(v[i][2] & 0x7FFF7FFFu, v[i][3] & keep));
  return m;
}

#define VL 0
struct Peers {
  uint32_t a[2];
  DEVI Peers(uint32_t sb, int j) {
#pragma unroll
    for (int r = 0; r < 2; r++) { int peer = j + 1 + r; if (peer >= 3) peer -= 3; a[r] = mapa(sb, peer); }
  }
};
DEVI uint32_t lane_id() { const uint32_t l = threadIdx.x & 31; return __shfl_sync(0xffffffffu, l, l); }
DEVI void score_tile(uint32_t sb, uint32_t qa, const uint32_t (&b0)[4], const uint32_t (&b1)[4], const Peers& pe, uint32_t off, uint32_t lane) {
  float c0[4] = {0.f, 0.f, 0.f, 0.f}, c1[4] = {0.f, 0.f, 0.f, 0.f};
  uint32_t a0[4], a1[4], a2[4], a3[4];
  ldsm4t(a0, qa); ldsm4t(a1, qa + 256); ldsm4t(a2, qa + 512); ldsm4t(a3, qa + 768);
  mma16816(c0, a0, b0[0], b0[1]); mma16816(c1, a1, b0[2], b0[3]);
  mma16816(c0, a2, b1[0], b1[1]); mma16816(c1, a3, b1[2], b1[3]);
  if (!VL) asm volatile("bar.arrive 5, 288;" : "+f"(c0[0]), "+f"(c1[0]) :: "memory");
  const float cs = 0.25f * 0.07216878364870322f * 1.4426950408889634f;
  const float x = ((c0[0] + c0[2]) + (c1[0] + c1[2])) * cs, y = ((c0[1] + c0[3]) + (c1[1] + c1[3])) * cs;
  uint32_t u; asm("cvt.rn.satfinite.f16x2.f32 %0, %1, %2;" : "=r"(u) : "f"(y), "f"(x));
  st_async32(pe.a[0] + off, u, pe.a[0] + ch::BAR_S);
  st_async32(pe.a[1] + off, u, pe.a[1] + ch::BAR_S);
  sts32(sb + off, u);
  __syncwarp();
  if (lane == 0) mbar_arrive(sb + ch::BAR_S);
}
DEVI uint32_t hadd2(uint32_t a, uint32_t b) { uint32_t r; asm("add.rn.f16x2 %0, %1, %2;" : "=r"(r) : "r"(a), "r"(b)); return r; }
DEVI uint32_t hmax2(uint32_t a, uint32_t b) { uint32_t r; asm("max.f16x2 %0, %1, %2;" : "=r"(r) : "r"(a), "r"(b)); return r; }
DEVI uint32_t add_bf16x2(uint32_t a, uint32_t b) { uint32_t r; asm("add.rn.bf16x2 %0, %1, %2;" : "=r"(r) : "r"(a), "r"(b)); return r; }

DEVI uint32_t slab_off(uint32_t base, int w, uint32_t lane) { return base + (16 * w + (lane >> 2)) * 80 + (lane & 3) * 4; }
DEVI void release_x(uint32_t sb, int half, int w, uint32_t lane) {
  if (lane == 0) {
    if (w == 0) mbar_expect(sb + ch::BAR_X0 + half * 8, 20480);
    mbar_arrive_cluster(mapa(sb + ch::BAR_XF, half));
  }
}
#define TSYNC 1
#define KORD 0
#define X0E 0
#define X0D_ 0
#define X1E 1
#define KS2 0
#define SKIPT 0
DEVI void store_slabs(uint32_t sb, int s, int h, int j) {
  bf16* kvp = g_kv + ((size_t)(s * NH + h) * 2 * DH + 64 * j) * NKEY;
  fence_async();
  bulk_store(kvp, sb + ch::KT, SLAB);
  bulk_store(kvp + DH * NKEY, sb + ch::VT, SLAB);
  asm volatile("cp.async.bulk.commit_group;" ::: "memory");
}

template <int MODE>
DEVI void tokens_partial(uint32_t sb, uint32_t dst, const uint32_t* W, uint32_t xdesc, int w, uint32_t lane) {
  float d[16];
#pragma unroll
  for (int i = 0; i < 16; i++) d[i] = 0.f;
  wg_fence();
  if (!((SKIPT >> (MODE == 3 ? 1 : MODE)) & 1)) Unroll<20, 40, 0>::kbulk(d, W - 80, xdesc);
  wg_commit();
  if (MODE == 1) bar_sync(12, 384);
  if (!KS2 && MODE == 2) bar_sync(11, 256);
  wg_wait<0>();
  if (!KS2 && (MODE == 1 || MODE == 3)) release_x(sb, 1, w, lane);
  if (MODE == 1) bar_sync(13, 384);
  if (KS2 && MODE == 2) release_x(sb, 1, w, lane);
  dst += sb + w * 512 + opq(lane) * 16;
#pragma unroll
  for (int i = 0; i < 4; i++)
    sts128(dst + i * 2048, __float_as_uint(d[4 * i]), __float_as_uint(d[4 * i + 1]), __float_as_uint(d[4 * i + 2]), __float_as_uint(d[4 * i + 3]));
  if (KS2 && MODE == 2) bar_arrive(11, 256);
}
#define LSH 0
#define KPK 16
template <bool LOOP>
DEVI void tokens_finish(uint32_t sb, const uint32_t* W, uint32_t xdesc, int w, uint32_t lane, int s = 0, const CUtensorMap* mx = nullptr) {
  const uint32_t ln = opq(lane), t16 = sb + w * 512 + ln * 16, slab = sb + slab_off(16, w, ln);
  float d[16]; uint32_t e[4][4];
#pragma unroll
  for (int i = 0; i < 16; i++) d[i] = 0.f;
  wg_fence();
  if (!(LOOP && (SKIPT & 8))) Unroll<0, 20, 0>::kbulk(d, W + 80, xdesc);
  wg_commit();
  if (!KS2 && !KORD && LOOP) bar_arrive(6, 256);
  if (LOOP && LSH == 2 && s < 0) bar_sync(8, 256);
  if (!LOOP) {
    bar_sync(8, 256);
    if (w == 3 && lane == 0) { mbar_expect(sb + ch::BAR_X1, 20480); tma3d(sb + ch::XB + 20480, mx, 0, SEG, 5, sb + ch::BAR_X1); }
    __syncwarp();
  }
#pragma unroll
  for (int i = 0; i < 4; i++) lds128(e[i], t16 + ch::QS + i * 2048);
  wg_wait<0>();
  uint32_t u[8];
#pragma unroll
  for (int i = 0; i < 4; i++) {
    u[2 * i] = pack_bf16(d[4 * i] + __uint_as_float(e[i][0]), d[4 * i + 1] + __uint_as_float(e[i][1]));
    u[2 * i + 1] = pack_bf16(d[4 * i + 2] + __uint_as_float(e[i][2]), d[4 * i + 3] + __uint_as_float(e[i][3]));
  }
  wg_fence();
  if (!(LOOP && (SKIPT & 16))) Unroll<0, 6, 0>::kbulk(d, W, xdesc);
#pragma unroll
  for (int i = 0; i < 4; i++) { sts32(slab + ch::VT + i * 16, u[2 * i]); sts32(slab + ch::VT + i * 16 + 640, u[2 * i + 1]); }
  if (KS2) {
    if (!(LOOP && (SKIPT & 16))) Unroll<6, KPK>::kbulk(d, W, xdesc);
    if (LOOP) bar_sync(11, 256);
  }
#pragma unroll
  for (int i = 0; i < 4; i++) lds128(e[i], t16 + ch::PK + i * 2048);
  if (!KS2) {
    if (!(LOOP && (SKIPT & 16))) Unroll<6, KPK>::kbulk(d, W, xdesc);
    if (LOOP) asm volatile("bar.arrive 11, 256;" : "+r"(e[0][0]), "+r"(e[1][0]), "+r"(e[2][0]), "+r"(e[3][0]) :: "memory");
  }
  if (!(LOOP && (SKIPT & 16))) Unroll<KPK, 20>::kbulk(d, W, xdesc);
  wg_commit(); wg_wait<0>();
  release_x(sb, 0, w, lane);
  if (LOOP) E1(7, __float_as_uint(d[0]));
#pragma unroll
  for (int i = 0; i < 4; i++) {
    sts32(slab + ch::KT + i * 16, pack_bf16(d[4 * i] + __uint_as_float(e[i][0]), d[4 * i + 1] + __uint_as_float(e[i][1])));
    sts32(slab + ch::KT + i * 16 + 640, pack_bf16(d[4 * i + 2] + __uint_as_float(e[i][2]), d[4 * i + 3] + __uint_as_float(e[i][3])));
  }
}

DEVI uint32_t afrag_off(int w, uint32_t lane) { return ((lane >> 4) * 8 + (lane & 7)) * 128 + (((w * 2 + ((lane >> 3) & 1)) ^ (lane & 7)) << 4); }
#define NF 5
#define WQR 0
DEVI void ldwq(uint32_t (&f)[4], uint32_t a) { if (WQR) lds128(f, a); else ldsm4t(f, a); }
DEVI void proj_stage(uint32_t (&f)[NF][4], uint32_t qa) {
#pragma unroll
  for (int i = 0; i < NF; i++) ldwq(f[i], qa + i * 2048);
}
template <int WG>
DEVI void proj_mem(float (&q)[4], float (&k)[4], float (&v)[4], uint32_t (&f)[NF][4], const uint32_t* W, uint32_t qa, uint32_t ba, uint32_t sb, int w, int s) {
  uint32_t b[2][4];
  const int wg = WG; (void)wg; (void)sb; (void)w; (void)s;
#pragma unroll
  for (int i = 0; i < 4; i++) q[i] = k[i] = v[i] = 0.f;
  bar_sync(1, 384);
  ldsm4t(b[0], ba);
  if (WG == 0) E1(8, b[0][0]);
  if (WG == 1) { TSX(TSD(5, b[0][0])); }
#pragma unroll
  for (int k2 = 0; k2 < 10; k2++) {
    if (WG == 1 && k2 + 1 == 2 * ARH) { TSX(TSD(7, __float_as_uint(v[0]))); }
    if (k2 + 1 == 2 * ARH) bar_sync(3, 384);
    if (k2 < 9) ldsm4t(b[(k2 + 1) & 1], ba + (k2 + 1) * 512);
    if (WG == 1 && k2 + 1 == 2 * ARH) { TSX(TSD(6, b[(k2 + 1) & 1][0])); }
    if (WG == 0 && k2 + 1 == 2 * ARH) { TSX(TSD(7, __float_as_uint(v[0]))); }
    mma16816(q, f[(2 * k2) % NF], b[k2 & 1][0], b[k2 & 1][1]);
    if (2 * k2 + NF < 20) ldwq(f[(2 * k2) % NF], qa + (2 * k2 + NF) * 2048);
    mma16816(k, &W[k2 * 8], b[k2 & 1][0], b[k2 & 1][1]);
    mma16816(v, &W[80 + k2 * 8], b[k2 & 1][0], b[k2 & 1][1]);
    mma16816(q, f[(2 * k2 + 1) % NF], b[k2 & 1][2], b[k2 & 1][3]);
    if (2 * k2 + 1 + NF < 20) ldwq(f[(2 * k2 + 1) % NF], qa + (2 * k2 + 1 + NF) * 2048);
    mma16816(k, &W[k2 * 8 + 4], b[k2 & 1][2], b[k2 & 1][3]);
    mma16816(v, &W[84 + k2 * 8], b[k2 & 1][2], b[k2 & 1][3]);
  }
}

template <bool BAR>
DEVI void wo_tile_smem(uint32_t sb, uint32_t fa, uint32_t ob, int par, const char* p, const char* px, bool last, float& sc) {
  uint32_t f[6][4], b[2][4];
  float c0[4] = {0.f, 0.f, 0.f, 0.f}, c1[4] = {0.f, 0.f, 0.f, 0.f};
#pragma unroll
  for (int k = 0; k < 6; k++) lds128(f[k], fa + k * 512);
  if (BAR) bar_sync(9, 384);
  ldsm4t(b[0], ob); ldsm4t(b[1], ob + 512);
  sc = __uint_as_float(lds32(sb + ch::MX + 16));
  float2 iv = lds64f(sb + ch::INV + (opq(threadIdx.x) & 3) * 8);
  iv.x *= sc; iv.y *= sc;
  mma16816(c0, f[0], b[0][0], b[0][1]); mma16816(c1, f[1], b[0][2], b[0][3]);
  mma16816(c0, f[2], b[1][0], b[1][1]); mma16816(c1, f[3], b[1][2], b[1][3]);
#pragma unroll
  for (int k = 0; k < 4; k++) lds128(f[k], fa + (6 + k) * 512);
  mbar_wait(sb + ch::BAR_O, par);
  ldsm4t(b[0], ob + 1024); ldsm4t(b[1], ob + 1536);
  mma16816(c0, f[4], b[0][0], b[0][1]); mma16816(c1, f[5], b[0][2], b[0][3]);
  lds128(f[4], fa + 10 * 512); lds128(f[5], fa + 11 * 512);
  ldsm4t(b[0], ob + 2048);
  mma16816(c0, f[0], b[1][0], b[1][1]); mma16816(c1, f[1], b[1][2], b[1][3]);
  ldsm4t(b[1], ob + 2560);
  mma16816(c0, f[2], b[0][0], b[0][1]); mma16816(c1, f[3], b[0][2], b[0][3]);
  mma16816(c0, f[4], b[1][0], b[1][1]); mma16816(c1, f[5], b[1][2], b[1][3]);
  const uint32_t w0 = pack_f16((c0[0] + c1[0]) * iv.x, (c0[1] + c1[1]) * iv.y), w1 = pack_f16((c0[2] + c1[2]) * iv.x, (c0[3] + c1[3]) * iv.y);
  wo_red(p, w0, w1, last);
  wo_red_extra_p(px, w0, w1, last ? 31u : 0u);
}

#define LNFIRST 0
DEVI void chain_prepare(const bf16* __restrict__ x) {
  const int t = threadIdx.x, lane = t & 31, r0 = blockIdx.x * 11 + (t >> 5);
  asm volatile("griddepcontrol.wait;" ::: "memory");
  uint2 u[2][5];
#pragma unroll
  for (int i = 0; i < 10; i++) u[i / 5][i % 5] = __ldcg((const uint2*)(x + min(r0 + (i / 5) * 1056, S_LEN - 1) * DM + (i % 5) * 128 + lane * 4));
#pragma unroll
  for (int rr = 0; rr < 2; rr++) {
    float v[20];
#pragma unroll
    for (int i = 0; i < 5; i++) {
      v[4 * i] = __uint_as_float(u[rr][i].x << 16); v[4 * i + 1] = __uint_as_float(u[rr][i].x & 0xFFFF0000u);
      v[4 * i + 2] = __uint_as_float(u[rr][i].y << 16); v[4 * i + 3] = __uint_as_float(u[rr][i].y & 0xFFFF0000u);
    }
    if (r0 + rr * 1056 < S_LEN) ln_row(v, g_xn + (r0 + rr * 1056) * DM, lane);
  }
}
#define LNF 0
#define PWIN 3
#define PWIN1 4
#define PQP 0
#define PQN 1
#define LASTG 1
#define PSPL 1
DEVI void load_weights(uint32_t (&W)[160], uint32_t sb, int G, int w, int j, int layer) {
  using namespace ch;
  const uint32_t lane = threadIdx.x & 31;
  const uint32_t wa = sb + G * 40960 + afrag_off(w, lane);
#pragma unroll 1
  for (int i = 0; i < 5; i++) mbar_wait_long(sb + PB + i * 8, 0);
  if (threadIdx.x == 0) PT(0, 10);
#pragma unroll
  for (int kk = 0; kk < 20; kk++) ldsm4t_p(&W[80 + kk * 4], wa + 81920 + kk * 2048);
  uint32_t m = 0;
#pragma unroll
  for (int kk = 0; kk < 20; kk++) m = mag4(m, &W[80 + kk * 4]);
  publish_max(sb + WMX, m);
  bar_sync(8, 256);
  if (threadIdx.x == 0) mbar_arrive(sb + BAR_W1);
#pragma unroll 1
  for (int i = 7; i < 12; i++) mbar_wait_long(sb + PB + i * 8, 0);
  if (threadIdx.x == 0) PT(0, 9);
#pragma unroll
  for (int kk = 0; kk < 20; kk++) ldsm4t_p(&W[kk * 4], wa + kk * 2048);
  loaded(W[79]);
  bar_sync(8, 256);
  if (threadIdx.x == 0) mbar_arrive(sb + BAR_WK);
  m = 0;
  mbar_wait_long(sb + PB + (G == 0 ? 13 : 6) * 8, 0);
  if (threadIdx.x == 0) PT(0, 11);
  const uint32_t src = (G == 0 ? sb + WOF : sb + WOSTAGE + 2 * 24576) + afrag_off(w, lane);
  if (G == 1) {
    for (int kk = 0; kk < 12; kk++) { uint32_t f[4]; ldsm4t(f, src + kk * 2048); m = mag4(m, f); }
    publish_max(sb + WMX + 4, m);
    bar_sync(7, 384);
  }
  if (G == 1 || w < 2) {
    for (int kk = 0; kk < 12; kk++) {
      uint32_t f[4];
      ldsm4t(f, src + ((kk + 4 * j) % 12) * 2048);
      sts128(sb + WOF + ((G == 0 ? 4 + w : w) * 12 + kk) * 512 + lane * 16, f[0], f[1], f[2], f[3]);
      if (G == 0) m = mag4(m, f);
    }
  }
  if (G == 0) { publish_max(sb + WMX + 4, m); bar_sync(7, 384); }
  bar_sync(7, 384);
}
DEVI void arrange_wq(uint32_t sb, int G, int w, int layer) {
  using namespace ch;
  const uint32_t lane = threadIdx.x & 31;
  mbar_wait_long(sb + BAR_W2, 0);
  if (threadIdx.x == 0) PT(0, 15);
  if (WQR) {
    const uint32_t src = sb + WQ + G * 40960 + afrag_off(w, lane), dst = sb + WQ + G * 40960 + w * 512 + lane * 16;
#pragma unroll 1
    for (int r = 0; r < 5; r++) {
      uint32_t f[4][4];
#pragma unroll
      for (int i = 0; i < 4; i++) ldsm4t(f[i], src + (r * 4 + i) * 2048);
      bar_sync(14 + G, 128);
#pragma unroll
      for (int i = 0; i < 4; i++) sts128(dst + (r * 4 + i) * 2048, f[i][0], f[i][1], f[i][2], f[i][3]);
    }
    __syncwarp();
  }
}

namespace tl {
constexpr uint32_t FULL = 225280, EMPTY = FULL + 56;
#define TSL0 10
constexpr int RT0 = 13, SL0 = TSL0;
}
DEVI uint32_t fresh_tid() { uint32_t t; asm volatile("mov.u32 %0, %%tid.x;" : "=r"(t)); return t; }
DEVI int fresh_cta() { uint32_t t; asm volatile("mov.u32 %0, %%ctaid.x;" : "=r"(t)); const uint32_t h = t * 86 >> 8; return (t - h * 3) * 32 + h; }
DEVI void ldcg128(uint32_t (&r)[4], const void* p) { asm volatile("ld.global.cg.v4.u32 {%0,%1,%2,%3}, [%4];" : "=r"(r[0]), "=r"(r[1]), "=r"(r[2]), "=r"(r[3]) : "l"(p) : "memory"); }
#define TNST 3
#define TCV 0
#define TPOS 2
#define TEF 0
template <bool EF> DEVI void tma2d_h(uint32_t dst, const CUtensorMap* m, int c0, int c1, uint32_t bar) {
  if (EF) asm volatile("cp.async.bulk.tensor.2d.shared::cluster.global.mbarrier::complete_tx::bytes.L2::cache_hint [%0], [%1, {%3, %4}], [%2], %5;"
                       :: "r"(dst), "l"(m), "r"(bar), "r"(c0), "r"(c1), "l"(stream_policy()) : "memory");
  else tma2d(dst, m, c0, c1, bar);
}
DEVI void tail_load(uint32_t sb, Sync* sy, const CUtensorMap* moa, const CUtensorMap* mwo, int layer) {
  using namespace tl;
  (void)layer;
  const int i = fresh_cta(), a = i & 3, b = (i & 31) >> 2, rt = RT0 + (i >> 5);
  const bool last = rt == 15;
  const int nst = last ? 7 : TNST, npre = last ? 7 : 0;
  const uint32_t ab = last ? 8192 : 16384, stage = ab + 20480;
#pragma unroll 1
  for (int g = 0; g < npre; g++) { mbar_expect(sb + FULL + g * 8, stage); tma3d(sb + g * stage + ab, mwo, 0, (b * 12 + g) * 64, a * 5, sb + FULL + g * 8); }
  spin_count(&sy->o[rt * 16 + b], last ? 4 : 8);
  if (!last) XT(i, 0);
  fence_flag_to_bulk();
  int st = 0, par = 1;
#pragma unroll 1
  for (int g = 0; g < (last ? 24 : 12); g++) {
    const uint32_t dst = sb + st * stage, fb = sb + FULL + st * 8;
    const int k = (b * 12 + (g < 12 ? g : g < 19 ? g - 7 : g - 19)) * 64;
    if (g == 12) { spin_count(&sy->o[15 * 16 + 8 + b], 4); XT(i, 0); fence_flag_to_bulk(); }
    if (g >= npre) {
      mbar_wait_long(sb + EMPTY + st * 8, par);
      mbar_expect(fb, g >= 12 && g < 19 ? ab : stage);
      if (g < 12 || g >= 19) tma3d(dst + ab, mwo, 0, k, a * 5, fb);
    }
    tma2d_h<TEF>(dst, moa, k, rt * 128 + (g >= 12) * 64, fb);
    if (!last) tma2d_h<TEF>(dst + 8192, moa, k, rt * 128 + 64, fb);
    if (++st == nst) { st = 0; par ^= 1; }
  }
}
DEVI void tail_sum(uint32_t sb, Sync* sy, const bf16* __restrict__ xin, int layer) {
  using namespace tl;
  const int ct = fresh_tid(), lane = ct & 31, cw = __shfl_sync(0xffffffffu, ct >> 7, 0), w = ct >> 5 & 3;
  const int i = TCV ? __shfl_sync(0xffffffffu, fresh_cta(), 0) : blockIdx.x % 3 * 32 + blockIdx.x / 3, a = i & 3, b = (i & 31) >> 2, rt = RT0 + (i >> 5);
  const bool last = rt == 15;
  const uint32_t nst = last ? 7 : TNST, stage = last ? 28672 : 36864, ao = last ? 0 : cw * 8192, bo = stage - 20480, ost = sb + (last ? 200704 : 184320 + cw * 20480);
  float d[80];
#pragma unroll
  for (int n = 0; n < 80; n++) d[n] = 0.f;
  bar_sync(14, 288);
  if (last && cw) bar_sync(6, 256);
  uint32_t st = last && cw ? 5 : 0, par = last && cw, prev = 0;
#pragma unroll 1
  for (int c = 0; c < 12; c++) {
    mbar_wait_long(sb + FULL + st * 8, par);
    if (c == 0 && ct == 128) XT(i, 1);
    const uint64_t da = mkdesc(sb + st * stage + ao, 16, 1024, 1), db = mkdesc(sb + st * stage + bo, 4096, 512, 2);
    wg_fence();
#pragma unroll
    for (int k = 0; k < 4; k++) wgmma_n160_nt(d, da + k * 2, db + k * 64, c | k);
    wg_commit();
    if (c > 0) { wg_wait<1>(); if (lane == 0) mbar_arrive(prev); }
    prev = sb + EMPTY + st * 8;
    if (++st == nst) { st = 0; par ^= 1; }
  }
  if (last && !cw) bar_arrive(6, 256);
  const int rl = last ? cw * 64 + b * 8 + (ct >> 4 & 7) : b * 16 + (ct >> 4), q = ct & 15, r = rt * 128 + rl;
  const int c0 = r * DM + a * 160 + q * 8, c1 = c0 + 128 - (q & 12) * 8;
  uint32_t u[9][2][4];
  ldcg128(u[8][0], xin + c0); ldcg128(u[8][1], xin + c1);
  if (last && cw) bar_sync(5, 256);
  wg_wait<0>();
  if (lane == 0) mbar_arrive(prev);
  const uint32_t orow = w * 16 + (lane & 15), ob = ost + orow * 64;
#pragma unroll
  for (int n = 0; n < 10; n++)
    stsm4(ob + (n >> 1) * 4096 + ((((n & 1) * 2 + (lane >> 4)) ^ ((orow >> 1) & 3)) << 4), pack_bf16(d[8 * n], d[8 * n + 1]), pack_bf16(d[8 * n + 2], d[8 * n + 3]),
          pack_bf16(d[8 * n + 4], d[8 * n + 5]), pack_bf16(d[8 * n + 6], d[8 * n + 7]));
  fence_async();
  bar_sync(7 + cw, 128);
  const int sl0 = SL0 * 8 + (rt - RT0) * 64 + a * 16;
  if ((ct & 127) == 0) {
    bulk_store(g_sl + (size_t)(sl0 + cw * 8 + b) * 10240, ost, 20480);
    asm volatile("cp.async.bulk.commit_group; cp.async.bulk.wait_group 0;" ::: "memory");
    XT(i, 2 + cw);
    publish_bulk<WFEN>(&sy->wcnt[(rt * 4 + a) * 2 + cw]);
  }
  if ((ct & 127) == 32) spin_count(&sy->wcnt[(rt * 4 + a) * 2 + (rl >> 6)], 8);
  __syncwarp();
  bar_sync(7 + cw, 128);
  const bf16* sl = g_sl + (size_t)(sl0 + (rl >> 6) * 8) * 10240 + (rl & 63) * 32 + (((q & 3) ^ (rl >> 1 & 3)) << 3);
#pragma unroll
  for (int n = 0; n < 8; n++) { ldcg128(u[n][0], sl + n * 10240 + (q >> 2) * 2048); ldcg128(u[n][1], sl + n * 10240 + 8192); }
  if (last && !cw) bar_arrive(5, 256);
  if (ct == 128 && last) XT(128 + (i & 31), 0);
  sched_fence(layer >> 4);
  const uint32_t id = (lane >> 2) == (lane & 3) * 2 ? 0x3F80u : (lane >> 2) == (lane & 3) * 2 + 1 ? 0x3F800000u : 0u;
  float y[4][4], s1 = 0.f, s2 = 0.f;
#pragma unroll
  for (int e = 0; e < 16; e++) y[e >> 2][e & 3] = 0.f;
#pragma unroll
  for (int n = 0; n < 9; n++)
#pragma unroll
    for (int m = 0; m < 2; m++) { mma16816(y[2 * m], u[n][m], id, 0u); mma16816(y[2 * m + 1], u[n][m], 0u, id); }
#pragma unroll
  for (int m = 0; m < 2; m++) {
    const bool on = !m || q < 4;
    uint32_t z[4];
    float t1 = 0.f, t2 = 0.f;
#pragma unroll
    for (int e = 0; e < 4; e++) {
      z[e] = pack_bf16(y[2 * m + (e >> 1)][(e & 1) * 2], y[2 * m + (e >> 1)][(e & 1) * 2 + 1]);
      const float lo = __uint_as_float(z[e] << 16), hi = __uint_as_float(z[e] & 0xFFFF0000u);
      t1 += lo + hi; t2 = fmaf(lo, lo, fmaf(hi, hi, t2));
    }
    if (on) { s1 += t1; s2 += t2; }
    asm volatile("{.reg .pred p; setp.ne.u32 p, %5, 0; @p st.global.v4.u32 [%0], {%1,%2,%3,%4};}"
                 :: "l"(g_xa + (m ? c1 : c0)), "r"(z[0]), "r"(z[1]), "r"(z[2]), "r"(z[3]), "r"((uint32_t)on) : "memory");
  }
#pragma unroll
  for (int o = 1; o < 16; o <<= 1) { s1 += __shfl_xor_sync(0xffffffffu, s1, o); s2 += __shfl_xor_sync(0xffffffffu, s2, o); }
  asm volatile("{.reg .pred p; setp.ne.u32 p, %3, 0; @p red.relaxed.gpu.global.add.v2.f32 [%0], {%1,%2};}"
               :: "l"(&sy->rstat[r]), "f"(s1), "f"(s2), "r"((uint32_t)(q == 0)) : "memory");
  if (ct == 128 && last) XT(128 + (i & 31), 1);
  if (BFL) {
    bar_sync(7 + cw, 128);
    if ((ct & 127) == 0) red_release(&sy->pro[1 + rt - RT0]);
    if (ct == 128 && last) XT(128 + (i & 31), 2);
    __syncwarp();
  }
}

__global__ void __cluster_dims__(3, 1, 1) __launch_bounds__(384, 1)
chain_kernel(const __grid_constant__ CUtensorMap mq, const __grid_constant__ CUtensorMap mk, const __grid_constant__ CUtensorMap mv,
             const __grid_constant__ CUtensorMap mo, const __grid_constant__ CUtensorMap mx, const bf16* __restrict__ mem0, const bf16* __restrict__ xin, uint32_t zero, int layer
             , const __grid_constant__ CUtensorMap moa, const __grid_constant__ CUtensorMap mwo
             ) {
  using namespace ch;
  extern __shared__ __align__(1024) uint8_t smraw[];
  const uint32_t sb = smem_u32(smraw);
  const int tid = threadIdx.x;
  const int wg = __shfl_sync(0xffffffffu, tid >> 7, 0), w = __shfl_sync(0xffffffffu, (tid >> 5) & 3, 0);
  int h, j;
  asm("mov.u32 %0, %%clusterid.x;" : "=r"(h));
  asm("mov.u32 %0, %%cluster_ctarank;" : "=r"(j));
  h = __shfl_sync(0xffffffffu, h, 0); j = __shfl_sync(0xffffffffu, j, 0);
  const int T0 = j == 0 ? 0 : (j == 1 ? 14 : 27), NT = j == 0 ? 14 : 13;
  const uint32_t PD = PD_, XD = XD_, X1D = X1D_;
  constexpr uint32_t CS = 0, UP = 0, DMIN = 0, FL = 0, SD = 0;

  if (tid == 0) {
    mbar_init(sb + BAR_W1, 1); mbar_init(sb + BAR_W2, 1); mbar_init(sb + BAR_X0, 1); mbar_init(sb + BAR_X1, 1);
    mbar_init(sb + BAR_S, 6); mbar_init(sb + BAR_O, 1); mbar_init(sb + BAR_WK, 1); mbar_init(sb + BAR_XF, 12);
    for (int i = 0; i < 14; i++) mbar_init(sb + PB + i * 8, 1);
    sts64(sb + WMX, 0, 0);
    asm volatile("fence.mbarrier_init.release.cluster;" ::: "memory");
    mbar_expect(sb + BAR_W2, 81920);
    mbar_expect(sb + BAR_S, 1280); mbar_expect(sb + BAR_O, 2048);
  }
  asm volatile("griddepcontrol.launch_dependents;");
  GT(0, 0);
  __syncthreads();
  asm volatile("barrier.cluster.arrive.relaxed.aligned;" ::: "memory");
  asm volatile("barrier.cluster.wait.aligned;" ::: "memory");
  if (tid == 0) PT(0, 0);
  const char* arb = (const char*)g_ar;
  const uint32_t xdesc = desc_lo(sb + XB, 16);

  if (wg < 2) {
    asm volatile("setmaxnreg.inc.sync.aligned.u32 208;");
    if (!(BLN && layer) && !(WLN >> layer & 1)) chain_prepare(xin);
    if (WLN != 3) bar_arrive(9, 352);
    uint32_t W[160];
    load_weights(W, sb, wg, w, j, layer);
    float inv_sc = 1.0f;
    if (wg == 0) {
      const uint32_t lane = lane_id();
      code_pad<PAD0>(zero);
      mbar_wait_long(sb + BAR_X0, 0);
      if (tid == 0) PT(0, 12);
      if (LSH == 1) bar_sync(8, 256);
      if (!LSH) {
        tokens_finish<false>(sb, W, xdesc, w, lane, 0, &mx);
        if (tid == 0) PT(0, 13);
        if (!KS2) bar_arrive(8, 256);
        arrange_wq(sb, 0, w, layer);
      }
#pragma unroll 1
      for (int s = LSH ? -1 : 0; s < NSEG; s++) {
        float sc = 1.0f;
        if (!LSH || s >= 0) {
        uint32_t A0[2];
        {
          float q[4], k[4], v[4];
          const uint32_t ln = opq(lane), t16 = w * 512 + ln * 16;
          uint32_t f[NF][4], wq = sb + WQ + (WQR ? t16 : afrag_off(w, ln)), ba = sb + MEMB + ln * 16;
          proj_stage(f, wq);
          PIN(ba);
          proj_mem<0>(q, k, v, f, W, wq, ba, sb, w, s);
          const uint32_t qd = sb + QS + w * 256 + ln * 4;
          sts32(qd, pack_bf16(q[0] * inv_sc, q[1] * inv_sc)); sts32(qd + 128, pack_bf16(q[2] * inv_sc, q[3] * inv_sc));
          sts32(qd + 2048, pack_bf16(k[0] * inv_sc, k[1] * inv_sc)); sts32(qd + 2048 + 128, pack_bf16(k[2] * inv_sc, k[3] * inv_sc));
          sts128(sb + EX + t16, __float_as_uint(k[0]), __float_as_uint(k[1]), __float_as_uint(k[2]), __float_as_uint(k[3]));
          E1(1, __float_as_uint(v[0]) ^ __float_as_uint(q[0]));
          uint32_t qa = sb + QS + ((ln >> 3) & 1) * 1024 + ((ln >> 4) * 8 + (ln & 7)) * 16;
          PIN(qa);
          TS(0);
          bar_sync(2, 384);
          if (w == 3 && s < NSEG - 1) {
            uint32_t b0[4], b1[4], c0[4], c1[4];
            const uint32_t ka = sb + KP + ln * 16;
            ldsm4t(b0, ka); ldsm4t(c0, ka + 1024); ldsm4t(b1, ka + 512); ldsm4t(c1, ka + 1536);
#pragma unroll
            for (int i = 0; i < 4; i++) { b0[i] = add_bf16x2(b0[i], c0[i]); b1[i] = add_bf16x2(b1[i], c1[i]); }
            score_tile(sb, qa, b0, b1, Peers(sb, j), SX + j * 640 + ln * 4, ln);
          }
          uint32_t e[4];
          lds128(e, sb + EX + 2048 + t16);
          A0[0] = pack_bf16((v[0] + __uint_as_float(e[0])) * inv_sc, (v[1] + __uint_as_float(e[1])) * inv_sc);
          A0[1] = pack_bf16((v[2] + __uint_as_float(e[2])) * inv_sc, (v[3] + __uint_as_float(e[3])) * inv_sc);
          const uint32_t slab = slab_off(VT, w, ln);
          sts32(sb + slab, A0[0]); sts32(sb + slab + 640, A0[1]);
          bar_arrive(12, 384);
        }
        if (s == NSEG - 1) break;
        {
          const uint32_t ln = opq(lane);
          const uint32_t va = sb + VT + (16 * w + (ln & 15)) * 80 + 16 + (ln >> 4) * 16;
          const uint32_t sa = sb + SX + ln * 4, off = OB + w * 256 + ln * 4;
          const Peers pe(sb, j);
          uint32_t f1[4], f2[4];
          ldsm4(f1, va); ldsm4(f2, va + 32);
          TSX(TS(1));
          mbar_wait(sb + BAR_S, s & 1);
          TS(2);
          uint32_t u[3][5];
#pragma unroll
          for (int i = 0; i < 15; i++) u[i / 5][i % 5] = lds32(sa + (i % 5) * 128 + (i / 5) * 640);
          E1(2, u[0][0]);
          sched_fence(zero);
          uint32_t hs[5];
#pragma unroll
          for (int i = 0; i < 5; i++) hs[i] = hadd2(hadd2(u[0][i], u[1][i]), u[2][i]);
          uint32_t m2 = hmax2(hmax2(hmax2(hs[0], hs[1]), hmax2(hs[2], hs[3])), hs[4]);
          asm volatile("bar.arrive 13, 384;" : "+r"(m2) :: "memory");
          m2 = hmax2(m2, __byte_perm(m2, 0, 0x1032));
          m2 = hmax2(m2, __shfl_xor_sync(0xffffffffu, m2, 1));
          m2 = hmax2(m2, __shfl_xor_sync(0xffffffffu, m2, 2));
          TSX(TSD(3, m2));
          const float m4 = -4.0f * __low2float(*reinterpret_cast<__half2*>(&m2));
          uint32_t P[5];
#pragma unroll
          for (int i = 0; i < 5; i++) {
            const float2 x = __half22float2(*reinterpret_cast<__half2*>(&hs[i]));
            P[i] = pack_bf16(ex2(fmaf(x.x, 4.0f, m4)), ex2(fmaf(x.y, 4.0f, m4)));
          }
          float o[4] = {0.f, 0.f, 0.f, 0.f}, o2[4] = {0.f, 0.f, 0.f, 0.f}, o3[4] = {0.f, 0.f, 0.f, 0.f};
          mma16816(o2, f1, P[1], P[2]); mma1688(o, A0[0], A0[1], P[0]); mma16816(o3, f2, P[3], P[4]);
          const uint32_t w0 = pack_bf16((o[0] + o2[0]) + o3[0], (o[1] + o2[1]) + o3[1]), w1 = pack_bf16((o[2] + o2[2]) + o3[2], (o[3] + o2[3]) + o3[3]);
#pragma unroll
          for (int r = 0; r < 2; r++) { st_async32(pe.a[r] + off + (2 - r) * 1024, w0, pe.a[r] + BAR_O); st_async32(pe.a[r] + off + (2 - r) * 1024 + 128, w1, pe.a[r] + BAR_O); }
          E1(3, w0 ^ w1);
          sts32(sb + off, w0); sts32(sb + off + 128, w1);
          if (w == 3) {
            float z[4] = {0.f, 0.f, 0.f, 0.f}, z2[4] = {0.f, 0.f, 0.f, 0.f};
            const uint32_t one[4] = {0x3F803F80u, 0x3F803F80u, 0x3F803F80u, 0x3F803F80u};
            mma1688(z, one[0], one[1], P[0]); mma16816(z2, one, P[1], P[2]); mma16816(z, one, P[3], P[4]);
            if (ln < 4) sts64(sb + INV + ln * 8, __float_as_uint(rcp(z[0] + z2[0])), __float_as_uint(rcp(z[1] + z2[1])));
          }
          TS(4);
        }
        if (12 + w < NT) {
          const uint32_t ln = opq(lane);
          const char* pr = arb + ar_tile_off(T0 + 12 + w) + ln * 4; const char* px = arb + ar_extra_off(T0 + 12 + w);
          PINL(pr);
          wo_tile_smem<true>(sb, sb + WOF + (4 + w) * 6144 + ln * 16, sb + OB + ln * 16, s & 1, pr, px, ln == 31, sc);
        } else {
          bar_sync(9, 384);
          sc = __uint_as_float(lds32(sb + MX + 16));
          if (w == 3 && lane == 0) {
            mbar_expect(sb + BAR_S, 1280);
            if (!KS2 && !X1E && j == 1 && s + 2 < NSEG) {
              mbar_wait(sb + BAR_XF, s & 1);
              tma3d_mc(sb + XB + 20480, &mx, 0, (s + 2) * SEG, 5, sb + BAR_X1, 7);
            }
            mbar_wait(sb + BAR_O, s & 1);
            mbar_expect(sb + BAR_O, 2048);
          }
          __syncwarp();
        }
        TSX(TS(5));
        if (w == 1) SS(0);
        mbar_wait(sb + BAR_X0, (s + 1) & 1);
        if (w == 1) SS(1);
        bar_sync(4, 384);
        if (w == 1) SS(2);
        arb += AR_STEP_BYTES;
        }
        tokens_finish<true>(sb, W, xdesc, w, lane, s);
        TS(6);
        if (LSH && s < 0) {
          if (tid == 0) PT(0, 13);
          arrange_wq(sb, 0, w, layer);
        }
        inv_sc = __uint_as_float(0x7F000000u - __float_as_uint(sc));
      }
    } else {
      const uint32_t lane = lane_id();
      static_assert(!X0E && !KS2, "prologue");
      code_pad<PAD1>(zero);
#pragma unroll 1
      for (int pass = 0; pass < (LSH ? 1 : 2); pass++) {
        mbar_wait_long(sb + BAR_X1, pass);
        if (pass) bar_sync(8, 256);
        tokens_partial<0>(sb, PK, W, xdesc, w, lane);
        if (pass) break;
        mbar_wait(sb + BAR_X1, 0);
        tokens_partial<0>(sb, QS, W + 80, xdesc, w, lane);
        bar_sync(8, 256);
      }
      if (LSH) {
        if (w == 3 && lane == 0) { mbar_expect(sb + BAR_X1, 20480); tma3d(sb + XB + 20480, &mx, 0, SEG, 5, sb + BAR_X1); }
        __syncwarp();
      } else {
        if (tid == 128) PT(0, 14);
        arrange_wq(sb, 1, w, layer);
      }
#pragma unroll 1
      for (int s = LSH ? -1 : 0; s < NSEG; s++) {
        float sc = 1.0f;
        if (!LSH || s >= 0) {
        {
          float q[4], k[4], v[4];
          const uint32_t ln = opq(lane), t16 = w * 512 + ln * 16;
          uint32_t f[NF][4], wq = sb + WQ + 40960 + (WQR ? t16 : afrag_off(w, ln)), ba = sb + MEMB + 5120 + ln * 16;
          proj_stage(f, wq);
          PIN(ba);
          proj_mem<1>(q, k, v, f, W, wq, ba, sb, w, s);
          const uint32_t qd = sb + QS + 1024 + w * 256 + ln * 4;
          sts32(qd, pack_bf16(q[0] * inv_sc, q[1] * inv_sc)); sts32(qd + 128, pack_bf16(q[2] * inv_sc, q[3] * inv_sc));
          sts32(qd + 2048, pack_bf16(k[0] * inv_sc, k[1] * inv_sc)); sts32(qd + 2048 + 128, pack_bf16(k[2] * inv_sc, k[3] * inv_sc));
          sts128(sb + EX + 2048 + t16, __float_as_uint(v[0]), __float_as_uint(v[1]), __float_as_uint(v[2]), __float_as_uint(v[3]));
          TSX(TS(0));
          bar_sync(2, 384);
          uint32_t e[4];
          lds128(e, sb + EX + t16);
          const uint32_t slab = slab_off(KT, w, ln);
          sts32(sb + slab, pack_bf16((k[0] + __uint_as_float(e[0])) * inv_sc, (k[1] + __uint_as_float(e[1])) * inv_sc));
          sts32(sb + slab + 640, pack_bf16((k[2] + __uint_as_float(e[2])) * inv_sc, (k[3] + __uint_as_float(e[3])) * inv_sc));
        }
        if (s == NSEG - 1) { bar_arrive(12, 384); break; }
        if (w == 1) SS(3);
        if (KS2) mbar_wait(sb + BAR_X1, (s + 1) & 1);
        if (w == 1) SS(4);
        if (VL) {
          bar_arrive(12, 384); bar_arrive(13, 384);
          bar_sync(9, 384);
          tokens_partial<3>(sb, QS, W + 80, xdesc, w, lane);
        } else {
          bar_sync(5, 288);
          TSX(TS(1));
          tokens_partial<1>(sb, QS, W + 80, xdesc, w, lane);
        }
        if (!KS2 && X1E && j == 1 && w == 3 && s + 2 < NSEG) {
          if (opq(lane) == 0) {
            mbar_wait(sb + BAR_XF, s & 1);
            tma3d_mc(sb + XB + 20480, &mx, 0, (s + 2) * SEG, 5, sb + BAR_X1, 7);
          }
          __syncwarp();
        }
        TS(2);
        {
          const uint32_t ln = opq(lane);
          const char* pr = arb + ar_tile_off(T0 + 8 + w) + ln * 4; const char* px = arb + ar_extra_off(T0 + 8 + w);
          PINL(pr);
          wo_tile_smem<!VL>(sb, sb + WOF + w * 6144 + ln * 16, sb + OB + ln * 16, s & 1, pr, px, ln == 31, sc);
        }
        if (KS2) bar_sync(4, 384);
        else if (KORD) {
          if (s + 2 < NSEG) mbar_wait(sb + BAR_X1, s & 1);
          bar_sync(4, 384);
        } else {
          bar_arrive(4, 384);
        }
        arb += AR_STEP_BYTES;
        }
        if (!KS2 && !KORD) {
          if (s + 2 < NSEG) { if (LSH && s < 0) mbar_wait_long(sb + BAR_X1, 1); else mbar_wait(sb + BAR_X1, s & 1); }
          bar_sync(6, 256);
        }
        tokens_partial<2>(sb, PK, W, xdesc, w, lane);
        if (LSH && s < 0) {
          if (tid == 128) PT(0, 14);
          arrange_wq(sb, 1, w, layer);
        }
        if (X0E && j == 0 && w == 2 && s + 2 < NSEG) {
          if (opq(lane) == 0) {
            mbar_wait(sb + BAR_XF, (s + 1) & 1);
            const uint32_t t9 = clk32();
            while (clk32() - t9 < X0D_) {}
            tma3d_mc(sb + XB, &mx, 0, (s + 2) * SEG, 0, sb + BAR_X0, 7);
          }
          __syncwarp();
        }
        if (KS2 && j == 1 && w == 0 && s + 2 < NSEG) {
          if (opq(lane) == 0) {
            mbar_wait(sb + BAR_XF, s & 1);
            tma3d_mc(sb + XB + 20480, &mx, 0, (s + 2) * SEG, 5, sb + BAR_X1, 7);
          }
          __syncwarp();
        }
        TS(4);
        inv_sc = __uint_as_float(0x7F000000u - __float_as_uint(sc));
      }
    }
    asm volatile("barrier.cluster.arrive.relaxed.aligned;" ::: "memory");
    tail_sum(sb, &g_sync[layer], xin, layer);
  } else {
    asm volatile("setmaxnreg.dec.sync.aligned.u32 88;");
    const uint32_t lane = lane_id();
    uint32_t W[44];
    if (tid - 256 < 80) asm volatile("prefetch.global.L2 [%0];" :: "l"(mem0 + (tid - 256) * 64) : "memory");
    if (w == 3) {
      if (layer && LNF == 1) bar_sync(10, 64);
      const int win = layer ? PWIN1 : PWIN;
#pragma unroll
      for (int part = 0; part < 2; part++) {
        if (lane == 0) {
#pragma unroll
          for (int i = part ? 2 : 0; i < (part ? 14 : 2); i++) {
            const uint32_t bar = sb + PB + i * 8;
            if (i >= win) mbar_wait_long(bar - win * 8, 0);
            if (i == 12) mbar_wait_long(sb + BAR_W1, 0);
            if (PQP && layer && i >= PQP && i < PQP + 5 / PQN + (5 % PQN != 0))
              for (int n = (i - PQP) * PQN; n < min((i - PQP + 1) * PQN, 5); n++)
                asm volatile("cp.async.bulk.prefetch.tensor.2d.L2.global [%0, {%1, %2}];" :: "l"(&mq), "r"(h * DH + 64 * j), "r"(n * 128) : "memory");
            if (i < 5 || (i >= 7 && i < 12)) {
              mbar_expect(bar, 16384);
              if (i < 5) tma2d(sb + 81920 + i * 16384, &mv, h * DH + 64 * j, i * 128, bar);
              else tma2d(sb + (i - 7) * 16384, &mk, h * DH + 64 * j, (i - 7) * 128, bar);
            } else {
              const int bx = i < 7 ? i - 4 : (i - 12) * 3;
              mbar_expect(bar, 24576);
              tma2d(bx < 3 ? sb + WOSTAGE + bx * 24576 : sb + WOF, &mo, T0 * 16 + 64 * bx, h * DH, bar);
            }
          }
        }
        __syncwarp();
        if (part == 0 && layer && LNF == 2) bar_sync(10, 64);
      }
      if (lane == 0) {
        mbar_wait_long(sb + BAR_WK, 0);
        for (int i = 0; i < 2; i++) tma2d(sb + WQ + i * 16384, &mq, h * DH + 64 * j, i * 128, sb + BAR_W2);
      }
      __syncwarp();
    } else {
      if (!(BLN && layer) && !(WLN >> layer & 1)) {
        chain_prepare(xin);
        for (int i = blockIdx.x * 96 + tid - 256; i < (NSEG - 1) * 24 * 32; i += 96 * 96) ((uint4*)g_ar)[(i >> 5) * 64 + (i & 31)] = make_uint4(0, 0, 0, 0);
      } else if (BLN && w == 0) asm volatile("griddepcontrol.wait;" ::: "memory");
      if (WLN != 3) bar_sync(9, 352);
    }
    PT(0, 1);
    if (w == 0) {
      if (lane == 0) {
        if (layer) sts32(sb + MX + 24, __ldcg(&g_kw));
        if (!(WLN >> layer & 1)) red_release(&g_sync[layer].pro[0]);
        else if (layer && blockIdx.x == 0) {
          asm volatile("griddepcontrol.wait;" ::: "memory");
          if (WREL) red_release(&g_sync[1].pro[1]);
          else asm volatile("red.relaxed.gpu.global.add.u32 [%0], 1;" :: "l"(&g_sync[1].pro[1]) : "memory");
        }
      }
      PT(0, 2);
      __syncwarp();
      if (layer && LNF) bar_arrive(10, 64);
    }
    if (!(PSPL && layer) && !(WLN & 1) && tid == 256) spin_count(&g_sync[layer].pro[0], 96);
    __syncwarp();
    PT(0, 3);
    mbar_wait_long(sb + PB + 5 * 8, 0); mbar_wait_long(sb + PB + 12 * 8, 0);
    PT(0, 4);
    {
      const int i = lane >> 3, r = lane & 7;
      uint32_t m = 0;
#pragma unroll
      for (int kk = 0; kk < 12; kk++)
#pragma unroll
        for (int tt = 0; tt < 2; tt++) {
          const int tl = 2 * w + tt;
          const uint32_t src = sb + WOSTAGE + (tl >> 2) * 24576 + (((kk + 4 * j) % 12) * 16 + (i >> 1) * 8 + r) * 128 + ((((tl & 3) * 2 + (i & 1)) ^ r) << 4);
          const int q = kk * 2 + tt;
          if (q >= 13) { ldsm4t_p(&W[(q - 13) * 4], src); m = mag4(m, &W[(q - 13) * 4]); }
          else { uint32_t f[4]; ldsm4t(f, src); sts128(sb + (q < 12 ? WOF2 + (w * 12 + q) * 512 : WOF3 + w * 512) + lane * 16, f[0], f[1], f[2], f[3]); m = mag4(m, f); }
        }
      publish_max(sb + WMX + 4, m);
    }
    bar_sync(7, 384);
    PT(0, 5);
    if (tid == 256 && !layer) {
      const float2 mm = lds64f(sb + WMX);
      asm volatile("st.relaxed.gpu.global.u32 [%0], %1;" :: "l"(&g_sync[layer].wmax[blockIdx.x]), "r"(0x10000u | (__float_as_uint(mm.x) >> 7 << 8) | (__float_as_uint(mm.y) >> 7)) : "memory");
    }
    uint32_t m0[3][8];
#pragma unroll
    for (int i = 0; i < 24; i++) m0[i >> 3][i & 7] = __ldg((const uint32_t*)(mem0 + (i & 7) * DM) + min(tid - 256 + (i >> 3) * 128, DM / 2 - 1));
    if (tid == 352) {
      if (BLN) asm volatile("griddepcontrol.wait;" ::: "memory");
      else if (WLN >> layer & 1) spin_count(&g_sync[layer].pro[2], 4);
      else if (PSPL && layer) spin_count(&g_sync[layer].pro[0], 96);
      if (XFEN == 0) asm volatile("fence.proxy.async;" ::: "memory");
      if (XFEN == 1) asm volatile("fence.proxy.async.global;" ::: "memory");
      mbar_expect(sb + BAR_X1, 20480); tma3d(sb + XB + 20480, &mx, 0, 0, 5, sb + BAR_X1);
      mbar_expect(sb + BAR_X0, 20480); tma3d(sb + XB, &mx, 0, 0, 0, sb + BAR_X0);
      for (int i = 2; i < 5; i++) tma2d(sb + WQ + i * 16384, &mq, h * DH + 64 * j, i * 128, sb + BAR_W2);
    }
    __syncwarp();
    bar_sync(7, 384);
    PT(0, 6);
    uint32_t wv[3];
    if (w == 0 && !layer)
#pragma unroll
      for (int i = 0; i < 3; i++) asm volatile("ld.relaxed.gpu.global.u32 %0, [%1];" : "=r"(wv[i]) : "l"(&g_sync[layer].wmax[lane + i * 32]) : "memory");
    {
      int em;
      uint32_t m = 0;
#pragma unroll
      for (int i = 0; i < 3; i++) {
        const int p = tid - 256 + i * 128;
        if (p < DM / 2) {
          uint32_t lo[4], hi[4];
#pragma unroll
          for (int q = 0; q < 4; q++) { lo[q] = __byte_perm(m0[i][2 * q], m0[i][2 * q + 1], 0x5410); hi[q] = __byte_perm(m0[i][2 * q], m0[i][2 * q + 1], 0x7632); }
          sts128(sb + MEMB + p * 32, lo[0], lo[1], lo[2], lo[3]); sts128(sb + MEMB + p * 32 + 16, hi[0], hi[1], hi[2], hi[3]);
        }
#pragma unroll
        for (int q = 0; q < 8; q++) m = __vmaxu2(m, m0[i][q] & 0x7FFF7FFFu);
      }
      em = __reduce_max_sync(0xffffffffu, (int)(max(m & 0xFFFFu, m >> 16) >> 7) - 126);
      if (lane == 0) sts32(sb + MX + w * 4, em);
    }
    if ((WLN >> layer & 1) && tid == 352) spin_count(&g_sync[layer].pro[0], 128);
    __syncwarp();
    PT(0, 7);
    bar_arrive(1, 384);
    bar_sync(3, 384);
    if (w == 0 && !layer) {
      for (int n = 0; n < 4000000 && !__all_sync(0xffffffffu, (wv[0] & wv[1] & wv[2]) >> 16); n++) {
#pragma unroll
        for (int i = 0; i < 3; i++) asm volatile("ld.relaxed.gpu.global.u32 %0, [%1];" : "=r"(wv[i]) : "l"(&g_sync[layer].wmax[lane + i * 32]) : "memory");
      }
      const int ev = __reduce_max_sync(0xffffffffu, max(max(wv[0] >> 8 & 255, wv[1] >> 8 & 255), wv[2] >> 8 & 255));
      const int eo = __reduce_max_sync(0xffffffffu, max(max(wv[0] & 255, wv[1] & 255), wv[2] & 255));
      if (lane == 0) {
        sts32(sb + MX + 24, 245 - ev - eo);
        if (blockIdx.x == 0) g_kw = 245 - ev - eo;
      }
      __syncwarp();
    }
    int dly = PD;
    PT(0, 8);
    for (int s = 0; s < NSEG; s++) {
      const uint32_t t0 = clk32();
      TS(0);
      {
        uint32_t b0[4], b1[4];
        const uint32_t ln = opq(lane);
        const uint32_t ka = sb + KT + ln * 80 + (1 + w) * 16;
        ldsm4t(b0, ka); ldsm4t(b1, ka + 2560);
        if (w == 0 && ln == 0 && s + 1 < NSEG) {
          if (!X0E && j == 0) {
            mbar_wait(sb + BAR_XF, s & 1);
            while (clk32() - t0 < XD) {}
            tma3d_mc(sb + XB, &mx, 0, (s + 1) * SEG, 0, sb + BAR_X0, 7);
          }
          if (s + 2 < NSEG - 1 && !(FL & 2)) asm volatile("prefetch.global.L2 [%0];" :: "l"(arb + 2 * AR_STEP_BYTES + ar_line_off(h * 3 + j)) : "memory");
          if (PFW && layer == 0 && s >= PFW && s < PFW + 10) tma2d_prefetch(s & 1 ? &mk : &mv, h * DH + 64 * j, ((s - PFW) >> 1) * 128);
          if (j == 2 && h == (s & 31) && s + 3 < NSEG) { tma3d_prefetch(&mx, 0, (s + 3) * SEG, 0); tma3d_prefetch(&mx, 0, (s + 3) * SEG, 5); }
        }
        __syncwarp();
        uint32_t qa = sb + QS + ((ln >> 3) & 1) * 1024 + ((ln >> 4) * 8 + (ln & 7)) * 16, off = SX + j * 640 + (1 + w) * 128 + ln * 4;
        PIN(qa); PIN(off);
        bar_sync(2, 384);
        if (s == NSEG - 1) break;
        score_tile(sb, qa, b0, b1, Peers(sb, j), off, ln);
        bar_sync(12, 384);
        if (SD) bar_sync(13, 384);
        if (w == 1 && ln == 0 && !(FL & 1)) {
          store_slabs(sb, s, h, j);
        }

        __syncwarp();
      }
      if (w == 0) {
        uint32_t v[4]; lds128(v, sb + MX);
        const int kw = lds32(sb + MX + 24);
        const int em = max(max(max((int)v[0], (int)v[1]), max((int)v[2], (int)v[3])), 1);
        const int e = min(max(kw - em, -120), 120);
        if (opq(lane) == 0) { sts32(sb + MX + 16, (uint32_t)(e + 127) << 23); sts32(sb + MX + 20, 0u); }
      }
      if (!SD) bar_sync(13, 384);
      uint32_t tref;
      {
        float c0[4] = {0.f, 0.f, 0.f, 0.f}, c1[4] = {0.f, 0.f, 0.f, 0.f}, d0[4] = {0.f, 0.f, 0.f, 0.f}, d1[4] = {0.f, 0.f, 0.f, 0.f};
        uint32_t f[4][4], b[2][4];
        const uint32_t ln = opq(lane);
        const uint32_t fa = sb + WOF2 + w * 6144 + ln * 16, ob = sb + OB + ln * 16;
#pragma unroll
        for (int i = 0; i < 4; i++) lds128(f[i], fa + i * 512);
        if (w == 1) SS(5);
        asm volatile("cp.async.bulk.wait_group.read 0;" ::: "memory");
        if (w == 1) SS(6);
        bar_sync(9, 384);
        ldsm4t(b[0], ob); ldsm4t(b[1], ob + 512);
        mma16816(c0, f[0], b[0][0], b[0][1]); mma16816(c1, f[1], b[0][0], b[0][1]);
        lds128(f[0], fa + 2048); lds128(f[1], fa + 2560);
        mma16816(d0, f[2], b[0][2], b[0][3]); mma16816(d1, f[3], b[0][2], b[0][3]);
        lds128(f[2], fa + 3072); lds128(f[3], fa + 3584);
        mma16816(c0, f[0], b[1][0], b[1][1]); mma16816(c1, f[1], b[1][0], b[1][1]);
        mma16816(d0, f[2], b[1][2], b[1][3]); mma16816(d1, f[3], b[1][2], b[1][3]);
#pragma unroll
        for (int i = 0; i < 4; i++) lds128(f[i], fa + (8 + i) * 512);
        mbar_wait(sb + BAR_O, s & 1);
        ldsm4t(b[0], ob + 1024);
        E1(4, b[0][0]);
        mma16816(c0, f[0], b[0][0], b[0][1]); mma16816(c1, f[1], b[0][0], b[0][1]);
        mma16816(d0, f[2], b[0][2], b[0][3]); mma16816(d1, f[3], b[0][2], b[0][3]);
        ldsm4t(b[0], ob + 1536); lds128(f[0], sb + WOF3 + w * 512 + ln * 16); ldsm4t(f[1], ob + 2048); ldsm4t(f[2], ob + 2560);
        float2 iv = lds64f(sb + INV + (ln & 3) * 8);
        const float sc = __uint_as_float(lds32(sb + MX + 16));
        sched_fence(zero);
        mma16816(c1, &W[0], b[0][0], b[0][1]); mma16816(d0, &W[4], b[0][2], b[0][3]); mma16816(d1, &W[8], b[0][2], b[0][3]);
        mma16816(c0, f[0], b[0][0], b[0][1]);
        const char* pr = arb + ar_tile_off(T0 + 2 * w) + ln * 4;
        PINL(pr);
        iv.x *= sc; iv.y *= sc;
        mma16816(c1, &W[16], f[1][0], f[1][1]); mma16816(d0, &W[20], f[1][2], f[1][3]); mma16816(d1, &W[24], f[1][2], f[1][3]);
        mma16816(c0, &W[12], f[1][0], f[1][1]);
        mma16816(c1, &W[32], f[2][0], f[2][1]); mma16816(d0, &W[36], f[2][2], f[2][3]); mma16816(d1, &W[40], f[2][2], f[2][3]);
        mma16816(c0, &W[28], f[2][0], f[2][1]);
        const uint32_t w2 = pack_f16((c1[0] + d1[0]) * iv.x, (c1[1] + d1[1]) * iv.y), w3 = pack_f16((c1[2] + d1[2]) * iv.x, (c1[3] + d1[3]) * iv.y);
        wo_red(pr + ((T0 & 1) ? 768 : 256), w2, w3, ln == 31);
        const uint32_t w0 = pack_f16((c0[0] + d0[0]) * iv.x, (c0[1] + d0[1]) * iv.y), w1 = pack_f16((c0[2] + d0[2]) * iv.x, (c0[3] + d0[3]) * iv.y);
        E1(5, w0 ^ w2);
        wo_red(pr, w0, w1, ln == 31);
        wo_red_extra_p(arb + ar_extra_off(T0 + 2 * w + 1), w2, w3, ln);
        wo_red_extra_p(arb + ar_extra_off(T0 + 2 * w), w0, w1, ln);
        if (TSYNC) bar_sync(4, 384); else bar_arrive(4, 384);
        tref = clk32();
      }
      TSV(2, tref); TS(3);
      if (w == 1 && opq(lane) == 0) {
        asm volatile("cp.async.bulk.wait_group 0;" ::: "memory");
        publish_bulk<0>(&g_sync[layer].kv[s * NH + h]);
      }
      __syncwarp();
      {
        const uint32_t m = ar_read(arb, sb, w, lane, zero, tref, dly, s);
        dly = lds32(sb + MX + 20) ? dly + (int)UP : max(dly - (int)CS, (int)DMIN);
        if (w == 3) TSV(1, dly);
        const int em = __reduce_max_sync(0xffffffffu, (int)(max(m & 0xFFFFu, m >> 16) >> 10) - 13 + 127 - (int)(lds32(sb + MX + 16) >> 23));
        if (opq(lane) == 0) sts32(sb + MX + w * 4, em);
      }
      arb += AR_STEP_BYTES;
    }
    asm volatile("barrier.cluster.arrive.relaxed.aligned;" ::: "memory");
    if (fresh_tid() >= 352) {
      if (fresh_tid() == 352) {
        asm volatile("prefetch.tensormap [%0];" :: "l"(&mwo) : "memory"); asm volatile("prefetch.tensormap [%0];" :: "l"(&moa) : "memory");
        const uint32_t n = fresh_cta() < 64 ? 8 : 4;
        for (int i = 0; i < 7; i++) { mbar_init(sb + tl::FULL + i * 8, 1); mbar_init(sb + tl::EMPTY + i * 8, n); }
        asm volatile("fence.mbarrier_init.release.cluster;" ::: "memory");
      }
      __syncwarp();
      bar_arrive(14, 288);
    }
    bar_sync(12, 384);
    if (LASTG) {
      bf16* kvp = g_kv + ((size_t)((NSEG - 1) * NH + h) * 2 * DH + 64 * j) * NKEY;
#pragma unroll
      for (int k = 0; k < 5; k++) {
        const int u = k * 128 + tid - 256;
        uint32_t v[4];
        lds128(v, sb + KT + u * 16);
        __stcg((uint4*)(kvp + (u < 320 ? u * 8 : DH * NKEY + (u - 320) * 8)), make_uint4(v[0], v[1], v[2], v[3]));
      }
      bar_sync(10, 128);
      if (tid == 256 + 32) {
        asm volatile("cp.async.bulk.wait_group 0;" ::: "memory");
        red_release(&g_sync[layer].kv[(NSEG - 1) * NH + h]);
        GT(0, 1);
        if (TPOS < 2) tail_load(sb, &g_sync[layer], &moa, &mwo, layer);
      }
      __syncwarp();

    } else if (tid == 256 + 32) {
      store_slabs(sb, NSEG - 1, h, j);
      asm volatile("cp.async.bulk.wait_group 0;" ::: "memory");
      publish_bulk<WFEN>(&g_sync[layer].kv[(NSEG - 1) * NH + h]);
    }
  }
  if (TPOS) {
    const uint32_t t = fresh_tid();
    uint32_t sb2 = smem_u32(smraw);
    if (TPOS == 3) sb2 += zero;
    if (TPOS >= 2 && t == 288) tail_load(sb2, &g_sync[layer], &moa, &mwo, layer);
    __syncwarp();
  }
  asm volatile("barrier.cluster.wait.aligned;" ::: "memory");
}

DEVI void bulk_load(uint32_t dst, const void* g, uint32_t bytes, uint32_t bar) {
  if (EVF & 2) asm volatile("cp.async.bulk.shared::cluster.global.mbarrier::complete_tx::bytes.L2::cache_hint [%0], [%1], %2, [%3], %4;" :: "r"(dst), "l"(g), "r"(bytes), "r"(bar), "l"(stream_policy()) : "memory");
  else asm volatile("cp.async.bulk.shared::cluster.global.mbarrier::complete_tx::bytes [%0], [%1], %2, [%3];" :: "r"(dst), "l"(g), "r"(bytes), "r"(bar) : "memory");
}
DEVI void bulk_load_plain(uint32_t dst, const void* g, uint32_t bytes, uint32_t bar) {
  asm volatile("cp.async.bulk.shared::cluster.global.mbarrier::complete_tx::bytes [%0], [%1], %2, [%3];" :: "r"(dst), "l"(g), "r"(bytes), "r"(bar) : "memory");
}
DEVI void tma3d_store(const CUtensorMap* m, uint32_t src, int c0, int c1, int c2) {
  if (EVF & 4) asm volatile("cp.async.bulk.tensor.3d.global.shared::cta.bulk_group.L2::cache_hint [%0, {%2, %3, %4}], [%1], %5;" :: "l"(m), "r"(src), "r"(c0), "r"(c1), "r"(c2), "l"(stream_policy()) : "memory");
  else asm volatile("cp.async.bulk.tensor.3d.global.shared::cta.bulk_group [%0, {%2, %3, %4}], [%1];" :: "l"(m), "r"(src), "r"(c0), "r"(c1), "r"(c2) : "memory");
}
namespace wk {
constexpr uint32_t STAGE = 40960, NST = 4, OST = NST * STAGE;
constexpr uint32_t MISC = OST + 49152;
constexpr uint32_t FULL = MISC, EMPTY = MISC + 32, TFULL = MISC + 64, TEMPTY = MISC + 80, TASK = MISC + 96;
constexpr uint32_t DONE = MISC + 104, FREE = MISC + 120, DTASK = MISC + 136, FIN = MISC + 144, DSLOT = MISC + 152;
constexpr uint32_t CGO = MISC + 160;
constexpr uint32_t LBAR = MISC + 168, TL = MISC + 176;
constexpr uint32_t SMEM = TL + 5136;
#define NP2 10
constexpr int NZ = 16, NP = NZ + 80 + NP2, NQ = 512;
#define S15 8
#define SPLITS rt < RT_SPLIT ? 1 : rt < 11 ? 2 : rt < 13 ? 4 : rt < 15 ? 8 : S15
__host__ __device__ constexpr int split(int rt) { return SPLITS; }
__host__ __device__ constexpr int count_w(int rt) { return rt < 0 ? 0 : 4 * split(rt) + count_w(rt - 1); }
constexpr int NW = count_w(15);
__host__ __device__ constexpr int first_slice(int rt) { return rt <= RT_SPLIT ? 0 : first_slice(rt - 1) + split(rt - 1); }
static_assert(first_slice(16) <= NSL, "slice buffer");
DEVI int slice_of(int rt) {
  constexpr int f9 = first_slice(9), f10 = first_slice(10), f11 = first_slice(11), f12 = first_slice(12), f13 = first_slice(13), f14 = first_slice(14), f15 = first_slice(15);
  return rt < 9 ? 0 : rt == 9 ? f9 : rt == 10 ? f10 : rt == 11 ? f11 : rt == 12 ? f12 : rt == 13 ? f13 : rt == 14 ? f14 : f15;
}
static_assert(RT_SPLIT >= 8, "slice_of");
enum { T_Q, T_W, T_P, T_END, T_G, T_F };
#define RG0 14
#define RG1 13
#define BKVZ (CTAIL ? 12 : 14)
#define PFB 0
#define WLD 2
#define OKEEP 13
#define OPF 0
#define SENT 1
#define FLATE 10
#define WGRID 0
#define PFRONT 0
#define PTAIL 0
#define WPRE 0
#define PFF (CTAIL ? 12 : 14)
#define PFACC 0
#define P2LATE 0
#define LAGK0 16
#define LAGK1 16
#define DEFW0 13
#define DEFW1 13
#define NWE0 0
#define NWE1 0
#define SLATE0 1
#define SLATE1 1
#define SLATE 1
#define FLAG 3
#define FWARM 0
#define SLEV 1
#define SLC 1
#define LFAST 1
#define SCOUT0 13
#define SCOUT1 13
#define NSCOUT 0
#define FVOL 1
#define FXT 10
#define FCGO 0
#define P1M 1
#define TMPF 1
#define ZPRE 1
#define CLQ 8
#define CLW 3
struct Task { int type, rt, a, b; };
DEVI int wtasks(int rt) { return 4 * split(rt); }
DEVI int lsplit(int rt) { return 31 - __clz(split(rt)); }
DEVI Task decode(int id) { return {id >> 24, (id >> 16) & 255, id & 255, (id >> 8) & 255}; }
struct __align__(16) TaskList { int n, tail0, late0, pad; uint32_t t[1280]; };
constexpr void add_w(TaskList& l, int rt, int i0 = 0, int i1 = 64) {
  for (int b = 0; b < split(rt); b++) for (int a = 0; a < 4; a++) if (b * 4 + a >= i0 && b * 4 + a < i1) l.t[l.n++] = (T_W << 24) | (rt << 16) | (b << 8) | a;
}
constexpr void add_f(TaskList& l, int rt, int i0 = 0, int i1 = 64) {
  if (rt >= 0 && split(rt) > 1) for (int a = 0; a < 4; a++) for (int b = 0; b < 128 / FROWS; b++)
    if (a * (128 / FROWS) + b >= i0 && a * (128 / FROWS) + b < i1) l.t[l.n++] = (T_F << 24) | (rt << 16) | (b << 8) | a;
}
constexpr TaskList make_list(int layer) {
  TaskList l = {};
  const int rg = layer == 0 ? RG0 : RG1, lagk = layer == 0 ? LAGK0 : LAGK1, defw = layer == 0 ? DEFW0 : DEFW1, nwe = layer == 0 ? NWE0 : NWE1;
  if (layer == 0) for (int i = NZ; i < (P2LATE ? NZ + 80 : NP) - PTAIL && i < NZ + PFRONT; i++) l.t[l.n++] = (T_P << 24) | i;
  for (int rt = 15; rt >= rg; rt--) for (int h = 0; h < NH; h++) l.t[l.n++] = (T_G << 24) | (rt << 16) | h;
  if (layer == 0) for (int i = NZ + PFRONT; i < (P2LATE ? NZ + 80 : NP) - PTAIL; i++) l.t[l.n++] = (T_P << 24) | i;
  for (int i = 0; i < NZ; i++) l.t[l.n++] = (T_P << 24) | i;
  if (layer == 0 && P2LATE) for (int i = NZ + 80; i < NP; i++) l.t[l.n++] = (T_P << 24) | i;
  for (int rt = 0; rt < 16; rt++) {
    if (rt == 15) l.tail0 = l.n;
    for (int h = 0; h < NH; h++) l.t[l.n++] = (T_Q << 24) | (rt << 16) | ((rt >= rg) << 8) | h;
    if (rt > 0 && rt - 1 < lagk && rt - 1 < defw) add_w(l, rt - 1);
    if (rt >= lagk && rt < defw) add_w(l, rt);
    if (rt == 14 && defw < 14) add_w(l, defw, 0, nwe);
    if (rt == (layer ? SCOUT1 : SCOUT0)) for (int i = 0; i < NSCOUT; i++) l.t[l.n++] = (T_END << 24) | 1;
    if (FWARM && rt - FLAG + 1 == RT_SPLIT) add_f(l, RT_SPLIT, 0, 1);
    if (rt - FLAG < FLATE) add_f(l, rt - FLAG, FWARM && rt - FLAG == RT_SPLIT ? 1 : 0);
  }
  if (layer == 0) for (int i = NP - PTAIL; i < NP; i++) l.t[l.n++] = (T_P << 24) | i;
  if (CTAIL) {
    l.late0 = 1 << 20;
    for (int rt = FLATE; rt < tl::RT0; rt++) add_f(l, rt);
    return l;
  }
  constexpr int W15E = 4 * S15 - 32;
  if (SLATE) add_w(l, 15, 0, W15E);
  if (SLATE && (layer ? SLATE1 : SLATE0) == 2) {
    l.late0 = l.n;
    add_w(l, 14); add_w(l, 15, W15E); add_f(l, 10); add_f(l, 11);
    for (int rt = 12; rt < 16; rt++) add_f(l, rt);
    return l;
  } else if (SLATE) {
    l.late0 = l.n;
    add_w(l, 13); add_w(l, 14); add_w(l, 15, W15E);
  } else {
    for (int rt = defw; rt < 16; rt++) add_w(l, rt, rt == defw && defw < 14 ? nwe : 0);
  }
  for (int rt = FLATE; rt < 16; rt++) add_f(l, rt);
  return l;
}
__device__ const TaskList d_tasks[2] = {make_list(0), make_list(1)};
__host__ __device__ constexpr uint32_t first_task(int layer, int b) {
  if (layer == 0 && PTAIL < NP - NZ) { if (b < PFRONT) return (T_P << 24) | (NZ + b); b -= PFRONT; }
  return (T_G << 24) | ((15 - (b >> 5)) << 16) | (b & 31);
}
constexpr int NLATE = SLATE && !CTAIL ? 96 : 0;
static_assert(CTAIL || !BFL, "flags");
static_assert(!CTAIL || (first_slice(tl::RT0) == tl::SL0 && DEFW0 == tl::RT0 && DEFW1 == tl::RT0 && S15 == 8 && !WGRID && BSL && SLC && LASTG), "tail of the recurrence kernel");
__host__ __device__ constexpr uint32_t late_task(int layer, int i) {
  if ((layer ? SLATE1 : SLATE0) == 2) return i < 64 ? (T_W << 24) | ((14 + (i >> 5)) << 16) | ((((i & 31) >> 2) + (i >> 5) * (S15 - 8)) << 8) | (i & 3)
                                                    : (T_F << 24) | ((6 + (i >> 4)) << 16) | ((i & 3) << 8) | ((i & 15) >> 2);
  return (T_W << 24) | ((13 + (i >> 5)) << 16) | ((((i & 31) >> 2) + (i >> 6) * (S15 - 8)) << 8) | (i & 3);
}
constexpr bool check_first() {
  for (int layer = 0; layer < 2; layer++) {
    const TaskList l = make_list(layer);
    for (int b = 0; b < 64; b++) if (l.t[b] != first_task(layer, b)) return false;
    for (int b = 0; b < NLATE; b++) if (l.t[l.late0 + b] != late_task(layer, b)) return false;
  }
  return true;
}
static_assert(check_first(), "first_task does not match the list");
}

#define WQP 0
#define WQP_D 0
#define WTR 1
DEVI void pass_stage(uint32_t sb, uint32_t it, int lane) {
  mbar_wait_long(sb + wk::FULL + (it % wk::NST) * 8, (it / wk::NST) & 1);
  if (lane == 0) mbar_arrive(sb + wk::EMPTY + (it % wk::NST) * 8);
}
#define AT(i, x)
template <int NT>
DEVI void attend(uint32_t sb, const uint32_t (&q)[48], int cw, int w, int lane, uint32_t itk, uint32_t itv, uint32_t mid, uint32_t nd) {
  using namespace wk;
  const int g = lane >> 2, t = lane & 3;
  AT(0, q[0]);
  float sc[NT][4];
#pragma unroll
  for (int i = 0; i < NT * 4; i++) sc[i >> 2][i & 3] = 0.f;
  const uint32_t ka = sb + (itk % NST) * STAGE + (w >> 1) * 15360 + lane * 80;
#pragma unroll
  for (int k2 = 0; k2 < 6; k2++) {
    uint32_t b[NT][4];
#pragma unroll
    for (int n = 0; n < NT; n++) ldsm4t(b[n], ka + k2 * 2560 + n * 16);
#pragma unroll
    for (int n = 0; n < NT; n++) mma16816(sc[n], &q[k2 * 8], b[n][0], b[n][1]);
#pragma unroll
    for (int n = 0; n < NT; n++) mma16816(sc[n], &q[k2 * 8 + 4], b[n][2], b[n][3]);
  }
  AT(1, __float_as_uint(sc[NT - 1][0]) ^ __float_as_uint(sc[0][0]));
  __syncwarp();
  if (lane == 0) mbar_arrive(sb + EMPTY + (itk % NST) * 8);
  const float cs = 0.07216878364870322f * 1.4426950408889634f;
  const int r0 = NMEM + (NT == 5 ? 16 : 0) + g;
  float m0 = -INFINITY, m1 = -INFINITY;
#pragma unroll
  for (int n = 0; n < NT; n++)
#pragma unroll
    for (int e = 0; e < 2; e++) {
      const int key = n * 8 + 2 * t + e;
      sc[n][e] = (n < NT - 2 || key <= r0) ? sc[n][e] * cs : -INFINITY; sc[n][2 + e] = (n < NT - 1 || key <= r0 + 8) ? sc[n][2 + e] * cs : -INFINITY;
      m0 = fmaxf(m0, sc[n][e]); m1 = fmaxf(m1, sc[n][2 + e]);
    }
  m0 = fmaxf(m0, __shfl_xor_sync(0xffffffffu, m0, 1)); m1 = fmaxf(m1, __shfl_xor_sync(0xffffffffu, m1, 1));
  m0 = fmaxf(m0, __shfl_xor_sync(0xffffffffu, m0, 2)); m1 = fmaxf(m1, __shfl_xor_sync(0xffffffffu, m1, 2));
  uint32_t P[2 * NT]; float s0 = 0.f, s1 = 0.f;
#pragma unroll
  for (int n = 0; n < NT; n++) {
    const float a = ex2(sc[n][0] - m0), b = ex2(sc[n][1] - m0), c = ex2(sc[n][2] - m1), e = ex2(sc[n][3] - m1);
    s0 += a + b; s1 += c + e; P[2 * n] = pack_bf16(a, b); P[2 * n + 1] = pack_bf16(c, e);
  }
  s0 += __shfl_xor_sync(0xffffffffu, s0, 1); s1 += __shfl_xor_sync(0xffffffffu, s1, 1);
  s0 += __shfl_xor_sync(0xffffffffu, s0, 2); s1 += __shfl_xor_sync(0xffffffffu, s1, 2);
  const float i0 = rcp(s0), i1 = rcp(s1);
  AT(2, __float_as_uint(i0) ^ __float_as_uint(i1));
  mbar_wait_long(sb + FREE + cw * 8, (nd & 1) ^ 1);
  AT(3, 0);
  if (mid != 0xFFFFFFFFu) pass_stage(sb, mid, lane);
  mbar_wait_long(sb + FULL + (itv % NST) * 8, (itv / NST) & 1);
  AT(4, 0);
  const uint32_t vb = sb + (itv % NST) * STAGE + (w >> 1) * 15360;
  const uint32_t va = vb + (lane & 7) * 80 + (lane >> 3) * 16, vc = vb + lane * 80 + 64;
  const uint32_t orow = w * 16 + (lane & 15), ob = sb + OST + cw * 24576 + orow * 128;
#pragma unroll
  for (int n8 = 0; n8 < 3; n8++) {
    uint32_t b[8][4], c[2][4];
    float o[8][4];
#pragma unroll
    for (int i = 0; i < 8; i++) { ldsm4(b[i], va + (n8 * 8 + i) * 640); o[i][0] = o[i][1] = o[i][2] = o[i][3] = 0.f; }
    if (NT == 5) { ldsm4(c[0], vc + n8 * 5120); ldsm4(c[1], vc + n8 * 5120 + 2560); }
#pragma unroll
    for (int i = 0; i < 8; i++) mma16816(o[i], &P[0], b[i][0], b[i][1]);
#pragma unroll
    for (int i = 0; i < 8; i++) { if (NT == 5) mma16816(o[i], &P[4], b[i][2], b[i][3]); else mma1688(o[i], P[4], P[5], b[i][2]); }
    if (NT == 5)
#pragma unroll
      for (int i = 0; i < 8; i++) mma1688(o[i], P[2 * NT - 2], P[2 * NT - 1], c[i >> 2][i & 3]);
#pragma unroll
    for (int i = 0; i < 4; i++)
      stsm4(ob + n8 * 8192 + (((i * 2 + (lane >> 4)) ^ (orow & 7)) << 4), pack_bf16(o[2 * i][0] * i0, o[2 * i][1] * i0), pack_bf16(o[2 * i][2] * i1, o[2 * i][3] * i1),
            pack_bf16(o[2 * i + 1][0] * i0, o[2 * i + 1][1] * i0), pack_bf16(o[2 * i + 1][2] * i1, o[2 * i + 1][3] * i1));
  }
  __syncwarp();
  AT(5, 0);
  if (lane == 0) mbar_arrive(sb + EMPTY + (itv % NST) * 8);
}

__global__ void __launch_bounds__(384, 1)
worker_kernel(int layer, Sync* sy, const bf16* __restrict__ xin, const bf16* __restrict__ wphi, const bf16* __restrict__ wo2,
              const __grid_constant__ CUtensorMap mx, const __grid_constant__ CUtensorMap mq, const __grid_constant__ CUtensorMap moa,
              const __grid_constant__ CUtensorMap mos, const __grid_constant__ CUtensorMap mwo, const __grid_constant__ CUtensorMap mxa,
              const __grid_constant__ CUtensorMap macc, const __grid_constant__ CUtensorMap mwb) {
  using namespace wk;
  extern __shared__ __align__(1024) uint8_t smraw[];
  const uint32_t sb = smem_u32(smraw);
  const int tid = threadIdx.x, lane = tid & 31;
  const int wg = __shfl_sync(0xffffffffu, tid >> 7, 0), w = __shfl_sync(0xffffffffu, (tid >> 5) & 3, 0);
  constexpr int WF = 0;
  if (!WLD) asm volatile("griddepcontrol.launch_dependents;");
  GT(1, 0);
  const int nstat = WGRID ? 0 : min(max((int)gridDim.x - (CTAIL ? 0 : 96), 0), 64);
  int idx0 = 0;
  const int nl = min((int)gridDim.x - nstat, NLATE);
  if (tid == 96 && (int)blockIdx.x >= nstat + nl) idx0 = atomicAdd(&sy->head, 1);
  int id0 = -1;
  uint32_t flag0 = 0;
  if (LFAST && tid == 0 && (int)blockIdx.x >= nstat && (int)blockIdx.x < nstat + nl) {
    if (TMPF) { asm volatile("prefetch.tensormap [%0];" :: "l"(&mwo) : "memory"); asm volatile("prefetch.tensormap [%0];" :: "l"(&moa) : "memory"); }
    id0 = late_task(layer, blockIdx.x - nstat);
    flag0 = ld_acquire(&sy->o[(id0 >> 16 & 255) * 16 + (id0 >> 8 & 255)]);
  }
  if (tid == 0) {
    sts64(sb + FIN, 0, 0);
    for (int i = 0; i < NST; i++) { mbar_init(sb + FULL + i * 8, 1); mbar_init(sb + EMPTY + i * 8, 8); }
    for (int i = 0; i < 2; i++) { mbar_init(sb + TFULL + i * 8, 1); mbar_init(sb + TEMPTY + i * 8, 9); mbar_init(sb + DONE + i * 8, 128); mbar_init(sb + FREE + i * 8, 1); }
    mbar_init(sb + CGO, 1); mbar_init(sb + LBAR, 1);
    asm volatile("fence.mbarrier_init.release.cluster;" ::: "memory");
    mbar_expect(sb + LBAR, sizeof(TaskList));
    bulk_load_plain(sb + TL, &d_tasks[layer], sizeof(TaskList), sb + LBAR);
  }
  if (WQP && layer && tid == 64 && blockIdx.x >= 4) {
    if (WQP_D) __nanosleep(WQP_D);
    for (int i = blockIdx.x - 4; i < WQP * 32; i += gridDim.x - 4) tma3d_prefetch(&mq, 0, i / 32 * 64, i % 32 * 3);
  }
  uint32_t early = 0;
  if (wg == 0) {
    asm volatile("setmaxnreg.dec.sync.aligned.u32 40;");
    if (LFAST && w == 0) bar_arrive(0, 384); else bar_sync(0, 384);
    if (tid == 96) {
      uint32_t nres = 0;
      bool tail = false;
      int ntask = 0, tail0 = 0, late0 = 0;
      for (uint32_t nt = 0;; nt++) {
        mbar_wait_long(sb + TEMPTY + (nt & 1) * 8, ((nt >> 1) & 1) ^ 1);
        if (nt) mbar_wait_long(sb + CGO, (nt - 1) & 1);
        if (tail) for (int i = 0; i < 4000000 && (lds32(sb + FIN) < nres || lds32(sb + FIN + 4) < nres); i++) {}
        int id;
        if (nt == 0 && (int)blockIdx.x < nstat) id = first_task(layer, blockIdx.x);
        else if (nt == 0 && (int)blockIdx.x < nstat + nl) { id = late_task(layer, blockIdx.x - nstat); tail = true; }
        else {
          const int idx = nstat + (nt ? atomicAdd(&sy->head, 1) : idx0);
          if (!ntask) { mbar_wait_long(sb + LBAR, 0); ntask = lds32(sb + TL); tail0 = lds32(sb + TL + 4); late0 = lds32(sb + TL + 8); }
          const int e = !SLATE || idx < late0 ? idx : idx + nl;
          id = e < ntask ? lds32(sb + TL + 16 + e * 4) : T_END << 24;
          tail = idx >= tail0;
        }
        sts32(sb + TASK + (nt & 1) * 4, id);
        mbar_arrive(sb + TFULL + (nt & 1) * 8);
        if (WLD == 1 && (id >> 24) == T_F && (id >> 16 & 255) >= FLATE) asm volatile("griddepcontrol.launch_dependents;");
        if ((id >> 24) == T_END) {
          if (WLD) asm volatile("griddepcontrol.launch_dependents;");
          early = id & 1;
          break;
        }
        nres += (id >> 24) < T_P;
      }
    } else if (tid == 0) {
      uint32_t it = 0;
      bool have_xn = false, have_zero = false;
      if (TMPF && !LFAST && (int)blockIdx.x >= nstat) {
        asm volatile("prefetch.tensormap [%0];" :: "l"(&mwo) : "memory");
        asm volatile("prefetch.tensormap [%0];" :: "l"(&moa) : "memory");
      }
      if (!BSL && ZPRE && (int)blockIdx.x >= nstat) have_zero = ld_acquire(&sy->zeroed) >= NZ;
      for (uint32_t nt = 0;; nt++) {
        int id = id0;
        if (nt || id0 < 0) {
          mbar_wait_long(sb + TFULL + (nt & 1) * 8, (nt >> 1) & 1);
          id = lds32(sb + TASK + (nt & 1) * 4);
        }
        const Task tk = decode(id);
        if (nt == 0) WS(1, tk.type);
        mbar_arrive(sb + TEMPTY + (nt & 1) * 8);
        if (tk.type == T_END) {
          if (PFB && blockIdx.x < 128) {
            asm volatile("cp.async.bulk.prefetch.L2.global [%0], 19200;" :: "l"((const char*)g_wb1 + blockIdx.x * 19200) : "memory");
            asm volatile("cp.async.bulk.prefetch.L2.global [%0], 6400;" :: "l"((const char*)g_wb2 + blockIdx.x * 6400) : "memory");
          }
          early = id & 1;
          GT(1, 1); break;
        }
        if (tk.type == T_Q && tk.b) {
          for (int c = 0; c < 4; c++, it++) {
            const uint32_t st = it % NST, a = sb + st * STAGE, fb = sb + FULL + st * 8;
            if (!(c & 1)) {
              wait_count_t(&sy->kv[(tk.rt * 4 + c + 1) * NH + tk.a], 3, tk.rt == 15 && c == 2); fence_flag_to_bulk();
              if (LASTG && tk.rt == 15 && c == 2) asm volatile("fence.proxy.async.global;" ::: "memory");
            }
            if (OPF && c == 0 && tk.rt == 15)
              for (int n = 0; n < OPF; n++) tma3d_prefetch(&mos, 0, 13 * 128 + n * 64, tk.a * 3);
            if (c == 2) mbar_arrive(sb + CGO);
            mbar_wait_long(sb + EMPTY + st * 8, ((it / NST) & 1) ^ 1);
            mbar_expect(fb, 30720);
            const bf16* src = g_kv + ((size_t)((tk.rt * 4 + (c & 2)) * NH + tk.a) * 2 + (c & 1)) * DH * NKEY;
            bulk_load(a, src, 15360, fb);
            bulk_load(a + 15360, src + (size_t)NH * 2 * DH * NKEY, 15360, fb);
          }
        } else if (tk.type == T_G) {
          if (!have_xn) { spin_count(&sy->pro[0], NPRO); asm volatile("fence.proxy.async;" ::: "memory"); have_xn = true; }
          for (int c = 0; c < 10; c++, it++) {
            const uint32_t st = it % NST, a = sb + st * STAGE, fb = sb + FULL + st * 8;
            if (c == CLQ) mbar_arrive(sb + CGO);
            mbar_wait_long(sb + EMPTY + st * 8, ((it / NST) & 1) ^ 1);
            mbar_expect(fb, 40960);
            tma2d(a, &mx, c * 64, tk.rt * 128, fb);
            tma3d(a + 16384, &mq, 0, c * 64, tk.a * 3, fb);
          }
        } else if (tk.type == T_Q) {
          if (!have_xn) { spin_count(&sy->pro[0], NPRO); asm volatile("fence.proxy.async;" ::: "memory"); have_xn = true; }
          bool have_kv = false;
          for (int c = (WF & 2) ? 8 : 0; c < 14; c++, it++) {
            const uint32_t st = it % NST, a = sb + st * STAGE, fb = sb + FULL + st * 8;
            if (c == CLQ) mbar_arrive(sb + CGO);
            if (c >= 4 && !have_kv) {
              const uint32_t* fl = &sy->kv[(tk.rt * 4 + 3) * NH + tk.a];
              if (c == 10) wait_count(fl, 3);
              if (c == 10 || ld_acquire(fl) >= 3) { have_kv = true; fence_flag_to_bulk(); }
            }
            mbar_wait_long(sb + EMPTY + st * 8, ((it / NST) & 1) ^ 1);
            if (c < 10) {
              mbar_expect(fb, 40960);
              tma2d(a, &mx, c * 64, tk.rt * 128, fb);
              tma3d(a + 16384, &mq, 0, c * 64, tk.a * 3, fb);
            } else {
              mbar_expect(fb, 30720);
              const bf16* src = g_kv + ((size_t)((tk.rt * 4 + (c & 1) * 2) * NH + tk.a) * 2 + ((c - 10) >> 1)) * DH * NKEY;
              bulk_load(a, src, 15360, fb);
              bulk_load(a + 15360, src + (size_t)NH * 2 * DH * NKEY, 15360, fb);
            }
          }
        } else if (tk.type == T_W) {
          const int nc = (WF & 1) ? 2 : 96 >> lsplit(tk.rt), c0 = tk.b * nc;
          if (!BSL && tk.rt >= RT_SPLIT && !have_zero) { wait_count(&sy->zeroed, NZ); have_zero = true; }
          const int npre = WPRE ? min(nc, (int)NST) : 0;
          for (int c = 0; c < npre; c++) {
            const uint32_t st = (it + c) % NST, fb = sb + FULL + st * 8;
            mbar_wait_long(sb + EMPTY + st * 8, (((it + c) / NST) & 1) ^ 1);
            mbar_expect(fb, 36864);
            tma3d(sb + st * STAGE + 16384, &mwo, 0, (c0 + c) * 64, tk.a * 5, fb);
          }
          if (nt || flag0 < (64u >> lsplit(tk.rt))) wait_count_t(&sy->o[tk.rt * 16 + tk.b], 64 >> lsplit(tk.rt), tk.rt == 15);
          if (tk.rt >= 13) XT((tk.rt - 13) * 32 + (tk.b >> (tk.rt == 15 && S15 == 16) & 7) * 4 + tk.a, 0);
          fence_flag_to_bulk();
          if (tk.rt >= 13) XT((tk.rt - 13) * 32 + (tk.b >> (tk.rt == 15 && S15 == 16) & 7) * 4 + tk.a, 1);
          for (int c = 0; c < nc; c++, it++) {
            const uint32_t st = it % NST, a = sb + st * STAGE, fb = sb + FULL + st * 8;
            if (c == max(nc - CLW, 0)) mbar_arrive(sb + CGO);
            if (c >= npre) {
              mbar_wait_long(sb + EMPTY + st * 8, ((it / NST) & 1) ^ 1);
              mbar_expect(fb, 36864);
              tma3d(a + 16384, &mwo, 0, (c0 + c) * 64, tk.a * 5, fb);
            }
            tma2d(a, &moa, (c0 + c) * 64, tk.rt * 128, fb);
          }
        } else if (tk.type == T_P && tk.a >= NZ && tk.a < NZ + 80) {
          const uint32_t st = it % NST, a = sb + st * STAGE, fb = sb + FULL + st * 8;
          const int gq = (tk.a - NZ) / 10, k0 = (tk.a - NZ) % 10 * 64;
          mbar_arrive(sb + CGO);
          mbar_wait_long(sb + EMPTY + st * 8, ((it / NST) & 1) ^ 1);
          mbar_expect(fb, 30720 + 3200);
          for (int p = 0; p < 3; p++) tma2d(a + p * 10240, &mwb, p * DM + gq * 80, k0, fb);
          bulk_load_plain(a + 30720, wphi + gq * 4 * BDH * BDH, 3200, fb);
          it++;
        } else if (tk.type != T_F) mbar_arrive(sb + CGO);
      }
    } else if (tid == 32 || tid == 64) {
      const int cw = (tid >> 5) - 1;
      for (uint32_t n = 0;; n++) {
        mbar_wait_long(sb + DONE + cw * 8, n & 1);
        const Task tk = decode(lds32(sb + DTASK + cw * 4));
        if (tk.type == T_END) {
          if (BFL) red_release(&sy->pad1[0]);
          early = tk.a; break;
        }
        if (tk.type == T_W && tk.rt == FXT) XT(128 + (tk.b & 1) * 4 + tk.a, cw);
        if (tk.type == T_Q && tk.rt >= OKEEP)
          asm volatile("cp.async.bulk.tensor.3d.global.shared::cta.bulk_group [%0, {%2, %3, %4}], [%1];" :: "l"(&mos), "r"(sb + OST + cw * 24576), "r"(0), "r"(tk.rt * 128 + cw * 64), "r"(tk.a * 3) : "memory");
        else if (tk.type == T_Q) tma3d_store(&mos, sb + OST + cw * 24576, 0, tk.rt * 128 + cw * 64, tk.a * 3);
        else if (split(tk.rt) == 1) tma3d_store(&mxa, sb + OST + cw * 24576, 0, tk.rt * 128 + cw * 64, tk.a * 5);
        else if (BSL && SLC) {
          bf16* dst = g_sl + (size_t)(((slice_of(tk.rt) + tk.b) * 4 + tk.a) * 2 + cw) * 10240;
          if (SLEV) bulk_store(dst, sb + OST + cw * 24576, 20480);
          else asm volatile("cp.async.bulk.global.shared::cta.bulk_group [%0], [%1], 20480;" :: "l"(dst), "r"(sb + OST + cw * 24576) : "memory");
        }
        else if (BSL) tma3d_store(&macc, sb + OST + cw * 24576, 0, (slice_of(tk.rt) + tk.b) * 128 + cw * 64, tk.a * 5);
        else {
          const uint32_t slot = lds32(sb + DSLOT + cw * 4);
            asm volatile("cp.reduce.async.bulk.tensor.3d.global.shared::cta.add.tile.bulk_group [%0, {%2, %3, %4}], [%1];"
                         :: "l"(&macc), "r"(sb + slot * STAGE), "r"(0), "r"(layer * ACC_ROWS + (tk.rt - RT_SPLIT) * 128 + cw * 64), "r"(tk.a * 5) : "memory");
          asm volatile("cp.async.bulk.commit_group; cp.async.bulk.wait_group.read 0;" ::: "memory");
          asm volatile("mbarrier.arrive.shared::cta.b64 _, [%0], 8;" :: "r"(sb + EMPTY + slot * 8) : "memory");
        }
        asm volatile("cp.async.bulk.commit_group; cp.async.bulk.wait_group.read 0;" ::: "memory");
        mbar_arrive(sb + FREE + cw * 8);
        if (tk.type == T_Q && tk.rt == 15) XT(96 + tk.a, cw);
        asm volatile("cp.async.bulk.wait_group 0;" ::: "memory");
        if (tk.type == T_Q && tk.rt == 15) XT(96 + tk.a, 2 + cw);
        if (tk.type == T_W && tk.rt >= 13) XT((tk.rt - 13) * 32 + (tk.b >> (tk.rt == 15 && S15 == 16) & 7) * 4 + tk.a, 2 + cw);
        if (tk.type == T_W && tk.rt == FXT) XT(128 + (tk.b & 1) * 4 + tk.a, 2 + cw);
        if (tk.type == T_Q) {
          const int sl = tk.rt * 16 + (tk.a >> (5 - lsplit(tk.rt))) + (CTAIL && tk.rt == 15 ? cw * 8 : 0);
          publish_bulk<WFEN>(&sy->o[sl]);
        } else if (split(tk.rt) > 1) {
          publish_bulk<WFEN>(&sy->wcnt[(tk.rt * 4 + tk.a) * 2 + cw]);
        }
        sts32(sb + FIN + cw * 4, n + 1);
      }
    }
  } else {
    asm volatile("setmaxnreg.inc.sync.aligned.u32 232;");
    bar_sync(0, 384);
    const int cw = wg - 1, g = lane >> 2, t = lane & 3, ct = tid - 128;
    if (WLN >> layer & 1) {
      if (layer) { if (ct == 0) spin_count(&sy->pro[1], 1); bar_sync(3, 256); }
      uint2 u[2][10];
      const bf16* x = xin + (ct >> 5) * 2 * DM + lane * 4;
      int un = blockIdx.x, n = 0;
#pragma unroll
      for (int i = 0; i < 10; i++) u[1][i] = __ldcg((const uint2*)(x + un * 16 * DM + i * 128));
#pragma unroll 1
      for (; un < 128; un += gridDim.x, n++) {
#pragma unroll
        for (int i = 0; i < 10; i++) { u[0][i] = u[1][i]; u[1][i] = __ldcg((const uint2*)(x + min(un + (int)gridDim.x, 127) * 16 * DM + i * 128)); }
#pragma unroll
        for (int rr = 0; rr < 2; rr++) {
          float v[20];
#pragma unroll
          for (int i = 0; i < 5; i++) {
            const uint2 e = u[0][rr * 5 + i];
            v[4 * i] = __uint_as_float(e.x << 16); v[4 * i + 1] = __uint_as_float(e.x & 0xFFFF0000u);
            v[4 * i + 2] = __uint_as_float(e.y << 16); v[4 * i + 3] = __uint_as_float(e.y & 0xFFFF0000u);
          }
          ln_row(v, g_xn + (un * 16 + (ct >> 5) * 2 + rr) * DM, lane);
        }
        if (un < 4) {
          bar_sync(3, 256);
          if (ct == 0) red_release(&sy->pro[2]);
          __syncwarp();
        }
      }
      for (int i = blockIdx.x * 256 + ct; i < (NSEG - 1) * 24 * 32; i += gridDim.x * 256) ((uint4*)g_ar)[(i >> 5) * 64 + (i & 31)] = make_uint4(0, 0, 0, 0);
      bar_sync(3, 256);
      if (ct == 0) asm volatile("red.release.gpu.global.add.u32 [%0], %1;" :: "l"(&sy->pro[0]), "r"(n) : "memory");
      __syncwarp();
    }
    uint32_t it = 0, nd = 0;
    for (uint32_t nt = 0;; nt++) {
      mbar_wait_long(sb + TFULL + (nt & 1) * 8, (nt >> 1) & 1);
      const int tid_ = __shfl_sync(0xffffffffu, (int)lds32(sb + TASK + (nt & 1) * 4), 0);
      const Task tk = decode(tid_);
      if (nt == 0 && ct == 0) WS(2, tid_);
      __syncwarp();
      if (lane == 0) mbar_arrive(sb + TEMPTY + (nt & 1) * 8);
      if (tk.type == T_END) {
        mbar_wait_long(sb + FREE + cw * 8, (nd & 1) ^ 1);
        if (ct == cw * 128) sts32(sb + DTASK + cw * 4, tid_);
        mbar_arrive(sb + DONE + cw * 8);
        early = tid_ & 1;
        break;
      }
      if (tk.type == T_Q || tk.type == T_G) {
        if (PFACC && tk.type == T_Q && tk.rt >= RT_SPLIT && ct == 32)
          asm volatile("cp.async.bulk.prefetch.L2.global [%0], 10240;" :: "l"(g_acc + (size_t)(layer * ACC_ROWS + (tk.rt - RT_SPLIT) * 128 + tk.a * 4) * DM) : "memory");
        uint32_t q[48];
        uint4* qf = g_qf + (size_t)(tk.rt * NH + tk.a) * 12 * 256 + ct;
        if (tk.type == T_Q && tk.b) {
          if ((ct & 127) == 0) wait_count(&sy->gst[tk.rt * NH + tk.a], 2);
          bar_sync(1 + cw, 128);
#pragma unroll
          for (int i = 0; i < 12; i++) { const uint4 u = __ldcg(qf + i * 256); q[4 * i] = u.x; q[4 * i + 1] = u.y; q[4 * i + 2] = u.z; q[4 * i + 3] = u.w; }
        } else {
          float d[96];
#pragma unroll
          for (int i = 0; i < 96; i++) d[i] = 0.f;
          for (int c = 0; c < ((WF & 2) ? 2 : 10); c++, it++) {
            const uint32_t st = it % NST, a = sb + st * STAGE;
            mbar_wait_long(sb + FULL + st * 8, (it / NST) & 1);
            if (c == 0) TM(0);
            const uint64_t da = mkdesc(a + cw * 8192, 16, 1024, 1), db = mkdesc(a + 16384, 8192, 1024, 1);
            wg_fence();
#pragma unroll
            for (int k = 0; k < 4; k++) wgmma_n192_nt(d, da + k * 2, db + k * 128, c | k);
            wg_commit();
            if (c > 0) { wg_wait<1>(); if (lane == 0) mbar_arrive(sb + EMPTY + ((it - 1) % NST) * 8); }
          }
          wg_wait<0>();
          if (lane == 0) mbar_arrive(sb + EMPTY + ((it - 1) % NST) * 8);
#pragma unroll
          for (int i = 0; i < 48; i++) q[i] = pack_bf16(d[2 * i], d[2 * i + 1]);
        }
        TM(1);
        if (tk.type == T_G) {
#pragma unroll
          for (int i = 0; i < 12; i++) __stcg(qf + i * 256, make_uint4(q[4 * i], q[4 * i + 1], q[4 * i + 2], q[4 * i + 3]));
          bar_sync(1 + cw, 128);
          if ((ct & 127) == 0) red_release(&sy->gst[tk.rt * NH + tk.a]);
          __syncwarp();
          TM(2); TM(3);
          continue;
        }
        const uint32_t itk = tk.b ? it + 2 * cw : it + cw, itv = tk.b ? itk + 1 : it + 2 + cw;
        if (cw == 1) { pass_stage(sb, it, lane); if (tk.b) pass_stage(sb, it + 1, lane); }
        mbar_wait_long(sb + FULL + (itk % NST) * 8, (itk / NST) & 1);
        TM(2);
        const uint32_t mid = tk.b ? 0xFFFFFFFFu : itk + 1;
        if (w & 1) attend<5>(sb, q, cw, w, lane, itk, itv, mid, nd); else attend<3>(sb, q, cw, w, lane, itk, itv, mid, nd);
        if (!CTAIL && cw == 0) { if (tk.b) pass_stage(sb, it + 2, lane); pass_stage(sb, it + 3, lane); }
        if (ct == cw * 128) sts32(sb + DTASK + cw * 4, tid_);
        fence_async();
        mbar_arrive(sb + DONE + cw * 8);
        if (CTAIL && cw == 0) { if (tk.b) pass_stage(sb, it + 2, lane); pass_stage(sb, it + 3, lane); }
        it += 4;
        nd++;
        TM(3);
      } else if (tk.type == T_W) {
        float d[80];
#pragma unroll
        for (int i = 0; i < 80; i++) d[i] = 0.f;
        const int nc = (WF & 1) ? 2 : 96 >> lsplit(tk.rt);
        const int off = (tk.rt * 128 + cw * 64 + w * 16 + g) * DM + tk.a * 160 + 2 * t;
        const bool whole = BSL || split(tk.rt) == 1;
        uint32_t res[40];
        if (WTR) {
          const int ln = opq(lane);
          const bf16* x = xin + (tk.rt * 128 + cw * 64 + w * 16) * DM + tk.a * 160;
#pragma unroll
          for (int i = 0; i < 40; i++) res[i] = 0;
          if (split(tk.rt) == 1)
#pragma unroll
            for (int i = 0; i < 10; i++)
              ldcg128(*(uint32_t(*)[4])&res[4 * i], i < 8 ? x + (2 * i + (ln >> 4)) * DM + (ln & 15) * 8 : x + ((i - 8) * 8 + (ln >> 2)) * DM + 128 + (ln & 3) * 8);
        } else
#pragma unroll
        for (int i = 0; i < 40; i++) res[i] = split(tk.rt) == 1 ? *(const uint32_t*)(xin + off + (i >> 1) * 8 + (i & 1) * 8 * DM) : 0u;
        for (int c = 0; c < nc; c++, it++) {
          const uint32_t st = it % NST, a = sb + st * STAGE;
          mbar_wait_long(sb + FULL + st * 8, (it / NST) & 1);
          if (c == 0) TM(0);
          const uint64_t da = mkdesc(a + cw * 8192, 16, 1024, 1), db = mkdesc(a + 16384, 4096, 512, 2);
          wg_fence();
#pragma unroll
          for (int k = 0; k < 4; k++) wgmma_n160_nt(d, da + k * 2, db + k * 64, c | k);
          wg_commit();
          if (c > 0) { wg_wait<1>(); if (lane == 0 && (whole || c < nc - 1)) mbar_arrive(sb + EMPTY + ((it - 1) % NST) * 8); }
        }
        wg_wait<0>();
        if (lane == 0 && whole) mbar_arrive(sb + EMPTY + ((it - 1) % NST) * 8);
        TM(1);
        mbar_wait_long(sb + FREE + cw * 8, (nd & 1) ^ 1);
        TM(2);
        if (whole) {
          const uint32_t orow = w * 16 + (lane & 15), ob = sb + OST + cw * 24576 + orow * 64;
          float s1[2] = {0.f, 0.f}, s2[2] = {0.f, 0.f};
          if (WTR && split(tk.rt) == 1) {
            const uint32_t ln = opq(lane), tb = sb + OST + cw * 24576 + w * 1024;
#pragma unroll
            for (int i = 0; i < 10; i++)
              sts128(i < 8 ? tb + (2 * i + (ln >> 4)) * 64 + (ln >> 2 & 3) * 4096 + (((ln & 3) ^ (i & 3)) << 4) : tb + ((i - 8) * 8 + (ln >> 2)) * 64 + 16384 + (((ln & 3) ^ (ln >> 3)) << 4),
                     res[4 * i], res[4 * i + 1], res[4 * i + 2], res[4 * i + 3]);
            __syncwarp();
#pragma unroll
            for (int i2 = 0; i2 < 10; i2++) ldsm4(*(uint32_t(*)[4])&res[4 * i2], ob + (i2 >> 1) * 4096 + ((((i2 & 1) * 2 + (lane >> 4)) ^ ((orow >> 1) & 3)) << 4));
            __syncwarp();
          }
#pragma unroll
          for (int i2 = 0; i2 < 10; i2++) {
            uint32_t u[4];
#pragma unroll
            for (int e = 0; e < 4; e++) {
              const int i = 2 * i2 + (e >> 1);
              const uint32_t x = res[4 * i2 + e];
              u[e] = pack_bf16(d[4 * i + (e & 1) * 2] + __uint_as_float(x << 16), d[4 * i + (e & 1) * 2 + 1] + __uint_as_float(x & 0xFFFF0000u));
              const float lo = __uint_as_float(u[e] << 16), hi = __uint_as_float(u[e] & 0xFFFF0000u);
              s1[e & 1] += lo + hi; s2[e & 1] = fmaf(lo, lo, fmaf(hi, hi, s2[e & 1]));
            }
            stsm4(ob + (i2 >> 1) * 4096 + ((((i2 & 1) * 2 + (lane >> 4)) ^ ((orow >> 1) & 3)) << 4), u[0], u[1], u[2], u[3]);
          }
          fence_async();
          if (split(tk.rt) == 1)
#pragma unroll
          for (int e = 0; e < 2; e++) {
            s1[e] += __shfl_xor_sync(0xffffffffu, s1[e], 1); s2[e] += __shfl_xor_sync(0xffffffffu, s2[e], 1);
            s1[e] += __shfl_xor_sync(0xffffffffu, s1[e], 2); s2[e] += __shfl_xor_sync(0xffffffffu, s2[e], 2);
            if (t == 0) red_add2(&sy->rstat[tk.rt * 128 + cw * 64 + w * 16 + g + 8 * e], s1[e], s2[e]);
          }
        } else {
          bar_sync(3, 256);
          const uint32_t slot = (it - 2 + cw) % NST, a = sb + slot * STAGE + (w * 16 + g) * 128 + (t & 1) * 8;
#pragma unroll
          for (int i = 0; i < 20; i++) {
            const uint32_t o = a + (i >> 2) * 8192 + ((((i & 3) * 2 + (t >> 1)) ^ g) << 4);
            sts64(o, __float_as_uint(d[4 * i]), __float_as_uint(d[4 * i + 1])); sts64(o + 1024, __float_as_uint(d[4 * i + 2]), __float_as_uint(d[4 * i + 3]));
          }
          if (ct == cw * 128) sts32(sb + DSLOT + cw * 4, slot);
          fence_async();
        }
        if (ct == cw * 128) sts32(sb + DTASK + cw * 4, tid_);
        mbar_arrive(sb + DONE + cw * 8);
        nd++;
        TM(3);
      } else if (BSL && tk.type == T_F) {
        if (tk.rt == BKVZ && tk.b < 2) for (int i = ct; i < NH * BF * 6 / 8; i += 256) ((uint4*)g_bkv)[(tk.a * 2 + tk.b) * (NH * BF * 6 / 8) + i] = make_uint4(0, 0, 0, 0);
        if (PFF && tk.rt == PFF && tk.b < 2 && ct == 32) {
          const int q = tk.a * 2 + tk.b;
          for (int i = 0; i < 20; i++) asm volatile("cp.async.bulk.prefetch.L2.global [%0], 15360;" :: "l"((const char*)g_wb1 + (q * 20 + i) * 15360) : "memory");
          for (int i = 0; i < 8; i++) asm volatile("cp.async.bulk.prefetch.L2.global [%0], 12800;" :: "l"((const char*)g_wb2 + (q * 8 + i) * 12800) : "memory");
          asm volatile("cp.async.bulk.prefetch.L2.global [%0], 9600;" :: "l"((const char*)g_cs + q * 9600) : "memory");
        }
        constexpr int LPR = 256 / FROWS, NU = (20 + LPR - 1) / LPR;
        const int cq = opq(ct), rl = tk.b * FROWS + cq / LPR, q = cq % LPR, r = tk.rt * 128 + rl, c0 = tk.a * 160 + q * 8;
        if (ct == 0) { wait_count_t(&sy->wcnt[(tk.rt * 4 + tk.a) * 2 + tk.b * FROWS / 64], split(tk.rt), TIGHT == 1 && tk.rt >= 13); if (!FCGO) mbar_arrive(sb + CGO); }
        if (ct == 0 && tk.rt == FXT) XT(136 + tk.a * 4 + tk.b, 1);
        uint4 x[NU];
#pragma unroll
        for (int i = 0; i < NU; i++) x[i] = ldcg_if(xin + r * DM + c0 + i * LPR * 8, i * LPR + q < 20);
        bar_sync(3, 256);
        float a[NU][8];
#pragma unroll
        for (int i = 0; i < NU; i++) {
          a[i][0] = __uint_as_float(x[i].x << 16); a[i][1] = __uint_as_float(x[i].x & 0xFFFF0000u); a[i][2] = __uint_as_float(x[i].y << 16); a[i][3] = __uint_as_float(x[i].y & 0xFFFF0000u);
          a[i][4] = __uint_as_float(x[i].z << 16); a[i][5] = __uint_as_float(x[i].z & 0xFFFF0000u); a[i][6] = __uint_as_float(x[i].w << 16); a[i][7] = __uint_as_float(x[i].w & 0xFFFF0000u);
        }
        float y[NU][8];
#pragma unroll
        for (int i = 0; i < NU * 8; i++) y[i >> 3][i & 7] = 0.f;
        const bf16* sl = SLC ? g_sl + (size_t)((slice_of(tk.rt) * 4 + tk.a) * 2 + (rl >> 6)) * 10240 + (q >> 2) * 2048 + (rl & 63) * 32 + (((q & 3) ^ (rl >> 1 & 3)) << 3)
                             : g_sl + (size_t)(slice_of(tk.rt) * 128 + rl) * DM + c0;
        constexpr int US = SLC ? LPR / 4 * 2048 : LPR * 8;
        constexpr int SB = FROWS == 64 ? 4 : 8;
        for (int b0 = 0; b0 < split(tk.rt); b0 += SB) {
          uint4 u[SB][NU];
#pragma unroll
          for (int b = 0; b < SB; b++)
#pragma unroll
            for (int i = 0; i < NU; i++)
              if (FVOL) u[b][i] = ldcg_if(sl + (size_t)(b0 + b) * 128 * DM + i * US, b0 + b < split(tk.rt) && i * LPR + q < 20);
              else u[b][i] = b0 + b < split(tk.rt) && i * LPR + q < 20 ? __ldcg((const uint4*)(sl + (size_t)(b0 + b) * 128 * DM + i * US)) : make_uint4(0, 0, 0, 0);
          if (FVOL) sched_fence(layer >> 4);
#pragma unroll
          for (int b = 0; b < SB; b++)
#pragma unroll
            for (int i = 0; i < NU; i++) {
              y[i][0] += __uint_as_float(u[b][i].x << 16); y[i][1] += __uint_as_float(u[b][i].x & 0xFFFF0000u); y[i][2] += __uint_as_float(u[b][i].y << 16); y[i][3] += __uint_as_float(u[b][i].y & 0xFFFF0000u);
              y[i][4] += __uint_as_float(u[b][i].z << 16); y[i][5] += __uint_as_float(u[b][i].z & 0xFFFF0000u); y[i][6] += __uint_as_float(u[b][i].w << 16); y[i][7] += __uint_as_float(u[b][i].w & 0xFFFF0000u);
            }
        }
        if (FCGO && ct == 0) { loaded(__float_as_uint(y[0][0])); mbar_arrive(sb + CGO); }
        float s1 = 0.f, s2 = 0.f;
#pragma unroll
        for (int i = 0; i < NU; i++) {
          uint32_t z[4];
#pragma unroll
          for (int e = 0; e < 4; e++) {
            z[e] = pack_bf16(a[i][2 * e] + y[i][2 * e], a[i][2 * e + 1] + y[i][2 * e + 1]);
            const float lo = __uint_as_float(z[e] << 16), hi = __uint_as_float(z[e] & 0xFFFF0000u);
            s1 += lo + hi; s2 = fmaf(lo, lo, fmaf(hi, hi, s2));
          }
          asm volatile("{.reg .pred p; setp.ne.u32 p, %5, 0; @p st.global.v4.u32 [%0], {%1,%2,%3,%4};}"
                       :: "l"(g_xa + r * DM + c0 + i * LPR * 8), "r"(z[0]), "r"(z[1]), "r"(z[2]), "r"(z[3]), "r"((uint32_t)(i * LPR + q < 20)) : "memory");
        }
#pragma unroll
        for (int o = 1; o < LPR; o <<= 1) { s1 += __shfl_xor_sync(0xffffffffu, s1, o); s2 += __shfl_xor_sync(0xffffffffu, s2, o); }
        asm volatile("{.reg .pred p; setp.ne.u32 p, %3, 0; @p red.relaxed.gpu.global.add.v2.f32 [%0], {%1,%2};}"
                     :: "l"(&sy->rstat[r]), "f"(s1), "f"(s2), "r"((uint32_t)(q == 0)) : "memory");
        if (ct == 0 && tk.rt == FXT) XT(136 + tk.a * 4 + tk.b, 2);
        TM(0); TM(1); TM(2); TM(3);
      } else if (tk.type == T_F) {
        if (tk.rt == BKVZ) for (int i = ct; i < NH * BF * 6 / 8; i += 256) ((uint4*)g_bkv)[(tk.a * 2 + tk.b) * (NH * BF * 6 / 8) + i] = make_uint4(0, 0, 0, 0);
        if (PFF && tk.rt == PFF && ct == 32) {
          const int q = tk.a * 2 + tk.b;
          for (int i = 0; i < 20; i++) asm volatile("cp.async.bulk.prefetch.L2.global [%0], 15360;" :: "l"((const char*)g_wb1 + (q * 20 + i) * 15360) : "memory");
          for (int i = 0; i < 8; i++) asm volatile("cp.async.bulk.prefetch.L2.global [%0], 12800;" :: "l"((const char*)g_wb2 + (q * 8 + i) * 12800) : "memory");
          asm volatile("cp.async.bulk.prefetch.L2.global [%0], 9600;" :: "l"((const char*)g_cs + q * 9600) : "memory");
        }
        if (ct == 0) { wait_count(&sy->wcnt[(tk.rt * 4 + tk.a) * 2 + tk.b], split(tk.rt)); mbar_arrive(sb + CGO); }
        const int r = tk.rt * 128 + tk.b * 64 + (ct >> 2), c0 = tk.a * 160 + (ct & 3) * 4;
        uint2 x[10];
#pragma unroll
        for (int i = 0; i < 10; i++) x[i] = __ldg((const uint2*)(xin + r * DM + c0 + i * 16));
        bar_sync(3, 256);
        float4 a[10];
#pragma unroll
        for (int i = 0; i < 10; i++) a[i] = __ldcg((const float4*)(g_acc + (layer * ACC_ROWS + r - RT_SPLIT * 128) * DM + c0 + i * 16));
        float s1 = 0.f, s2 = 0.f;
#pragma unroll
        for (int i = 0; i < 10; i++) {
          const uint2 z = make_uint2(pack_bf16(a[i].x + __uint_as_float(x[i].x << 16), a[i].y + __uint_as_float(x[i].x & 0xFFFF0000u)),
                                     pack_bf16(a[i].z + __uint_as_float(x[i].y << 16), a[i].w + __uint_as_float(x[i].y & 0xFFFF0000u)));
          *(uint2*)(g_xa + r * DM + c0 + i * 16) = z;
          const float v0 = __uint_as_float(z.x << 16), v1 = __uint_as_float(z.x & 0xFFFF0000u), v2 = __uint_as_float(z.y << 16), v3 = __uint_as_float(z.y & 0xFFFF0000u);
          s1 += (v0 + v1) + (v2 + v3); s2 = fmaf(v0, v0, fmaf(v1, v1, fmaf(v2, v2, fmaf(v3, v3, s2))));
        }
        s1 += __shfl_xor_sync(0xffffffffu, s1, 1); s2 += __shfl_xor_sync(0xffffffffu, s2, 1);
        s1 += __shfl_xor_sync(0xffffffffu, s1, 2); s2 += __shfl_xor_sync(0xffffffffu, s2, 2);
        if ((ct & 3) == 0) red_add2(&sy->rstat[r], s1, s2);
        TM(0); TM(1); TM(2); TM(3);
      } else if (tk.a < NZ) {
        if (!BSL) for (int i = ct; i < ACC_ROWS * DM / 4 / NZ; i += 256) ((uint4*)(g_acc + layer * ACC_ROWS * DM))[tk.a * (ACC_ROWS * DM / 4 / NZ) + i] = make_uint4(0, 0, 0, 0);
        if (layer == 1) {
          if (ct == 0) wait_count(&sy->pro[0], NPRO);
          bar_sync(3, 256);
        }
        for (int i = tk.a * 256 + ct; i < (int)(sizeof(Sync) / 16); i += NZ * 256) ((uint4*)&g_sync[layer ^ 1])[i] = make_uint4(0, 0, 0, 0);
        bar_sync(3, 256);
        if (ct == 0) red_release(&sy->zeroed);
        __syncwarp();
      } else if (tk.a >= NZ + 80) {
        const int c = tk.a - NZ - 80, cq = opq(ct);
        uint4 u[20];
#pragma unroll
        for (int i = 0; i < 20; i++) u[i] = __ldg((const uint4*)(wo2 + c * 64 * DM) + i * 256 + cq);
#pragma unroll
        for (int i = 0; i < 20; i++) {
          const int p = i * 256 + cq, kr = p / 80, n8 = p % 80, gq = n8 / 10;
          g_wb2[(gq * 10 + c) * 640 + (n8 % 10 >> 1) * 128 + kr * 2 + ((n8 & 1) ^ (kr >> 2 & 1))] = u[i];
        }
      } else if (P1M) {
        const int gq = (tk.a - NZ) / 10, k0 = (tk.a - NZ) % 10 * 64;
        const uint32_t ln = opq(lane), gg = ln >> 2, tt = ln & 3, wi = opq(ct >> 5);
        const uint32_t T = sb + OST, stg = sb + (it % NST) * STAGE;
        mbar_wait_long(sb + FULL + (it % NST) * 8, (it / NST) & 1);
        uint32_t a0[4], a1[4], a0k[2], a1k;
        {
          const uint32_t pa = stg + 30720 + w * 800 + tt * 80 + gg * 2;
          auto pr = [&](int d, int f) { uint32_t lo, hi;
            asm volatile("ld.shared.u16 %0, [%1];" : "=r"(lo) : "r"(pa + d * 40 + f * 2) : "memory");
            asm volatile("ld.shared.u16 %0, [%1];" : "=r"(hi) : "r"(pa + d * 40 + 40 + f * 2) : "memory");
            return lo | hi << 16; };
          a0[0] = pr(0, 0); a0[1] = pr(0, 8); a0[2] = pr(8, 0); a0[3] = pr(8, 8);
          const int d2 = tt < 2 ? 16 : 0, f2 = gg < 4 ? 16 : 0;
          a0k[0] = pr(d2, 0); a0k[1] = pr(d2, 8);
          a1[0] = pr(0, f2); a1[2] = pr(8, f2); a1k = pr(d2, f2);
          a1[1] = a1[3] = 0;
          if (tt >= 2) a0k[0] = a0k[1] = a1k = 0;
          if (gg >= 4) a1[0] = a1[2] = a1k = 0;
        }
        float c[8][2][4];
        const uint32_t pb = stg + cw * 10240 + gg * 160 + w * 40 + tt * 4;
#pragma unroll
        for (int nt = 0; nt < 8; nt++) {
          const uint32_t b0 = lds32(pb + nt * 1280), b1 = lds32(pb + nt * 1280 + 16);
          uint32_t b2 = lds32(pb + nt * 1280 + (tt < 2 ? 32 : 0));
          if (tt >= 2) b2 = 0;
#pragma unroll
          for (int i = 0; i < 8; i++) c[nt][i >> 2][i & 3] = 0.f;
          mma16816(c[nt][0], a0, b0, b1); mma16816(c[nt][1], a1, b0, b1);
          mma1688(c[nt][0], a0k[0], a0k[1], b2); mma1688(c[nt][1], a1k, 0u, b2);
        }
        uint32_t v[3][4];
        const uint32_t pv = stg + 20480 + (wi * 8 + (ln & 7)) * 160 + (ln >> 3) * 16;
        ldsm4t(v[0], pv); ldsm4t(v[1], pv + 64); ldsm4t(v[2], pv + (ln >> 4 ? 96 : 128));
        mbar_wait_long(sb + FREE + cw * 8, (nd & 1) ^ 1);
        loaded(v[2][3]);
        bar_sync(3, 256);
        if (lane == 0) mbar_arrive(sb + EMPTY + (it % NST) * 8);
        it++;
        {
          const uint32_t n0 = cw * 80 + w * 2 + (gg >> 1) * 8 + (gg & 1);
#pragma unroll
          for (int q = 0; q < 3; q++) {
            const uint32_t n = n0 + q * 32, ro = T + n * 128 + tt * 4, sw = (n >> 3 & 3) * 2 + (n & 1);
            if (q < 2 || gg < 4)
#pragma unroll
              for (int nt = 0; nt < 8; nt++) sts32(ro + ((nt ^ sw) << 4), pack_bf16(c[nt][q >> 1][(q & 1) * 2], c[nt][q >> 1][(q & 1) * 2 + 1]));
          }
#pragma unroll
          for (int i = 0; i < 10; i++) sts32(T + (160 + i * 8 + gg) * 128 + ((wi ^ gg) << 4) + tt * 4, v[i >> 2][i & 3]);
        }
        bar_sync(3, 256);
        const int cq = opq(ct);
        for (int i = cq; i < 240 * 8; i += 256) {
          const uint32_t n = i >> 3, sw = n < 160 ? (n >> 3 & 3) * 2 + (n & 1) : n & 7;
          uint32_t u[4]; lds128(u, T + n * 128 + (((i & 7) ^ sw) << 4));
          *(uint4*)(g_wb1 + (gq * 240 + n) * DM + k0 + (i & 7) * 8) = make_uint4(u[0], u[1], u[2], u[3]);
        }
        if (cq < 240) {
          float cs = 0.f;
#pragma unroll
          for (int i = 0; i < 8; i++) {
            uint32_t u[4]; lds128(u, T + cq * 128 + (((i + cq) & 7) << 4));
#pragma unroll
            for (int e = 0; e < 4; e++) cs += __uint_as_float(u[e] << 16) + __uint_as_float(u[e] & 0xFFFF0000u);
          }
          g_cs[(k0 >> 6) * 3 * DM + gq * 240 + cq] = cs;
        }
        bar_sync(3, 256);
      } else {
        const int gq = (tk.a - NZ) / 10, k0 = (tk.a - NZ) % 10 * 64, r = ct & 63, hh = ct >> 6;
        bf16* T = (bf16*)(smraw + OST);
        float* ph = (float*)(smraw + OST + 30720);
        const uint32_t stg = sb + (it % NST) * STAGE;
        mbar_wait_long(sb + FULL + (it % NST) * 8, (it / NST) & 1);
        uint2 u[3][5];
#pragma unroll
        for (int i = 0; i < 15; i++) { const float2 v = lds64f(stg + (i / 5) * 10240 + r * 160 + hh * 40 + (i % 5) * 8); u[i / 5][i % 5] = make_uint2(__float_as_uint(v.x), __float_as_uint(v.y)); }
        uint32_t pv[4];
#pragma unroll
        for (int i = 0; i < 4; i++) pv[i] = lds32(stg + 30720 + min(ct + i * 256, 799) * 4);
        mbar_wait_long(sb + FREE + cw * 8, (nd & 1) ^ 1);
        loaded(u[2][4].x); loaded(pv[3]);
        bar_sync(3, 256);
        if (lane == 0) mbar_arrive(sb + EMPTY + (it % NST) * 8);
        it++;
#pragma unroll
        for (int i = 0; i < 4; i++) if (ct + i * 256 < 800) *(float2*)(ph + (ct + i * 256) * 2) = make_float2(__uint_as_float(pv[i] << 16), __uint_as_float(pv[i] & 0xFFFF0000u));
        bar_sync(3, 256);
#pragma unroll
        for (int part = 0; part < 2; part++) {
          float a[BDH];
#pragma unroll
          for (int i = 0; i < 5; i++) {
            a[4 * i] = __uint_as_float(u[part][i].x << 16); a[4 * i + 1] = __uint_as_float(u[part][i].x & 0xFFFF0000u);
            a[4 * i + 2] = __uint_as_float(u[part][i].y << 16); a[4 * i + 3] = __uint_as_float(u[part][i].y & 0xFFFF0000u);
          }
#pragma unroll 1
          for (int f4 = 0; f4 < 5; f4++) {
            float4 q = make_float4(0.f, 0.f, 0.f, 0.f);
#pragma unroll
            for (int dd = 0; dd < BDH; dd++) {
              const float4 p = *(const float4*)(ph + (hh * BDH + dd) * BDH + f4 * 4);
              q.x = fmaf(a[dd], p.x, q.x); q.y = fmaf(a[dd], p.y, q.y); q.z = fmaf(a[dd], p.z, q.z); q.w = fmaf(a[dd], p.w, q.w);
            }
            bf16* dst = T + (part * 80 + f4 * 16 + hh * 2) * 64 + r;
            dst[0] = __float2bfloat16(q.x); dst[64] = __float2bfloat16(q.y); dst[8 * 64] = __float2bfloat16(q.z); dst[9 * 64] = __float2bfloat16(q.w);
          }
        }
#pragma unroll
        for (int i = 0; i < 5; i++) {
          uint16_t* dst = (uint16_t*)T + (160 + hh * BDH + i * 4) * 64 + r;
          dst[0] = (uint16_t)u[2][i].x; dst[64] = (uint16_t)(u[2][i].x >> 16); dst[128] = (uint16_t)u[2][i].y; dst[192] = (uint16_t)(u[2][i].y >> 16);
        }
        bar_sync(3, 256);
        for (int i = ct; i < 240 * 8; i += 256) *(uint4*)(g_wb1 + (gq * 240 + (i >> 3)) * DM + k0 + (i & 7) * 8) = *(const uint4*)(T + i * 8);
        if (ct < 240) {
          float cs = 0.f;
#pragma unroll
          for (int i = 0; i < 8; i++) {
            const uint4 v = *(const uint4*)(T + ct * 64 + ((i + ct) & 7) * 8);
            const uint32_t vv[4] = {v.x, v.y, v.z, v.w};
#pragma unroll
            for (int e = 0; e < 4; e++) cs += __uint_as_float(vv[e] << 16) + __uint_as_float(vv[e] & 0xFFFF0000u);
          }
          g_cs[(k0 >> 6) * 3 * DM + gq * 240 + ct] = cs;
        }
        bar_sync(3, 256);
      }
    }
  }
  __syncwarp();
  if (CTAIL ? SENT && blockIdx.x == 0 : !__shfl_sync(0xffffffffu, early, 0)) asm volatile("griddepcontrol.wait;" ::: "memory");
}

#define KVREL 0
#define KVF 0
#define PFA_N 2
#define PFA_DELAY 500
#define PFA_LIMIT 30000
#define PFL 2
#define RESP 1
#define BTR 2
#define PFQ 0
#define PFQ_C 9
#define PFQ_N 8
#define PFQ_S 0
#define KVO 1
#define BOG 0
#define BWP 0
#define BWN 4
#define BEF 0
#define PFL_X 0
#define PFL_W2 4
#define PFL_C2 3
#define PFE 0
#define PFE_S 0
#define PFL_B 5
#define PFL_C 9
#define PFL_D 0
#define PFL_S 0
#define PFL_ORD 0x0312
#define PFB_KV 1
#define PFB_DELAY 2000
#define PFA_ORD 0x0312
#define PFA_SLEEP 0
#define BTPF 0
#define BHALF 0
#define LDL8 3
#define W2E 1
#define PREFETCH_A 0
namespace bk {
constexpr uint32_t STAGE = 47104, NST = 4;
constexpr uint32_t W2 = 0, A2 = 102400;
constexpr uint32_t PHI = 102400, VS = PHI + 128 * 336, KVS = PHI;
constexpr uint32_t OS = A2 + 65536;
constexpr uint32_t PHQ = NST * STAGE;
constexpr uint32_t CS = PHQ;
constexpr uint32_t MISC = PHQ + 128 * 336;
constexpr int NST2 = 7;
constexpr uint32_t FULL = MISC, EMPTY = MISC + 32, EMPTY2 = MISC + 64, BW2 = MISC + 128, BOK = MISC + 136, BKR = MISC + 144, BKV = MISC + 152, FULL2 = MISC + 160;
constexpr uint32_t SMEM = MISC + 256;
}
DEVI void feature_map(const float* d, uint32_t dst) {
#pragma unroll
  for (int r = 0; r < 2; r++) {
    const float l2e = 1.4426950408889634f;
    float mx = d[2 * r], mn = d[2 * r];
#pragma unroll
    for (int i = 1; i < 20; i++) { const float x = d[(i >> 1) * 4 + 2 * r + (i & 1)]; mx = fmaxf(mx, x); mn = fminf(mn, x); }
    mx *= l2e; mn *= l2e;
    float p[20], n[20], sp = 0.f, sn = 0.f;
#pragma unroll
    for (int i = 0; i < 20; i++) {
      const float x = d[(i >> 1) * 4 + 2 * r + (i & 1)];
      p[i] = ex2(fmaf(x, l2e, -mx)); n[i] = ex2(fmaf(x, -l2e, mn)); sp += p[i]; sn += n[i];
    }
    sp = rcp(sp); sn = rcp(sn);
#pragma unroll
    for (int i = 0; i < 5; i++)
      sts128(dst + r * 8 * 336 + i * 16, pack_bf16(p[4 * i] * sp, n[4 * i] * sn), pack_bf16(p[4 * i + 1] * sp, n[4 * i + 1] * sn),
             pack_bf16(p[4 * i + 2] * sp, n[4 * i + 2] * sn), pack_bf16(p[4 * i + 3] * sp, n[4 * i + 3] * sn));
  }
}

__global__ void __launch_bounds__(384, 1)
layerb_kernel(int layer, uint32_t nw2, Sync* sy, const bf16* __restrict__ xin, bf16* __restrict__ out, const void* wa0, const void* wa1, const void* wa2, const void* wa3,
              const __grid_constant__ CUtensorMap mx, const __grid_constant__ CUtensorMap mw1, const __grid_constant__ CUtensorMap mo,
              const __grid_constant__ CUtensorMap mos) {
  using namespace bk;
  extern __shared__ __align__(1024) uint8_t smraw[];
  const uint32_t sb = smem_u32(smraw);
  const int tid = threadIdx.x, lane = tid & 31;
  const int wg = __shfl_sync(0xffffffffu, tid >> 7, 0), w = __shfl_sync(0xffffffffu, (tid >> 5) & 3, 0);
  const int rt = CTAIL ? 15 - (blockIdx.x >> 3) : blockIdx.x >> 3, gq = blockIdx.x & 7;
  if (blockIdx.x >= 128) {
    asm volatile("griddepcontrol.launch_dependents;");
    if (BLN && tid >= 32) {
      asm volatile("griddepcontrol.wait;" ::: "memory");
      for (int i = (blockIdx.x - 128) * 352 + tid - 32; i < (NSEG - 1) * 24 * 32; i += (gridDim.x - 128) * 352) ((uint4*)g_ar)[(i >> 5) * 64 + (i & 31)] = make_uint4(0, 0, 0, 0);
    }
    if (tid == 0) {
      asm volatile("griddepcontrol.wait;" ::: "memory");
      const uint32_t t0 = clk32();
      __nanosleep(PFA_DELAY);
      const int nc = gridDim.x - 128;
      for (int i = blockIdx.x - 128; i < PFA_N * 480 && clk32() - t0 < PFA_LIMIT; i += nc) {
        const int m = PFA_ORD >> (i / 480 * 4) & 3;
        const char* p = (const char*)(m == 0 ? wa0 : m == 1 ? wa1 : m == 2 ? wa2 : wa3) + (size_t)(i % 480) * 16384;
        asm volatile("cp.async.bulk.prefetch.L2.global [%0], 16384;" :: "l"(p) : "memory");
        if (PFA_SLEEP) __nanosleep(PFA_SLEEP);
      }
    }
    return;
  }
  if (tid == 0) {
    for (int i = 0; i < NST; i++) { mbar_init(sb + FULL + i * 8, 1); mbar_init(sb + EMPTY + i * 8, 8); }
    for (int i = 0; i < NST2; i++) { mbar_init(sb + FULL2 + i * 8, 1); mbar_init(sb + EMPTY2 + i * 8, 8); }
    mbar_init(sb + BW2, 1); mbar_init(sb + BOK, 256); mbar_init(sb + BKV, 1); mbar_init(sb + BKR, 1);
    asm volatile("fence.mbarrier_init.release.cluster;" ::: "memory");
  }
  if (!LDL8) asm volatile("griddepcontrol.launch_dependents;");
  if (wg == 0) {
    asm volatile("setmaxnreg.dec.sync.aligned.u32 40;");
    bar_sync(0, 384);
    if (tid == 32 && layer == 0 && PREFETCH_A) {
      asm volatile("griddepcontrol.wait;" ::: "memory");
      __nanosleep(PFB_DELAY);
      for (int i = 0; i < 32; i++) {
        const char* p = (const char*)(PFB_KV ? (i < 16 ? wa2 : wa1) : (i < 16 ? wa3 : wa0)) + (size_t)blockIdx.x * 61440 + (i & 15) * 3840;
        asm volatile("cp.async.bulk.prefetch.L2.global [%0], 3840;" :: "l"(p) : "memory");
        __nanosleep(PREFETCH_A);
      }
    }
    if (PFL && w == 1 && !layer) {
      for (int c = PFL_C % NST; c <= PFL_C; c += NST) mbar_wait_long(sb + FULL + PFL_C % NST * 8, c / NST & 1);
      if (PFL_D) __nanosleep(PFL_D);
      uint32_t acc = 0;
#pragma unroll 1
      for (int i = 0; i < PFL * 15 / PFL_B - PFL_X; i++) {
        const int m = PFL_ORD >> (i / (15 / PFL_B) * 4) & 3;
        if (PFL_W2 && i == PFL_W2) mbar_wait_long(sb + FULL2 + PFL_C2 * 8, 0);
        const char* p = (const char*)(m == 0 ? wa0 : m == 1 ? wa1 : m == 2 ? wa2 : wa3) + (blockIdx.x * 15 + i % (15 / PFL_B) * PFL_B) * 4096 + lane * 128;
        uint32_t v[PFL_B];
#pragma unroll
        for (int n = 0; n < PFL_B; n++) asm volatile("ld.global.cg.L2::128B.u32 %0, [%1];" : "=r"(v[n]) : "l"(p + n * 4096) : "memory");
#pragma unroll
        for (int n = 0; n < PFL_B; n++) acc |= v[n];
        if (PFL_S) __nanosleep(PFL_S);
        loaded(acc);
      }
    }
    if (PFQ && tid == 96 && !layer) {
      if (PFQ == 1) for (int c = PFQ_C % NST; c <= PFQ_C; c += NST) mbar_wait_long(sb + FULL + PFQ_C % NST * 8, c / NST & 1);
      if (PFQ == 2) mbar_wait_long(sb + FULL2 + PFQ_C * 8, 0);
      if (PFQ == 3) mbar_wait_long(sb + BKR, 0);
      if (PFQ == 4) mbar_wait_long(sb + BOK, 0);
#pragma unroll 1
      for (int i = 0; i < PFQ_N; i++) {
        asm volatile("cp.async.bulk.prefetch.L2.global [%0], 7680;" :: "l"((const char*)(i < 8 ? wa0 : wa3) + (blockIdx.x * 8 + (i & 7)) * 7680) : "memory");
        if (PFQ_S) __nanosleep(PFQ_S);
      }
    }
    if (PFE && tid == 96 && !layer && blockIdx.x < 32) {
#pragma unroll 1
      for (int i = 0; i < PFE * 15; i++) {
        const int m = PFL_ORD >> (i / 15 * 4) & 3;
        const char* p = (const char*)(m == 0 ? wa0 : m == 1 ? wa1 : m == 2 ? wa2 : wa3) + (blockIdx.x * 15 + i % 15) * 16384;
        asm volatile("cp.async.bulk.prefetch.L2.global [%0], 16384;" :: "l"(p) : "memory");
        if (PFE_S) __nanosleep(PFE_S);
      }
    }
    if (BLN && w == 3 && layer) {
      asm volatile("griddepcontrol.wait;" ::: "memory");
      uint4* p = (uint4*)g_bst + blockIdx.x * 64 + lane;
      p[0] = p[32] = make_uint4(0, 0, 0, 0);
    }
    if (w == 2) {
      bar_sync(4, 288);
      if (lane == 0) {
        if (KVREL) red_release(&sy->bkv_cnt[gq]);
        spin_count(&sy->bkv_cnt[gq], 16);
        mbar_arrive(sb + BKR);
      }
    }
    if (tid == 0) {
      if (BTPF) {
        asm volatile("prefetch.tensormap [%0];" :: "l"(&mx) : "memory"); asm volatile("prefetch.tensormap [%0];" :: "l"(&mw1) : "memory");
        asm volatile("prefetch.tensormap [%0];" :: "l"(&mos) : "memory"); asm volatile("prefetch.tensormap [%0];" :: "l"(&mo) : "memory");
      }
      const int npre = BFL ? (rt >= tl::RT0 ? NST : 0) : (BWP >> layer & 1) ? BWN : 0;
      if (!BFL)
#pragma unroll 1
        for (int c = 0; c < npre; c++) { mbar_expect(sb + FULL + c * 8, STAGE); tma2d(sb + c * STAGE + 16384, &mw1, c * 64, gq * 240, sb + FULL + c * 8); }
      if (BFL) { wait_count(&sy->pad1[0], nw2); asm volatile("fence.proxy.async.global;" ::: "memory"); }
      else asm volatile("griddepcontrol.wait;" ::: "memory");
      GT(2, 0);
      if (BFL && npre) {
#pragma unroll 1
        for (int c = 0; c < (int)NST; c++) { mbar_expect(sb + FULL + c * 8, STAGE); tma2d(sb + c * STAGE + 16384, &mw1, c * 64, gq * 240, sb + FULL + c * 8); }
        spin_count(&sy->pro[1 + rt - tl::RT0], 64);
        asm volatile("fence.proxy.async.global;" ::: "memory");
      }
#pragma unroll 1
      for (int c = 0; c < 10; c++) {
        const uint32_t st = c % NST, a = sb + st * STAGE, fb = sb + FULL + st * 8;
        if (c >= npre) {
          mbar_wait_long(sb + EMPTY + st * 8, ((c / NST) & 1) ^ 1);
          mbar_expect(fb, STAGE - (BHALF & 1) * 8192);
        }
        tma2d_h<(BEF & 2) != 0>(a, &mx, c * 64, rt * 128, fb);
        if (c >= npre) tma2d_h<(BEF & 1) != 0>(a + 16384, &mw1, c * 64, gq * 240, fb);
      }
      mbar_wait_long(sb + BKV, 0);
      mbar_expect(sb + BW2, 102400);
      PT(1, 0);
      for (int c = 0; c < 2; c++) bulk_load_plain(sb + W2 + c * 51200, g_wb2 + gq * 6400 + c * 3200, 51200, sb + BW2);
      mbar_wait_long(sb + BOK, 0);
      if (BOG) red_release(&sy->bo_cnt[rt]);
      else {
        asm volatile("cp.async.bulk.tensor.2d.global.shared::cta.bulk_group [%0, {%2, %3}], [%1];" :: "l"(&mos), "r"(sb + OS), "r"(gq * 80), "r"(rt * 128) : "memory");
        asm volatile("cp.async.bulk.commit_group; cp.async.bulk.wait_group 0;" ::: "memory");
        publish_bulk<WFEN>(&sy->bo_cnt[rt]);
      }
      spin_count(&sy->bo_cnt[rt], 8);
      if (BOG) asm volatile("fence.proxy.async.global;" ::: "memory"); else fence_flag_to_bulk();
#pragma unroll 1
      for (int c = 0; c < 10; c++) {
        const uint32_t st = c < NST2 ? c : c - NST2, fb = sb + FULL2 + st * 8;
        if (c >= NST2) mbar_wait_long(sb + EMPTY2 + st * 8, 0);
        mbar_expect(fb, 16384 - (BHALF >> 1 & 1) * 8192);
        tma2d_h<(BEF & 4) != 0>(sb + A2 + st * 16384, &mo, c * 64, rt * 128, fb);
      }
    }
  } else {
    asm volatile("setmaxnreg.inc.sync.aligned.u32 232;");
    bar_sync(0, 384);
    if (!BFL) asm volatile("griddepcontrol.wait;" ::: "memory");
    const int cw = wg - 1, g = lane >> 2, t = lane & 3, ct = tid - 128;
    const int row = cw * 64 + w * 16 + g;
    float rs[2], ms[2], cv[10];
    if (BFL) {
      mbar_wait_long(sb + FULL, 0);
#pragma unroll
      for (int e = 0; e < 2; e++) asm volatile("ld.global.cg.v2.f32 {%0,%1}, [%2];" : "=f"(ms[e]), "=f"(rs[e]) : "l"(&sy->rstat[rt * 128 + row + 8 * e]) : "memory");
#pragma unroll
      for (int i = 0; i < 10; i++) asm volatile("ld.global.cg.f32 %0, [%1];" : "=f"(cv[i]) : "l"(g_cs + i * 3 * DM + gq * 240 + min(ct, 239)) : "memory");
    } else {
      float cs = 0.f;
      if (ct < 240) {
#pragma unroll
        for (int i = 0; i < 10; i++) cs += __ldcg(g_cs + i * 3 * DM + gq * 240 + ct);
      }
      if (!CTAIL)
#pragma unroll
      for (int e = 0; e < 2; e++) {
        const float2 st = __ldcg(&sy->rstat[rt * 128 + row + 8 * e]);
        const float m = st.x * (1.0f / DM);
        rs[e] = rsqrtf(fmaxf(st.y * (1.0f / DM) - m * m, 0.f) + 1e-5f);
        ms[e] = -m * rs[e];
      }
      if (ct < 240) sts32(sb + CS + ct * 4, __float_as_uint(cs));
      bar_sync(3, 256);
      if (CTAIL) {
        mbar_wait_long(sb + FULL, 0);
#pragma unroll
        for (int e = 0; e < 2; e++) asm volatile("ld.global.cg.v2.f32 {%0,%1}, [%2];" : "=f"(ms[e]), "=f"(rs[e]) : "l"(&sy->rstat[rt * 128 + row + 8 * e]) : "memory");
      }
    }
    uint32_t res[20];
    const int off = (rt * 128 + row) * DM + gq * 80 + 2 * t;
    {
      float d[120];
#pragma unroll
      for (int i = 0; i < 120; i++) d[i] = 0.f;
      for (int c = 0; c < 10; c++) {
        const uint32_t st = c % NST, a = sb + st * STAGE;
        mbar_wait_long(sb + FULL + st * 8, (c / NST) & 1);
        if (c == 0 && ct == 0) PT(1, 15);
        const uint64_t da = mkdesc(a + cw * 8192, 16, 1024, 1), db = mkdesc(a + 16384, 16, 1024, 1);
        wg_fence();
#pragma unroll
        for (int k = 0; k < 4; k++) wgmma_n240_nn(d, da + k * 2, db + k * 2, c | k);
        wg_commit();
        if (c > 0) { wg_wait<1>(); if (lane == 0) mbar_arrive(sb + EMPTY + ((c - 1) % NST) * 8); }
        if (BFL && c == 8) {
          float cs = 0.f;
#pragma unroll
          for (int i = 0; i < 10; i++) cs += cv[i];
          if (ct < 240) sts32(sb + CS + ct * 4, __float_as_uint(cs));
        }
      }
      if (BFL) bar_sync(3, 256);
      wg_wait<0>();
      if (lane == 0) mbar_arrive(sb + EMPTY + (9 % NST) * 8);
      if (ct == 0) PT(1, 2);
      if (CTAIL)
#pragma unroll
      for (int e = 0; e < 2; e++) {
        const float m = ms[e] * (1.0f / DM);
        rs[e] = rsqrtf(fmaxf(rs[e] * (1.0f / DM) - m * m, 0.f) + 1e-5f);
        ms[e] = -m * rs[e];
      }
#pragma unroll
      for (int i = 0; i < 30; i++) {
        const float2 c = lds64f(sb + CS + (8 * i + 2 * t) * 4);
        d[4 * i] = fmaf(c.x, ms[0], d[4 * i] * rs[0]); d[4 * i + 1] = fmaf(c.y, ms[0], d[4 * i + 1] * rs[0]);
        d[4 * i + 2] = fmaf(c.x, ms[1], d[4 * i + 2] * rs[1]); d[4 * i + 3] = fmaf(c.y, ms[1], d[4 * i + 3] * rs[1]);
      }
      if (ct == 0) PT(1, 11);
      bar_sync(3, 256);
      if (W2E && ct == 0) mbar_arrive(sb + BKV);
      feature_map(&d[40], sb + PHI + row * 336 + t * 80);
      if (ct == 0) PT(1, 12);
#pragma unroll
      for (int i = 0; i < 10; i++) {
        const int c = i * 8 + 2 * t;
        const uint32_t a = sb + VS + row * 208 + (c / 20) * 48 + (c % 20) * 2;
        sts32(a, pack_bf16(d[80 + 4 * i], d[81 + 4 * i])); sts32(a + 8 * 208, pack_bf16(d[82 + 4 * i], d[83 + 4 * i]));
      }
      { const uint32_t a = sb + VS + row * 208 + t * 48 + 40; sts64(a, 0x3F80u, 0u); sts64(a + 8 * 208, 0x3F80u, 0u); }
      bar_sync(3, 256);
      if (ct == 0) PT(1, 13);
      {
        float kv[5][4];
#pragma unroll
        for (int i = 0; i < 20; i++) kv[i >> 2][i & 3] = 0.f;
        const uint32_t pa = sb + PHI + ((lane >> 4) * 8 + (lane & 7)) * 336 + w * 80 + ((lane >> 3) & 1) * 16;
        const uint32_t va = sb + VS + lane * 208 + w * 48;
#pragma unroll
        for (int k2 = 0; k2 < 4; k2++) {
          uint32_t b[3][4];
#pragma unroll
          for (int n = 0; n < 3; n++) ldsm4t(b[n], va + k2 * 32 * 208 + n * 16);
#pragma unroll
          for (int kk = 0; kk < 2; kk++) {
            uint32_t a[4], a2[4];
            ldsm4t(a, pa + (k2 * 32 + kk * 16) * 336 + cw * 32);
            ldsm4t(a2, pa + (k2 * 32 + kk * 16) * 336 + 64);
#pragma unroll
            for (int n = 0; n < 3; n++) mma16816(kv[n], a, b[n][2 * kk], b[n][2 * kk + 1]);
            if (cw == 0) { mma16816(kv[3], a2, b[0][2 * kk], b[0][2 * kk + 1]); mma16816(kv[4], a2, b[1][2 * kk], b[1][2 * kk + 1]); }
            else mma16816(kv[3], a2, b[2][2 * kk], b[2][2 * kk + 1]);
          }
        }
        float* p = g_bkv + ((gq * 4 + w) * BF + g) * 24 + 2 * t;
        PINF(kv[0][0]); PINF(kv[3][0]);
        if (ct == 0) PT(1, 14);
        if (KVO) {
          float* f = g_bkv + (gq * 4 + w) * BF * 24;
#pragma unroll
          for (int n = 0; n < 3; n++)
            asm volatile("red.relaxed.gpu.global.add.v4.f32 [%0], {%1,%2,%3,%4};" :: "l"(f + (cw * 3 + n) * 128 + lane * 4), "f"(kv[n][0]), "f"(kv[n][1]), "f"(kv[n][2]), "f"(kv[n][3]) : "memory");
          asm volatile("red.relaxed.gpu.global.add.v2.f32 [%0], {%1,%2};" :: "l"(f + 768 + cw * 128 + lane * 2), "f"(kv[3][0]), "f"(kv[3][1]) : "memory");
          if (cw == 0) asm volatile("red.relaxed.gpu.global.add.v2.f32 [%0], {%1,%2};" :: "l"(f + 768 + 64 + lane * 2), "f"(kv[4][0]), "f"(kv[4][1]) : "memory");
        } else {
#pragma unroll
        for (int n = 0; n < 3; n++) {
          asm volatile("red.relaxed.gpu.global.add.v2.f32 [%0], {%1,%2};" :: "l"(p + cw * 16 * 24 + n * 8), "f"(kv[n][0]), "f"(kv[n][1]) : "memory");
          asm volatile("red.relaxed.gpu.global.add.v2.f32 [%0], {%1,%2};" :: "l"(p + (cw * 16 + 8) * 24 + n * 8), "f"(kv[n][2]), "f"(kv[n][3]) : "memory");
        }
        asm volatile("red.relaxed.gpu.global.add.v2.f32 [%0], {%1,%2};" :: "l"(p + 32 * 24 + cw * 16), "f"(kv[3][0]), "f"(kv[3][1]) : "memory");
        if (cw == 0) asm volatile("red.relaxed.gpu.global.add.v2.f32 [%0], {%1,%2};" :: "l"(p + 32 * 24 + 8), "f"(kv[4][0]), "f"(kv[4][1]) : "memory");
        }
      }
      if (ct == 0) PT(1, 3);
      if (LDL8 == 4) asm volatile("griddepcontrol.launch_dependents;");
      if (KVF == 1) __threadfence();
      bar_sync(4, 288);
      if (!KVREL) { if (ct == 0) red_release(&sy->bkv_cnt[gq]); __syncwarp(); }
      if (ct == 0) PT(1, 9);
      if (!W2E && ct == 0) mbar_arrive(sb + BKV);
      feature_map(&d[0], sb + PHQ + row * 336 + t * 80);
    }
    if (ct == 0) PT(1, 4);
    const int tw = (rt * 128 + cw * 64 + w * 16) * DM + gq * 80, to0 = tw + (lane >> 3) * DM + (lane & 7) * 8, to4 = tw + (lane >> 1) * DM + 64 + (lane & 1) * 8;
    auto load_res = [&]() {
      if (BTR == 2) {
#pragma unroll
        for (int i = 0; i < 5; i++) ldcg128(*(uint32_t(*)[4])&res[4 * i], g_xa + (i < 4 ? to0 + i * 4 * DM : to4));
      } else {
#pragma unroll
        for (int i = 0; i < 10; i++) { res[2 * i] = __ldcg((const uint32_t*)(g_xa + off + i * 8)); res[2 * i + 1] = __ldcg((const uint32_t*)(g_xa + off + i * 8 + 8 * DM)); }
      }
    };
    if (RESP == 0) load_res();
    mbar_wait_long(sb + BKR, 0);
    if (LDL8 == 1) asm volatile("griddepcontrol.launch_dependents;");
    if (KVF == 2) __threadfence();
    if (KVF == 3) __nanosleep(1500);
    if (ct == 0) PT(1, 5);
    {
      float4 a[4];
#pragma unroll
      for (int i = 0; i < 4; i++) a[i] = __ldcg((const float4*)(g_bkv + gq * 4 * BF * 24) + min(ct + i * 256, 4 * BF * 6 - 1));
#pragma unroll
      for (int i = 0; i < 4; i++) {
        const int e = ct + i * 256;
        if (!KVO) { if (e < 4 * BF * 6) sts64(sb + KVS + e * 8, pack_bf16(a[i].x, a[i].y), pack_bf16(a[i].z, a[i].w)); }
        else if (e < 4 * BF * 6) {
          const int hh = (e >> 4) * 69 >> 10, r = e - hh * 240, tl = r >> 5, q = r - 192;
          const uint32_t hb = sb + KVS + hh * 1920;
          const uint32_t p0 = q < 0 ? hb + ((tl >= 3) * 16 + (r >> 2 & 7)) * 48 + (tl >= 3 ? tl - 3 : tl) * 16 + (r & 3) * 4 : hb + (32 + (q >> 1 & 7)) * 48 + (q >> 4) * 16 + (q & 1) * 8;
          sts32(p0, pack_bf16(a[i].x, a[i].y)); sts32(p0 + (q < 0 ? 8 * 48 : 4), pack_bf16(a[i].z, a[i].w));
        }
      }
    }
    if (RESP == 2) load_res();
    bar_sync(3, 256);
    {
      float o[4][3][4];
#pragma unroll
      for (int hh = 0; hh < 4; hh++) {
        uint32_t a0[4], a1[4], a2[2], c[4];
        const uint32_t qa = sb + PHQ + (cw * 64 + w * 16 + (lane & 15)) * 336 + hh * 80;
        ldsm4(a0, qa + (lane >> 4) * 16); ldsm4(a1, qa + 32 + (lane >> 4) * 16); ldsm2(a2, qa + 64);
        ldsm4t(c, sb + KVS + hh * 1920 + (32 + (lane & 7)) * 48 + min(lane >> 3, 2) * 16);
#pragma unroll
        for (int n = 0; n < 3; n++) {
          uint32_t b[4];
          ldsm4t(b, sb + KVS + hh * 1920 + lane * 48 + n * 16);
          o[hh][n][0] = o[hh][n][1] = o[hh][n][2] = o[hh][n][3] = 0.f;
          mma16816(o[hh][n], a0, b[0], b[1]); mma16816(o[hh][n], a1, b[2], b[3]); mma1688(o[hh][n], a2[0], a2[1], c[n]);
        }
      }
      const uint32_t oa = sb + OS + row * 160 + t * 4;
#pragma unroll
      for (int hh = 0; hh < 4; hh++) {
        const float i0 = __fdividef(1.0f, __shfl_sync(0xffffffffu, o[hh][2][0], (lane & 28) + 2) + 1e-6f);
        const float i1 = __fdividef(1.0f, __shfl_sync(0xffffffffu, o[hh][2][2], (lane & 28) + 2) + 1e-6f);
#pragma unroll
        for (int n = 0; n < 3; n++)
          if (n < 2 || t < 2) {
            sts32(oa + hh * 40 + n * 16, pack_bf16(o[hh][n][0] * i0, o[hh][n][1] * i0));
            sts32(oa + hh * 40 + n * 16 + 8 * 160, pack_bf16(o[hh][n][2] * i1, o[hh][n][3] * i1));
          }
      }
      if (BOG) {
        __syncwarp();
        uint32_t y[5][4];
#pragma unroll
        for (int i = 0; i < 5; i++) lds128(y[i], sb + OS + (cw * 64 + w * 16) * 160 + (i < 4 ? (i * 4 + (lane >> 3)) * 160 + (lane & 7) * 16 : (lane >> 1) * 160 + 128 + (lane & 1) * 16));
#pragma unroll
        for (int i = 0; i < 5; i++) *(uint4*)(g_bo + (i < 4 ? to0 + i * 4 * DM : to4)) = make_uint4(y[i][0], y[i][1], y[i][2], y[i][3]);
      }
      fence_async();
    }
    if (ct == 0) PT(1, 6);
    mbar_arrive(sb + BOK);
    if (RESP == 1) load_res();
    if (LDL8 == 2) asm volatile("griddepcontrol.launch_dependents;");
    float d[40];
#pragma unroll
    for (int i = 0; i < 40; i++) d[i] = 0.f;
    mbar_wait_long(sb + BW2, 0);
    for (int c = 0; c < 10; c++) {
      const uint32_t st = c % NST2;
      mbar_wait_long(sb + FULL2 + st * 8, c / NST2);
      if (ct == 0 && c == 0) PT(1, 7);
      if (LDL8 == 3 && c == 0) asm volatile("griddepcontrol.launch_dependents;");
      const uint64_t da = mkdesc(sb + A2 + st * 16384 + cw * 8192, 16, 1024, 1), db = mkdesc(sb + W2 + c * 10240, 2048, 256, 3);
      wg_fence();
#pragma unroll
      for (int k = 0; k < 4; k++) wgmma_n80_nt(d, da + k * 2, db + k * 32, c | k);
      wg_commit();
      if (c > 0 && c <= 10 - NST2) { wg_wait<1>(); if (lane == 0) mbar_arrive(sb + EMPTY2 + (c - 1) * 8); }
    }
    wg_wait<0>();
    if (ct == 0) PT(1, 10);
    if (BTR == 2) {
      const uint32_t tb = sb + A2 + (w >> 1) * 16384 + cw * 8192 + (w & 1) * 3072;
      bar_sync(5 + cw, 128);
#pragma unroll
      for (int i = 0; i < 5; i++)
        stsm4(tb + (lane & 15) * 176 + (2 * i + (lane >> 4)) * 16, pack_bf16(d[8 * i], d[8 * i + 1]), pack_bf16(d[8 * i + 2], d[8 * i + 3]), pack_bf16(d[8 * i + 4], d[8 * i + 5]), pack_bf16(d[8 * i + 6], d[8 * i + 7]));
      __syncwarp();
      float a[5][2];
#pragma unroll
      for (int i = 0; i < 5; i++) {
        uint32_t y[4];
        lds128(y, tb + (i < 4 ? (i * 4 + (lane >> 3)) * 176 + (lane & 7) * 16 : (lane >> 1) * 176 + 128 + (lane & 1) * 16));
        a[i][0] = a[i][1] = 0.f;
#pragma unroll
        for (int e = 0; e < 4; e++) {
          const uint32_t x = res[4 * i + e];
          const uint32_t z = res[4 * i + e] = pack_bf16(__uint_as_float(y[e] << 16) + __uint_as_float(x << 16), __uint_as_float(y[e] & 0xFFFF0000u) + __uint_as_float(x & 0xFFFF0000u));
          const float lo = __uint_as_float(z << 16), hi = __uint_as_float(z & 0xFFFF0000u);
          a[i][0] += lo + hi; a[i][1] = fmaf(lo, lo, fmaf(hi, hi, a[i][1]));
        }
        if (!BLN || layer) *(uint4*)(out + (i < 4 ? to0 + i * 4 * DM : to4)) = make_uint4(res[4 * i], res[4 * i + 1], res[4 * i + 2], res[4 * i + 3]);
      }
      if (BLN && !layer) {
        float2* bst = g_bst + (rt * 128 + cw * 64 + w * 16) * 8;
        const bool b0 = lane & 1, b1 = lane & 2;
        const int r = (lane & 3) * 4 + (lane >> 3);
        float s[2];
#pragma unroll
        for (int m = 0; m < 2; m++) {
          const float u0 = (b0 ? a[1][m] : a[0][m]) + __shfl_xor_sync(0xffffffffu, b0 ? a[0][m] : a[1][m], 1);
          const float u1 = (b0 ? a[3][m] : a[2][m]) + __shfl_xor_sync(0xffffffffu, b0 ? a[2][m] : a[3][m], 1);
          const float e = a[4][m] + __shfl_xor_sync(0xffffffffu, a[4][m], 1);
          s[m] = (b1 ? u1 : u0) + __shfl_xor_sync(0xffffffffu, b1 ? u0 : u1, 2);
          s[m] += __shfl_xor_sync(0xffffffffu, s[m], 4) + __shfl_sync(0xffffffffu, e, 2 * r);
        }
        asm volatile("{.reg .pred p; .reg .b64 v; setp.eq.u32 p, %3, 0; mov.b64 v, {%1,%2}; @p st.relaxed.gpu.global.b64 [%0], v;}"
                     :: "l"(bst + r * 8 + gq), "r"(__float_as_uint(s[0])), "r"(__float_as_uint(s[1]) | 0x80000000u), "r"(lane & 4) : "memory");
#pragma unroll
        for (int i = 0; i < 5; i++) *(uint4*)(out + (i < 4 ? to0 + i * 4 * DM : to4)) = make_uint4(res[4 * i], res[4 * i + 1], res[4 * i + 2], res[4 * i + 3]);
        if (ct == 0) PT(1, 8);
        uint32_t u[2][4];
        for (int n = 0; n < 4000000; n++) {
#pragma unroll
          for (int e = 0; e < 2; e++)
            asm volatile("{.reg .b64 a, b; ld.relaxed.gpu.global.v2.b64 {a, b}, [%4]; mov.b64 {%0,%1}, a; mov.b64 {%2,%3}, b;}"
                         : "=r"(u[e][0]), "=r"(u[e][1]), "=r"(u[e][2]), "=r"(u[e][3]) : "l"(bst + lane * 4 + e * 2) : "memory");
          if (__all_sync(0xffffffffu, (int)(u[0][1] & u[0][3] & u[1][1] & u[1][3]) < 0)) break;
        }
        float s1 = __uint_as_float(u[0][0]) + __uint_as_float(u[0][2]) + (__uint_as_float(u[1][0]) + __uint_as_float(u[1][2]));
        float s2 = __uint_as_float(u[0][1]) + __uint_as_float(u[0][3]) + (__uint_as_float(u[1][1]) + __uint_as_float(u[1][3]));
        s1 += __shfl_xor_sync(0xffffffffu, s1, 1); s2 += __shfl_xor_sync(0xffffffffu, s2, 1);
        const float m = s1 * (1.0f / DM), sc = rsqrtf(fmaxf(s2 * (-1.0f / DM) - m * m, 0.f) + 1e-5f), sh = -m * sc;
#pragma unroll
        for (int i = 0; i < 5; i++) {
          const float c = i < 4 ? __shfl_sync(0xffffffffu, sc, i * 8 + (lane >> 3) * 2) : sc, h = i < 4 ? __shfl_sync(0xffffffffu, sh, i * 8 + (lane >> 3) * 2) : sh;
          uint32_t z[4];
#pragma unroll
          for (int e = 0; e < 4; e++) z[e] = pack_bf16(fmaf(__uint_as_float(res[4 * i + e] << 16), c, h), fmaf(__uint_as_float(res[4 * i + e] & 0xFFFF0000u), c, h));
          *(uint4*)(g_xn + (i < 4 ? to0 + i * 4 * DM : to4)) = make_uint4(z[0], z[1], z[2], z[3]);
        }
      } else if (ct == 0) PT(1, 8);
    } else {
#pragma unroll
    for (int i = 0; i < 20; i++) res[i] = pack_bf16(d[2 * i] + __uint_as_float(res[i] << 16), d[2 * i + 1] + __uint_as_float(res[i] & 0xFFFF0000u));
    float2* bst = g_bst + (rt * 128 + row) * 8;
    if (BLN && !layer) {
      float a[4] = {0.f, 0.f, 0.f, 0.f};
#pragma unroll
      for (int i = 0; i < 20; i++) {
        const float lo = __uint_as_float(res[i] << 16), hi = __uint_as_float(res[i] & 0xFFFF0000u);
        a[(i & 1) * 2] += lo + hi; a[(i & 1) * 2 + 1] = fmaf(lo, lo, fmaf(hi, hi, a[(i & 1) * 2 + 1]));
      }
      const bool odd = t & 1;
      float s1 = (odd ? a[2] : a[0]) + __shfl_xor_sync(0xffffffffu, odd ? a[0] : a[2], 1), s2 = (odd ? a[3] : a[1]) + __shfl_xor_sync(0xffffffffu, odd ? a[1] : a[3], 1);
      s1 += __shfl_xor_sync(0xffffffffu, s1, 2); s2 += __shfl_xor_sync(0xffffffffu, s2, 2);
      asm volatile("{.reg .pred p; .reg .b64 v; setp.lt.u32 p, %3, 2; mov.b64 v, {%1,%2}; @p st.relaxed.gpu.global.b64 [%0], v;}"
                   :: "l"(bst + (t & 1) * 64 + gq), "r"(__float_as_uint(s1)), "r"(__float_as_uint(s2) | 0x80000000u), "r"(t) : "memory");
    }
    const uint32_t tb = sb + A2 + (w >> 1) * 16384 + cw * 8192 + (w & 1) * 3072;
    int go[5];
    if (BTR) {
      bar_sync(5 + cw, 128);
#pragma unroll
      for (int i = 0; i < 5; i++) stsm4(tb + (lane & 15) * 176 + (2 * i + (lane >> 4)) * 16, res[4 * i], res[4 * i + 1], res[4 * i + 2], res[4 * i + 3]);
      __syncwarp();
#pragma unroll
      for (int i = 0; i < 5; i++) {
        const int n = i * 32 + lane, r = n * 205 >> 11;
        lds128(*(uint32_t(*)[4])&res[4 * i], tb + n * 16 + r * 16);
        go[i] = (rt * 128 + cw * 64 + w * 16) * DM + gq * 80 + n * 8 + r * (DM - 80);
      }
#pragma unroll
      for (int i = 0; i < 5; i++) *(uint4*)(out + go[i]) = make_uint4(res[4 * i], res[4 * i + 1], res[4 * i + 2], res[4 * i + 3]);
    } else {
#pragma unroll
      for (int i = 0; i < 20; i++) *(uint32_t*)(out + off + (i >> 1) * 8 + (i & 1) * 8 * DM) = res[i];
    }
    if (ct == 0) PT(1, 8);
    if (BLN && !layer) {
      uint32_t u[2][4];
      for (int n = 0; n < 4000000; n++) {
#pragma unroll
        for (int e = 0; e < 2; e++)
          asm volatile("{.reg .b64 a, b; ld.relaxed.gpu.global.v2.b64 {a, b}, [%4]; mov.b64 {%0,%1}, a; mov.b64 {%2,%3}, b;}"
                       : "=r"(u[e][0]), "=r"(u[e][1]), "=r"(u[e][2]), "=r"(u[e][3]) : "l"(bst + e * 64 + 2 * t) : "memory");
        if (__all_sync(0xffffffffu, (int)(u[0][1] & u[0][3] & u[1][1] & u[1][3]) < 0)) break;
      }
#pragma unroll
      for (int e = 0; e < 2; e++) {
        float s1 = __uint_as_float(u[e][0]) + __uint_as_float(u[e][2]), s2 = __uint_as_float(u[e][1]) + __uint_as_float(u[e][3]);
#pragma unroll
        for (int o = 1; o < 4; o <<= 1) { s1 += __shfl_xor_sync(0xffffffffu, s1, o); s2 += __shfl_xor_sync(0xffffffffu, s2, o); }
        const float m = s1 * (1.0f / DM);
        rs[e] = rsqrtf(fmaxf(s2 * (-1.0f / DM) - m * m, 0.f) + 1e-5f);
        ms[e] = -m * rs[e];
      }
      if (BTR) {
        if (t < 2) sts64(tb + 2816 + (g + 8 * t) * 8, __float_as_uint(t ? rs[1] : rs[0]), __float_as_uint(t ? ms[1] : ms[0]));
        __syncwarp();
#pragma unroll
        for (int i = 0; i < 5; i++) {
          const float2 c = lds64f(tb + 2816 + ((i * 32 + lane) * 205 >> 11) * 8);
          uint32_t z[4];
#pragma unroll
          for (int e = 0; e < 4; e++) z[e] = pack_bf16(fmaf(__uint_as_float(res[4 * i + e] << 16), c.x, c.y), fmaf(__uint_as_float(res[4 * i + e] & 0xFFFF0000u), c.x, c.y));
          *(uint4*)(g_xn + go[i]) = make_uint4(z[0], z[1], z[2], z[3]);
        }
      } else
#pragma unroll
      for (int i = 0; i < 20; i++)
        *(uint32_t*)(g_xn + off + (i >> 1) * 8 + (i & 1) * 8 * DM) = pack_bf16(fmaf(__uint_as_float(res[i] << 16), rs[i & 1], ms[i & 1]), fmaf(__uint_as_float(res[i] & 0xFFFF0000u), rs[i & 1], ms[i & 1]));
    }
    }
    if (ct == 0) GT(2, 1);
  }
}

typedef CUresult (*EncodeFn)(CUtensorMap*, CUtensorMapDataType, cuuint32_t, void*, const cuuint64_t*, const cuuint64_t*, const cuuint32_t*,
                             const cuuint32_t*, CUtensorMapInterleave, CUtensorMapSwizzle, CUtensorMapL2promotion, CUtensorMapFloatOOBfill);
static EncodeFn g_enc = nullptr;
#define P128 1
static void make_map(CUtensorMap* m, const void* p, uint64_t cols, uint64_t rows, uint32_t bc, uint32_t br, bool swz = true, bool p128 = false) {
  cuuint64_t dims[2] = {cols, rows}; cuuint64_t strides[1] = {cols * 2}; cuuint32_t box[2] = {bc, br}; cuuint32_t es[2] = {1, 1};
  g_enc(m, CU_TENSOR_MAP_DATA_TYPE_BFLOAT16, 2, (void*)p, dims, strides, box, es, CU_TENSOR_MAP_INTERLEAVE_NONE, swz ? CU_TENSOR_MAP_SWIZZLE_128B : CU_TENSOR_MAP_SWIZZLE_NONE,
        p128 ? CU_TENSOR_MAP_L2_PROMOTION_L2_128B : CU_TENSOR_MAP_L2_PROMOTION_L2_256B, CU_TENSOR_MAP_FLOAT_OOB_FILL_NONE);
}
static void make_map3(CUtensorMap* m, const void* p, uint64_t cols, uint64_t rows, uint32_t cw, uint32_t br, uint32_t bch) {
  cuuint64_t dims[3] = {cw, rows, cols / cw}; cuuint64_t strides[2] = {cols * 2, cw * 2}; cuuint32_t box[3] = {cw, br, bch}; cuuint32_t es[3] = {1, 1, 1};
  g_enc(m, CU_TENSOR_MAP_DATA_TYPE_BFLOAT16, 3, (void*)p, dims, strides, box, es, CU_TENSOR_MAP_INTERLEAVE_NONE,
        cw == 64 ? CU_TENSOR_MAP_SWIZZLE_128B : cw == 32 ? CU_TENSOR_MAP_SWIZZLE_64B : CU_TENSOR_MAP_SWIZZLE_32B, CU_TENSOR_MAP_L2_PROMOTION_L2_256B, CU_TENSOR_MAP_FLOAT_OOB_FILL_NONE);
}
template <typename T> static void* sym(T& s) { void* p = nullptr; cudaGetSymbolAddress(&p, s); return p; }
template <typename... KA, typename... A>
static void launch(void (*k)(KA...), int grid, int smem, bool pdl, A... a) {
  cudaLaunchConfig_t cfg = {};
  cfg.gridDim = dim3(grid); cfg.blockDim = dim3(384); cfg.dynamicSmemBytes = smem; cfg.stream = cudaStreamPerThread;
  cudaLaunchAttribute at[1]; at[0].id = cudaLaunchAttributeProgrammaticStreamSerialization; at[0].val.programmaticStreamSerializationAllowed = 1;
  cfg.attrs = at; cfg.numAttrs = pdl ? 1 : 0;
  cudaLaunchKernelEx(&cfg, k, a...);
}

constexpr int dev_layers = 2, dev_pdl = 1;
#define EV(i)
extern "C" void kernel_launch(void* const* d_in, const int* in_sizes, int n_in, void* d_out, int out_size) {
  static int nsm = 0;
  if (!g_enc) {
    void* fn = nullptr; cudaDriverEntryPointQueryResult st;
    cudaGetDriverEntryPoint("cuTensorMapEncodeTiled", &fn, cudaEnableDefault, &st);
    g_enc = (EncodeFn)fn;
    cudaFuncSetAttribute(chain_kernel, cudaFuncAttributeMaxDynamicSharedMemorySize, ch::SMEM);
    cudaFuncSetAttribute(worker_kernel, cudaFuncAttributeMaxDynamicSharedMemorySize, wk::SMEM);
    cudaFuncSetAttribute(layerb_kernel, cudaFuncAttributeMaxDynamicSharedMemorySize, bk::SMEM);
    cudaDeviceGetAttribute(&nsm, cudaDevAttrMultiProcessorCount, 0);
  }
  CUtensorMap mq, mk, mv, mo, mx, wx, wq, woa, wos, wwo, wxa, wacc, wwb, bx, bw1, bo, bos;
  make_map(&mq, d_in[2], HD, DM, 64, 128, true, P128); make_map(&mk, d_in[3], HD, DM, 64, 128, true, P128); make_map(&mv, d_in[4], HD, DM, 64, 128, true, P128);
  make_map(&mo, d_in[5], DM, HD, 64, 192, true, P128); make_map3(&mx, sym(g_xn), DM, S_LEN, 64, 32, 5);
  make_map(&wx, sym(g_xn), DM, S_LEN, 64, 128); make_map3(&wq, d_in[2], HD, DM, 64, 64, 3);
  make_map(&woa, sym(g_o), HD, S_LEN, 64, 128); make_map3(&wos, sym(g_o), HD, S_LEN, 64, 64, 3); make_map3(&wwo, d_in[5], DM, HD, 32, 64, 5);
  CUtensorMap toa;
  make_map(&toa, sym(g_o), HD, S_LEN, 64, 64);
  make_map3(&wxa, sym(g_xa), DM, S_LEN, 32, 64, 5);
  if (BSL) make_map3(&wacc, sym(g_sl), DM, NSL * 128, 32, 64, 5);
  else {
    cuuint64_t dims[3] = {32, 2 * ACC_ROWS, DM / 32}, strides[2] = {DM * 4, 128}; cuuint32_t box[3] = {32, 64, 5}, es[3] = {1, 1, 1};
    g_enc(&wacc, CU_TENSOR_MAP_DATA_TYPE_FLOAT32, 3, sym(g_acc), dims, strides, box, es, CU_TENSOR_MAP_INTERLEAVE_NONE, CU_TENSOR_MAP_SWIZZLE_128B,
          CU_TENSOR_MAP_L2_PROMOTION_NONE, CU_TENSOR_MAP_FLOAT_OOB_FILL_NONE);
  }
  make_map(&wwb, d_in[8], 3 * DM, DM, 80, 64, false);
  make_map(&bx, sym(g_xa), DM, S_LEN, 64, (BHALF & 1) ? 64 : 128); make_map(&bw1, sym(g_wb1), DM, 3 * DM, 64, 240);
  make_map(&bo, sym(g_bo), DM, S_LEN, 64, (BHALF & 2) ? 64 : 128); make_map(&bos, sym(g_bo), DM, S_LEN, 80, 128, false);
  cudaStream_t st = cudaStreamPerThread;
  for (int layer = 0; layer < dev_layers; layer++) {
    const bf16* x = layer == 0 ? (const bf16*)d_in[0] : (const bf16*)sym(g_xb);
    Sync* sy = (Sync*)sym(g_sync) + layer;
    EV(layer * 5);
    EV(layer * 5 + 1);
    launch(chain_kernel, 96, ch::SMEM, dev_pdl && layer, mq, mk, mv, mo, mx, (const bf16*)d_in[1], x, 0u, layer, toa, wwo);
    EV(layer * 5 + 2);
    launch(worker_kernel, WGRID ? WGRID : CTAIL ? nsm - 96 : nsm, wk::SMEM, dev_pdl, layer, sy, x, (const bf16*)d_in[9], (const bf16*)d_in[10], wx, wq, woa, wos, wwo, wxa, wacc, wwb);
    EV(layer * 5 + 3);
    launch(layerb_kernel, layer ? 128 : BLN ? 132 : PFA_N ? max(128, min(nsm, 132)) : 128, bk::SMEM, dev_pdl, layer, 2u * (nsm - 96), sy, x, layer == 0 ? (bf16*)sym(g_xb) : (bf16*)d_out,
           (const void*)d_in[2], (const void*)d_in[3], (const void*)d_in[4], (const void*)d_in[5], bx, bw1, bo, bos);
    EV(layer * 5 + 4);
  }
}
```

```cpp
#include <cuda_runtime.h>
#include <cuda_bf16.h>
#include <cuda_fp16.h>
#include <cuda.h>
#include <stdint.h>

typedef __nv_bfloat16 bf16;

constexpr int S_LEN = 2048, DM = 640, NH = 32, DH = 192, NMEM = 8, SEG = 32, NSEG = 64;
constexpr int HD = NH * DH;
constexpr int NKEY = NMEM + SEG;
constexpr int SLAB = 64 * NKEY * 2;
constexpr int AR_STEP_BYTES = 24 * 1024;
constexpr int BDH = 20, BF = 40;

__device__ __align__(1024) bf16 g_xn[S_LEN * DM];
__device__ __align__(1024) bf16 g_kv[(size_t)NSEG * NH * 2 * DH * NKEY];
__device__ __align__(1024) bf16 g_o[(size_t)S_LEN * HD];
__device__ __align__(1024) bf16 g_xa[S_LEN * DM];
__device__ __align__(1024) bf16 g_xb[S_LEN * DM];
__device__ __align__(32768) uint32_t g_ar[NSEG * AR_STEP_BYTES / 4];
#define RTS 10
constexpr int RT_SPLIT = RTS;
constexpr int ACC_ROWS = (16 - RT_SPLIT) * 128;
#define BSL 1
#define FROWS 32
__device__ __align__(1024) float g_acc[BSL ? 256 : 2 * ACC_ROWS * DM];
#define BFL 0
#define CTAIL 1
constexpr int NSL = 48;
__device__ __align__(1024) bf16 g_sl[BSL ? NSL * 128 * DM : 512];
__device__ __align__(1024) float g_cs[10 * 3 * DM];
__device__ __align__(1024) bf16 g_wb1[3 * DM * DM];
__device__ __align__(1024) uint4 g_wb2[DM * DM / 8];
__device__ __align__(1024) bf16 g_bo[S_LEN * DM];
__device__ __align__(1024) uint4 g_qf[16 * NH * 12 * 256];
struct __align__(1024) Sync {
  uint32_t kv[NSEG * NH];
  uint32_t o[16 * 16];
  uint32_t bkv_cnt[8], bo_cnt[16];
  uint32_t pro[4];
  uint32_t wmax[96];
  uint32_t pad1[4];
  uint32_t head, pad0[31];
  uint32_t zeroed, pad[31];
  uint32_t gst[16 * NH];
  uint32_t wcnt[16 * 8];
  float2 rstat[S_LEN];
};
__device__ __align__(1024) Sync g_sync[2];
#define BLN 0
#define WREL 0
#define WLN 2
static_assert(!(BLN && WLN), "layer norm");
#define NPRO ((WLN >> layer & 1) ? 128 : 96)
__device__ __align__(1024) float2 g_bst[BLN ? 2048 * 8 : 2];
__device__ uint32_t g_kw;
__device__ __align__(1024) float g_bkv[NH * BF * 24];

#define GT(k, e)
#define WS(e_, v_)
#undef TLOG
#undef TM
#undef PT
#undef XT
#define XT(i, e)
#define TLOG(id, ta)
#define TM(i)
#define PT(k, e)
#define DEVI __device__ __forceinline__
constexpr int SPIN_LIMIT = 20000;
DEVI uint32_t smem_u32(const void* p) { return (uint32_t)__cvta_generic_to_shared(p); }
DEVI uint32_t clk32() { uint64_t c; asm volatile("mov.u64 %0, %%clock64;" : "=l"(c)); return (uint32_t)c; }
DEVI uint32_t mapa(uint32_t a, uint32_t r) { uint32_t o; asm("mapa.shared::cluster.u32 %0, %1, %2;" : "=r"(o) : "r"(a), "r"(r)); return o; }
DEVI void mbar_init(uint32_t bar, uint32_t cnt) { asm volatile("mbarrier.init.shared::cta.b64 [%0], %1;" :: "r"(bar), "r"(cnt) : "memory"); }
DEVI void mbar_expect(uint32_t bar, uint32_t bytes) { asm volatile("mbarrier.arrive.expect_tx.shared::cta.b64 _, [%0], %1;" :: "r"(bar), "r"(bytes) : "memory"); }
DEVI void mbar_arrive(uint32_t bar) { asm volatile("mbarrier.arrive.shared::cta.b64 _, [%0];" :: "r"(bar) : "memory"); }
DEVI void mbar_arrive_cluster(uint32_t rbar) { asm volatile("mbarrier.arrive.relaxed.cluster.shared::cluster.b64 _, [%0];" :: "r"(rbar) : "memory"); }
DEVI bool mbar_try(uint32_t bar, uint32_t par) {
  uint32_t ok;
  asm volatile("{.reg .pred p; mbarrier.try_wait.parity.shared::cta.b64 p, [%1], %2; selp.u32 %0, 1, 0, p;}" : "=r"(ok) : "r"(bar), "r"(par) : "memory");
  return ok;
}
DEVI void mbar_wait(uint32_t bar, uint32_t par) {
  int n = 0;
  while (!mbar_try(bar, par) && ++n < SPIN_LIMIT) {}
}
DEVI void bar_sync(int id, int n) { asm volatile("bar.sync %0, %1;" :: "r"(id), "r"(n) : "memory"); }
DEVI void bar_arrive(int id, int n) { asm volatile("bar.arrive %0, %1;" :: "r"(id), "r"(n) : "memory"); }
DEVI void fence_async() { asm volatile("fence.proxy.async.shared::cta;" ::: "memory"); }
#define RFEN 2
#define CEND 1
#define XFEN 1
#define WFEN 2
template <int M> DEVI void publish_bulk(uint32_t* flag) {
  if (M == 1) asm volatile("fence.proxy.async;" ::: "memory");
  if (M == 2) asm volatile("red.release.gpu.global.add.u32 [%0], 1;" :: "l"(flag) : "memory");
  else asm volatile("red.relaxed.gpu.global.add.u32 [%0], 1;" :: "l"(flag) : "memory");
}
DEVI void fence_flag_to_bulk() {
  if (RFEN == 0) asm volatile("fence.proxy.async;" ::: "memory");
  if (RFEN == 1) asm volatile("fence.proxy.async.global;" ::: "memory");
}
DEVI void cluster_sync_full() { asm volatile("barrier.cluster.arrive.release.aligned; barrier.cluster.wait.acquire.aligned;" ::: "memory"); }
DEVI void tma2d(uint32_t dst, const CUtensorMap* m, int c0, int c1, uint32_t bar) {
  asm volatile("cp.async.bulk.tensor.2d.shared::cluster.global.mbarrier::complete_tx::bytes [%0], [%1, {%3, %4}], [%2];"
               :: "r"(dst), "l"(m), "r"(bar), "r"(c0), "r"(c1) : "memory");
}
DEVI void tma3d(uint32_t dst, const CUtensorMap* m, int c0, int c1, int c2, uint32_t bar) {
  asm volatile("cp.async.bulk.tensor.3d.shared::cluster.global.mbarrier::complete_tx::bytes [%0], [%1, {%3, %4, %5}], [%2];"
               :: "r"(dst), "l"(m), "r"(bar), "r"(c0), "r"(c1), "r"(c2) : "memory");
}
DEVI void tma3d_mc(uint32_t dst, const CUtensorMap* m, int c0, int c1, int c2, uint32_t bar, uint16_t mask) {
  asm volatile("cp.async.bulk.tensor.3d.shared::cluster.global.mbarrier::complete_tx::bytes.multicast::cluster [%0], [%1, {%3, %4, %5}], [%2], %6;"
               :: "r"(dst), "l"(m), "r"(bar), "r"(c0), "r"(c1), "r"(c2), "h"(mask) : "memory");
}
DEVI void tma3d_prefetch(const CUtensorMap* m, int c0, int c1, int c2) {
  asm volatile("cp.async.bulk.prefetch.tensor.3d.L2.global [%0, {%1, %2, %3}];" :: "l"(m), "r"(c0), "r"(c1), "r"(c2) : "memory");
}
DEVI void tma2d_prefetch(const CUtensorMap* m, int c0, int c1) {
  asm volatile("cp.async.bulk.prefetch.tensor.2d.L2.global [%0, {%1, %2}];" :: "l"(m), "r"(c0), "r"(c1) : "memory");
}
#define EVF 7
DEVI uint64_t stream_policy() { uint64_t p; asm("createpolicy.fractional.L2::evict_first.b64 %0, 1.0;" : "=l"(p)); return p; }
DEVI void bulk_store(void* g, uint32_t s, uint32_t bytes) {
  if (EVF & 1) asm volatile("cp.async.bulk.global.shared::cta.bulk_group.L2::cache_hint [%0], [%1], %2, %3;" :: "l"(g), "r"(s), "r"(bytes), "l"(stream_policy()) : "memory");
  else asm volatile("cp.async.bulk.global.shared::cta.bulk_group [%0], [%1], %2;" :: "l"(g), "r"(s), "r"(bytes) : "memory");
}
DEVI void ldsm4(uint32_t (&r)[4], uint32_t a) {
  asm volatile("ldmatrix.sync.aligned.m8n8.x4.shared.b16 {%0,%1,%2,%3}, [%4];" : "=r"(r[0]), "=r"(r[1]), "=r"(r[2]), "=r"(r[3]) : "r"(a) : "memory");
}
DEVI void ldsm4t(uint32_t (&r)[4], uint32_t a) {
  asm volatile("ldmatrix.sync.aligned.m8n8.x4.trans.shared.b16 {%0,%1,%2,%3}, [%4];" : "=r"(r[0]), "=r"(r[1]), "=r"(r[2]), "=r"(r[3]) : "r"(a) : "memory");
}
DEVI void ldsm4t_p(uint32_t* r, uint32_t a) {
  asm volatile("ldmatrix.sync.aligned.m8n8.x4.trans.shared.b16 {%0,%1,%2,%3}, [%4];" : "=r"(r[0]), "=r"(r[1]), "=r"(r[2]), "=r"(r[3]) : "r"(a) : "memory");
}
DEVI void ldsm2(uint32_t (&r)[2], uint32_t a) {
  asm volatile("ldmatrix.sync.aligned.m8n8.x2.shared.b16 {%0,%1}, [%2];" : "=r"(r[0]), "=r"(r[1]) : "r"(a) : "memory");
}
DEVI void stsm4(uint32_t a, uint32_t r0, uint32_t r1, uint32_t r2, uint32_t r3) {
  asm volatile("stmatrix.sync.aligned.m8n8.x4.shared.b16 [%0], {%1,%2,%3,%4};" :: "r"(a), "r"(r0), "r"(r1), "r"(r2), "r"(r3) : "memory");
}
DEVI void mma16816(float (&d)[4], const uint32_t* a, uint32_t b0, uint32_t b1) {
  asm volatile("mma.sync.aligned.m16n8k16.row.col.f32.bf16.bf16.f32 {%0,%1,%2,%3}, {%4,%5,%6,%7}, {%8,%9}, {%0,%1,%2,%3};"
               : "+f"(d[0]), "+f"(d[1]), "+f"(d[2]), "+f"(d[3]) : "r"(a[0]), "r"(a[1]), "r"(a[2]), "r"(a[3]), "r"(b0), "r"(b1));
}
DEVI void mma1688(float (&d)[4], uint32_t a0, uint32_t a1, uint32_t b0) {
  asm volatile("mma.sync.aligned.m16n8k8.row.col.f32.bf16.bf16.f32 {%0,%1,%2,%3}, {%4,%5}, {%6}, {%0,%1,%2,%3};"
               : "+f"(d[0]), "+f"(d[1]), "+f"(d[2]), "+f"(d[3]) : "r"(a0), "r"(a1), "r"(b0));
}
DEVI uint32_t pack_bf16(float lo, float hi) { uint32_t r; asm("cvt.rn.bf16x2.f32 %0, %1, %2;" : "=r"(r) : "f"(hi), "f"(lo)); return r; }
DEVI uint32_t pack_f16(float lo, float hi) { uint32_t r; asm("cvt.rn.f16x2.f32 %0, %1, %2;" : "=r"(r) : "f"(hi), "f"(lo)); return r; }
DEVI uint32_t f16x2_to_bf16x2(uint32_t h) { float2 f = __half22float2(*reinterpret_cast<__half2*>(&h)); return pack_bf16(f.x, f.y); }
DEVI void sts32(uint32_t a, uint32_t v) { asm volatile("st.shared.u32 [%0], %1;" :: "r"(a), "r"(v) : "memory"); }
DEVI void sts64(uint32_t a, uint32_t v0, uint32_t v1) { asm volatile("st.shared.v2.u32 [%0], {%1,%2};" :: "r"(a), "r"(v0), "r"(v1) : "memory"); }
DEVI void sts128(uint32_t a, uint32_t v0, uint32_t v1, uint32_t v2, uint32_t v3) { asm volatile("st.shared.v4.u32 [%0], {%1,%2,%3,%4};" :: "r"(a), "r"(v0), "r"(v1), "r"(v2), "r"(v3) : "memory"); }
DEVI uint32_t lds32(uint32_t a) { uint32_t v; asm volatile("ld.shared.u32 %0, [%1];" : "=r"(v) : "r"(a) : "memory"); return v; }
DEVI float2 lds64f(uint32_t a) { float2 v; asm volatile("ld.shared.v2.f32 {%0,%1}, [%2];" : "=f"(v.x), "=f"(v.y) : "r"(a) : "memory"); return v; }
DEVI void lds128(uint32_t (&r)[4], uint32_t a) { asm volatile("ld.shared.v4.u32 {%0,%1,%2,%3}, [%4];" : "=r"(r[0]), "=r"(r[1]), "=r"(r[2]), "=r"(r[3]) : "r"(a) : "memory"); }
DEVI void st_async64(uint32_t a, float x, float y, uint32_t bar) {
  asm volatile("st.async.weak.shared::cluster.mbarrier::complete_tx::bytes.v2.f32 [%0], {%1,%2}, [%3];" :: "r"(a), "f"(x), "f"(y), "r"(bar) : "memory");
}
DEVI void st_async32(uint32_t a, uint32_t x, uint32_t bar) {
  asm volatile("st.async.weak.shared::cluster.mbarrier::complete_tx::bytes.b32 [%0], %1, [%2];" :: "r"(a), "r"(x), "r"(bar) : "memory");
}
DEVI void ld_relaxed128(uint32_t (&r)[4], const void* p) {
  asm volatile("ld.relaxed.gpu.global.v4.u32 {%0,%1,%2,%3}, [%4];" : "=r"(r[0]), "=r"(r[1]), "=r"(r[2]), "=r"(r[3]) : "l"(p) : "memory");
}
DEVI void red_f16x2(void* p, uint32_t v) { asm volatile("red.relaxed.gpu.global.add.noftz.f16x2 [%0], %1;" :: "l"(p), "r"(v) : "memory"); }
DEVI void red_f16x2_v4(void* p, uint32_t a, uint32_t b, uint32_t c, uint32_t d) {
  asm volatile("red.relaxed.gpu.global.add.noftz.v4.f16x2 [%0], {%1,%2,%3,%4};" :: "l"(p), "r"(a), "r"(b), "r"(c), "r"(d) : "memory");
}
DEVI void red_add2(float2* p, float a, float b) { asm volatile("red.relaxed.gpu.global.add.v2.f32 [%0], {%1,%2};" :: "l"(p), "f"(a), "f"(b) : "memory"); }
DEVI float rcp(float x) { float y; asm("rcp.approx.ftz.f32 %0, %1;" : "=f"(y) : "f"(x)); return y; }
DEVI float ex2(float x) { float y; asm("ex2.approx.ftz.f32 %0, %1;" : "=f"(y) : "f"(x)); return y; }
DEVI uint64_t mkdesc(uint32_t addr, uint32_t lbo, uint32_t sbo, uint32_t swz) {
  return (uint64_t)((addr & 0x3FFFF) >> 4) | ((uint64_t)(lbo >> 4) << 16) | ((uint64_t)(sbo >> 4) << 32) | ((uint64_t)swz << 62);
}
DEVI void wg_fence() { asm volatile("wgmma.fence.sync.aligned;" ::: "memory"); }
DEVI void wg_commit() { asm volatile("wgmma.commit_group.sync.aligned;" ::: "memory"); }
template <int N> DEVI void wg_wait() { asm volatile("wgmma.wait_group.sync.aligned %0;" :: "n"(N) : "memory"); }
#define ACC4(d, o) "+f"(d[o]), "+f"(d[o + 1]), "+f"(d[o + 2]), "+f"(d[o + 3])
constexpr uint32_t DHI_SW128 = (1024u >> 4) | (1u << 30);
DEVI uint32_t desc_lo(uint32_t addr, uint32_t lbo) { return ((addr & 0x3FFFF) >> 4) | ((lbo >> 4) << 16); }
template <int OB_, int ACC> DEVI void wgmma_rs_n32(float (&d)[16], const uint32_t* a, uint32_t b) {
  asm volatile("{.reg .b64 db; .reg .b32 tb; add.u32 tb, %20, %21; mov.b64 db, {tb, %22};\n"
               "wgmma.mma_async.sync.aligned.m64n32k16.f32.bf16.bf16 {%0,%1,%2,%3,%4,%5,%6,%7,%8,%9,%10,%11,%12,%13,%14,%15}, {%16,%17,%18,%19}, db, %23, 1, 1, 0;}"
               : ACC4(d, 0), ACC4(d, 4), ACC4(d, 8), ACC4(d, 12) : "r"(a[0]), "r"(a[1]), "r"(a[2]), "r"(a[3]), "r"(b), "n"(OB_ >> 4), "n"(DHI_SW128), "n"(ACC));
}
template <int K0, int K1, int ACC = 1> struct Unroll {
  static DEVI void kbulk(float (&d)[16], const uint32_t* W, uint32_t x) { wgmma_rs_n32<(K0 >> 2) * 4096 + (K0 & 3) * 32, ACC>(d, W + K0 * 4, x); Unroll<K0 + 1, K1>::kbulk(d, W, x); }
};
template <int K1> struct Unroll<K1, K1, 1> {
  static DEVI void kbulk(float (&)[16], const uint32_t*, uint32_t) {}
};

DEVI void wgmma_n192_nt(float (&d)[96], uint64_t a, uint64_t b, int acc) {
  asm volatile("{.reg .pred p; setp.ne.b32 p, %98, 0;\n"
               "wgmma.mma_async.sync.aligned.m64n192k16.f32.bf16.bf16 {%0,%1,%2,%3,%4,%5,%6,%7,%8,%9,%10,%11,%12,%13,%14,%15,%16,%17,%18,%19,%20,%21,%22,%23,%24,%25,%26,%27,%28,%29,%30,%31,%32,%33,%34,%35,%36,%37,%38,%39,%40,%41,%42,%43,%44,%45,%46,%47,%48,%49,%50,%51,%52,%53,%54,%55,%56,%57,%58,%59,%60,%61,%62,%63,%64,%65,%66,%67,%68,%69,%70,%71,%72,%73,%74,%75,%76,%77,%78,%79,%80,%81,%82,%83,%84,%85,%86,%87,%88,%89,%90,%91,%92,%93,%94,%95}, %96, %97, p, 1, 1, 0, 1;}"
               : ACC4(d, 0), ACC4(d, 4), ACC4(d, 8), ACC4(d, 12), ACC4(d, 16), ACC4(d, 20), ACC4(d, 24), ACC4(d, 28), ACC4(d, 32), ACC4(d, 36), ACC4(d, 40), ACC4(d, 44), ACC4(d, 48), ACC4(d, 52), ACC4(d, 56), ACC4(d, 60), ACC4(d, 64), ACC4(d, 68), ACC4(d, 72), ACC4(d, 76), ACC4(d, 80), ACC4(d, 84), ACC4(d, 88), ACC4(d, 92) : "l"(a), "l"(b), "r"(acc));
}
DEVI void wgmma_n160_nt(float (&d)[80], uint64_t a, uint64_t b, int acc) {
  asm volatile("{.reg .pred p; setp.ne.b32 p, %82, 0;\n"
               "wgmma.mma_async.sync.aligned.m64n160k16.f32.bf16.bf16 {%0,%1,%2,%3,%4,%5,%6,%7,%8,%9,%10,%11,%12,%13,%14,%15,%16,%17,%18,%19,%20,%21,%22,%23,%24,%25,%26,%27,%28,%29,%30,%31,%32,%33,%34,%35,%36,%37,%38,%39,%40,%41,%42,%43,%44,%45,%46,%47,%48,%49,%50,%51,%52,%53,%54,%55,%56,%57,%58,%59,%60,%61,%62,%63,%64,%65,%66,%67,%68,%69,%70,%71,%72,%73,%74,%75,%76,%77,%78,%79}, %80, %81, p, 1, 1, 0, 1;}"
               : ACC4(d, 0), ACC4(d, 4), ACC4(d, 8), ACC4(d, 12), ACC4(d, 16), ACC4(d, 20), ACC4(d, 24), ACC4(d, 28), ACC4(d, 32), ACC4(d, 36), ACC4(d, 40), ACC4(d, 44), ACC4(d, 48), ACC4(d, 52), ACC4(d, 56), ACC4(d, 60), ACC4(d, 64), ACC4(d, 68), ACC4(d, 72), ACC4(d, 76) : "l"(a), "l"(b), "r"(acc));
}
DEVI void wgmma_n240_nn(float (&d)[120], uint64_t a, uint64_t b, int acc) {
  asm volatile("{.reg .pred p; setp.ne.b32 p, %122, 0;\n"
               "wgmma.mma_async.sync.aligned.m64n240k16.f32.bf16.bf16 {%0,%1,%2,%3,%4,%5,%6,%7,%8,%9,%10,%11,%12,%13,%14,%15,%16,%17,%18,%19,%20,%21,%22,%23,%24,%25,%26,%27,%28,%29,%30,%31,%32,%33,%34,%35,%36,%37,%38,%39,%40,%41,%42,%43,%44,%45,%46,%47,%48,%49,%50,%51,%52,%53,%54,%55,%56,%57,%58,%59,%60,%61,%62,%63,%64,%65,%66,%67,%68,%69,%70,%71,%72,%73,%74,%75,%76,%77,%78,%79,%80,%81,%82,%83,%84,%85,%86,%87,%88,%89,%90,%91,%92,%93,%94,%95,%96,%97,%98,%99,%100,%101,%102,%103,%104,%105,%106,%107,%108,%109,%110,%111,%112,%113,%114,%115,%116,%117,%118,%119}, %120, %121, p, 1, 1, 0, 0;}"
               : ACC4(d, 0), ACC4(d, 4), ACC4(d, 8), ACC4(d, 12), ACC4(d, 16), ACC4(d, 20), ACC4(d, 24), ACC4(d, 28), ACC4(d, 32), ACC4(d, 36), ACC4(d, 40), ACC4(d, 44), ACC4(d, 48), ACC4(d, 52), ACC4(d, 56), ACC4(d, 60), ACC4(d, 64), ACC4(d, 68), ACC4(d, 72), ACC4(d, 76), ACC4(d, 80), ACC4(d, 84), ACC4(d, 88), ACC4(d, 92), ACC4(d, 96), ACC4(d, 100), ACC4(d, 104), ACC4(d, 108), ACC4(d, 112), ACC4(d, 116) : "l"(a), "l"(b), "r"(acc));
}
DEVI void wgmma_n80_nt(float (&d)[40], uint64_t a, uint64_t b, int acc) {
  asm volatile("{.reg .pred p; setp.ne.b32 p, %42, 0;\n"
               "wgmma.mma_async.sync.aligned.m64n80k16.f32.bf16.bf16 {%0,%1,%2,%3,%4,%5,%6,%7,%8,%9,%10,%11,%12,%13,%14,%15,%16,%17,%18,%19,%20,%21,%22,%23,%24,%25,%26,%27,%28,%29,%30,%31,%32,%33,%34,%35,%36,%37,%38,%39}, %40, %41, p, 1, 1, 0, 1;}"
               : ACC4(d, 0), ACC4(d, 4), ACC4(d, 8), ACC4(d, 12), ACC4(d, 16), ACC4(d, 20), ACC4(d, 24), ACC4(d, 28), ACC4(d, 32), ACC4(d, 36) : "l"(a), "l"(b), "r"(acc));
}

#define ACQ 0
DEVI uint32_t ld_acquire(const uint32_t* p) {
  uint32_t v;
  if (ACQ) asm volatile("ld.acquire.gpu.global.u32 %0, [%1];" : "=r"(v) : "l"(p) : "memory");
  else asm volatile("ld.relaxed.gpu.global.u32 %0, [%1];" : "=r"(v) : "l"(p) : "memory");
  return v;
}
DEVI uint4 ldcg_if(const void* p, bool on) {
  uint4 v;
  asm volatile("{.reg .pred p; setp.ne.u32 p, %5, 0; mov.u32 %0, 0; mov.u32 %1, 0; mov.u32 %2, 0; mov.u32 %3, 0;\n"
               "@p ld.global.cg.v4.u32 {%0,%1,%2,%3}, [%4];}" : "=&r"(v.x), "=&r"(v.y), "=&r"(v.z), "=&r"(v.w) : "l"(p), "r"((uint32_t)on) : "memory");
  return v;
}
#define LEF 31
template <bool EF> DEVI uint4 ldcg_if_h(const void* p, bool on) {
  if (!EF) return ldcg_if(p, on);
  uint4 v;
  asm volatile("{.reg .pred p; setp.ne.u32 p, %5, 0; mov.u32 %0, 0; mov.u32 %1, 0; mov.u32 %2, 0; mov.u32 %3, 0;\n"
               "@p ld.global.cg.L2::cache_hint.v4.u32 {%0,%1,%2,%3}, [%4], %6;}" : "=&r"(v.x), "=&r"(v.y), "=&r"(v.z), "=&r"(v.w) : "l"(p), "r"((uint32_t)on), "l"(stream_policy()) : "memory");
  return v;
}
#define PEF 3
template <bool EF> DEVI void st128_h(void* p, uint4 v) {
  if (EF) asm volatile("st.global.L2::cache_hint.v4.u32 [%0], {%1,%2,%3,%4}, %5;" :: "l"(p), "r"(v.x), "r"(v.y), "r"(v.z), "r"(v.w), "l"(stream_policy()) : "memory");
  else *(uint4*)p = v;
}
template <bool EF> DEVI uint2 ld64_h(const void* p) {
  if (!EF) return __ldcg((const uint2*)p);
  uint2 v;
  asm volatile("ld.global.cg.L2::cache_hint.v2.u32 {%0,%1}, [%2], %3;" : "=r"(v.x), "=r"(v.y) : "l"(p), "l"(stream_policy()) : "memory");
  return v;
}
DEVI void red_release(uint32_t* p) { asm volatile("red.release.gpu.global.add.u32 [%0], 1;" :: "l"(p) : "memory"); }
#define TIGHT 1
DEVI void wait_count_t(const uint32_t* p, uint32_t n, bool tight) {
  for (int i = 0; i < 4000000 && ld_acquire(p) < n; i++) if (!(TIGHT && tight)) __nanosleep(100);
}
DEVI void wait_count(const uint32_t* p, uint32_t n) {
  for (int i = 0; i < 4000000 && ld_acquire(p) < n; i++) __nanosleep(100);
}
DEVI void spin_count(const uint32_t* p, uint32_t n) { for (int i = 0; i < 4000000 && ld_acquire(p) < n; i++) {} }
DEVI void mbar_wait_long(uint32_t bar, uint32_t par) { for (int n = 0; n < 4000000 && !mbar_try(bar, par); n++) {} }
DEVI void ln_row(float (&v)[20], bf16* y, int lane) {
  float s = 0.f;
#pragma unroll
  for (int i = 0; i < 20; i++) s += v[i];
#pragma unroll
  for (int o = 16; o; o >>= 1) s += __shfl_xor_sync(0xffffffffu, s, o);
  const float m = s * (1.0f / DM); float q = 0.f;
#pragma unroll
  for (int i = 0; i < 20; i++) { v[i] -= m; q += v[i] * v[i]; }
#pragma unroll
  for (int o = 16; o; o >>= 1) q += __shfl_xor_sync(0xffffffffu, q, o);
  const float r = rsqrtf(q * (1.0f / DM) + 1e-5f);
#pragma unroll
  for (int i = 0; i < 5; i++) *(uint2*)(y + i * 128 + lane * 4) = make_uint2(pack_bf16(v[4 * i] * r, v[4 * i + 1] * r), pack_bf16(v[4 * i + 2] * r, v[4 * i + 3] * r));
}

DEVI uint32_t mag4(uint32_t m, const uint32_t* f) {
  return __vmaxu2(__vmaxu2(m, __vmaxu2(f[0] & 0x7FFF7FFFu, f[1] & 0x7FFF7FFFu)), __vmaxu2(f[2] & 0x7FFF7FFFu, f[3] & 0x7FFF7FFFu));
}
DEVI void publish_max(uint32_t a, uint32_t m) {
  m = __reduce_max_sync(0xffffffffu, max(m & 0xFFFFu, m >> 16));
  if ((threadIdx.x & 31) == 0) asm volatile("red.shared.max.u32 [%0], %1;" :: "r"(a), "r"(m) : "memory");
}

namespace ch {
constexpr uint32_t WQ = 0;
constexpr uint32_t WOF2 = 81920;
constexpr uint32_t WOF = 106496;
constexpr uint32_t XB = 143360;
constexpr uint32_t MEMB = 184320;
constexpr uint32_t KT = 194560;
constexpr uint32_t VT = 199680;
constexpr uint32_t PK = 204800;
constexpr uint32_t QS = 212992;
constexpr uint32_t KP = 215040;
constexpr uint32_t EX = 217088;
constexpr uint32_t OB = 221184;
constexpr uint32_t SX = 224256;
constexpr uint32_t WOF3 = 226176;
constexpr uint32_t WOSTAGE = 143360;
constexpr uint32_t PB = OB;
constexpr uint32_t WMX = OB + 128;
constexpr uint32_t MISC = 228224;
constexpr uint32_t BAR_XF = MISC + 56;
constexpr uint32_t BAR_WK = MISC + 48, BAR_W1 = MISC, BAR_W2 = MISC + 8, BAR_X0 = MISC + 16, BAR_X1 = MISC + 24, BAR_S = MISC + 32, BAR_O = MISC + 40;
constexpr uint32_t MX = MISC + 64;
constexpr uint32_t INV = MX + 32;
#define PD_ 550
#define XD_ 150
#define X1D_ 0
#define PFW 0
constexpr uint32_t SMEM = 228352;
}

#define TS(e)
#define TSV(e, v)
#define TSX(x)
#define TSD(e, x)

#define SS(e)
#define E1(id, x)
#define PIN(x) asm volatile("" : "+r"(x))
#define PINF(x) asm volatile("" : "+f"(x))
#define PINL(x) asm volatile("" : "+l"(x))

DEVI uint32_t ar_line_off(uint32_t l) { return (l >> 2) * 1024 + (l & 3) * 128; }
DEVI uint32_t ar_tile_off(int T) { return (T >> 1) * 1024 + (T & 1) * 256; }
DEVI uint32_t ar_extra_off(uint32_t T) { return ar_line_off(80 + (T >> 2)) + (T & 3) * 32; }

DEVI void wo_red(const char* p, uint32_t w0, uint32_t w1, bool last) {
  red_f16x2((void*)p, last ? 0x3C00u : w0);
  red_f16x2((void*)(p + 128), last ? 0x3C00u : w1);
}
DEVI void wo_red_extra_p(const char* px, uint32_t w0, uint32_t w1, uint32_t ln) {
  asm volatile("{.reg .pred p; setp.eq.u32 p, %5, 31; @p red.relaxed.gpu.global.add.noftz.v4.f16x2 [%0], {%1,%2,%3,%4};}"
               :: "l"(px), "r"(w0), "r"(w1), "r"(0u), "r"(0x3C00u), "r"(ln) : "memory");
}

#define ARH 2
DEVI void sched_fence(uint32_t zero) {
#pragma unroll 1
  for (uint32_t i = 0; i < zero; i++) asm volatile("nanosleep.u32 0;" ::: "memory");
}
template <int N> DEVI void code_pad(uint32_t zero) {
  if (N > 0) {
#pragma unroll 1
    for (uint32_t i = 0; i < zero; i++) {
#pragma unroll
      for (int k = 0; k < N; k++) asm volatile("nanosleep.u32 0;" ::: "memory");
    }
  }
}
#define PAD1 0
#define PAD0 0
DEVI void loaded(uint32_t x) { asm volatile("{.reg .pred p; setp.eq.u32 p, %0, 0xdeadbeef; @p nanosleep.u32 0;}" :: "r"(x) : "memory"); }
DEVI uint32_t opq(uint32_t x) { asm volatile("" : "+r"(x)); return x; }

DEVI uint32_t ar_read(const char* arb, uint32_t sb, int w, uint32_t lane_, uint32_t zero, uint32_t tref, int dly, int s) {
  const int wg = 2; (void)wg; (void)s;
  const uint32_t lane = opq(lane_);
  const int b0 = (w >> 1) * 10 + (w & 1);
  const uint32_t e = min(lane, 9u), T = 2 * b0 + 4 * (e >> 1) + (e & 1);
  const char* p0 = arb + b0 * 1024 + lane * 16;
  const char* p2 = arb + ar_extra_off(T);
  uint32_t dst = sb + ch::MEMB + b0 * 512 + lane * 16, dst2 = sb + ch::MEMB + (16 * T + 7) * 16 + 12;
  uint32_t v[6][4];
  PINL(p0); PINL(p2); PIN(dst); PIN(dst2);
  while ((int)(clk32() - tref) < dly) {}
#pragma unroll
  for (int i = 0; i < 5; i++) ld_relaxed128(v[i], p0 + i * 2048);
  ld_relaxed128(v[5], p2);
  sched_fence(zero);
  TS(4);
  uint32_t bad = 0;
#pragma unroll
  for (int i = 0; i < 5; i++) bad |= v[i][3] ^ 0x5000u;
  if ((lane & 7) != 7) bad = 0;
  bad |= v[5][3] ^ 0x5000u;
  TSD(5, bad);
  E1(6, bad);
  int n = 0;
  if (__any_sync(0xffffffffu, bad != 0)) {
    if (lane == 0) sts32(sb + ch::MX + 20, 1u);
    while (true) {
      bad = 0;
#pragma unroll
      for (int i = 0; i < 6; i++) if ((i == 5 || (lane & 7) == 7) && v[i][3] != 0x5000u) bad |= 1u << i;
      bad = __reduce_or_sync(0xffffffffu, bad);
      if (!bad || ++n > SPIN_LIMIT) break;
#pragma unroll
      for (int i = 0; i < 6; i++) if (bad >> i & 1) ld_relaxed128(v[i], i < 5 ? p0 + i * 2048 : p2);
    }
  }
  TSV(6, n);
  const uint32_t x0 = f16x2_to_bf16x2(v[5][0]), x1 = f16x2_to_bf16x2(v[5][1]);
#pragma unroll
  for (int i = 0; i < 5; i++) {
    sts128(dst + i * 1024, f16x2_to_bf16x2(v[i][0]), f16x2_to_bf16x2(v[i][1]), f16x2_to_bf16x2(v[i][2]), f16x2_to_bf16x2(v[i][3]));
    if (i == ARH - 1 || i == 4) {
      __syncwarp();
      sts32(dst2, x0); sts32(dst2 + 128, x1);
      if (i < 4) { TS(7); bar_arrive(1, 384); sched_fence(zero); } else { TSX(TS(1)); bar_sync(3, 384); }
    }
  }
  const uint32_t keep = (lane & 7) == 7 ? 0u : 0x7FFF7FFFu;
  uint32_t m = __vmaxu2(v[5][0] & 0x7FFF7FFFu, v[5][1] & 0x7FFF7FFFu);
#pragma unroll
  for (int i = 0; i < 5; i++) m = __vmaxu2(__vmaxu2(m, __vmaxu2(v[i][0] & 0x7FFF7FFFu, v[i][1] & 0x7FFF7FFFu)), __vmaxu2(v[i][2] & 0x7FFF7FFFu, v[i][3] & keep));
  return m;
}

#define VL 0
struct Peers {
  uint32_t a[2];
  DEVI Peers(uint32_t sb, int j) {
#pragma unroll
    for (int r = 0; r < 2; r++) { int peer = j + 1 + r; if (peer >= 3) peer -= 3; a[r] = mapa(sb, peer); }
  }
};
DEVI uint32_t lane_id() { const uint32_t l = threadIdx.x & 31; return __shfl_sync(0xffffffffu, l, l); }
DEVI void score_tile(uint32_t sb, uint32_t qa, const uint32_t (&b0)[4], const uint32_t (&b1)[4], const Peers& pe, uint32_t off, uint32_t lane) {
  float c0[4] = {0.f, 0.f, 0.f, 0.f}, c1[4] = {0.f, 0.f, 0.f, 0.f};
  uint32_t a0[4], a1[4], a2[4], a3[4];
  ldsm4t(a0, qa); ldsm4t(a1, qa + 256); ldsm4t(a2, qa + 512); ldsm4t(a3, qa + 768);
  mma16816(c0, a0, b0[0], b0[1]); mma16816(c1, a1, b0[2], b0[3]);
  mma16816(c0, a2, b1[0], b1[1]); mma16816(c1, a3, b1[2], b1[3]);
  if (!VL) asm volatile("bar.arrive 5, 288;" : "+f"(c0[0]), "+f"(c1[0]) :: "memory");
  const float cs = 0.25f * 0.07216878364870322f * 1.4426950408889634f;
  const float x = ((c0[0] + c0[2]) + (c1[0] + c1[2])) * cs, y = ((c0[1] + c0[3]) + (c1[1] + c1[3])) * cs;
  uint32_t u; asm("cvt.rn.satfinite.f16x2.f32 %0, %1, %2;" : "=r"(u) : "f"(y), "f"(x));
  st_async32(pe.a[0] + off, u, pe.a[0] + ch::BAR_S);
  st_async32(pe.a[1] + off, u, pe.a[1] + ch::BAR_S);
  sts32(sb + off, u);
  __syncwarp();
  if (lane == 0) mbar_arrive(sb + ch::BAR_S);
}
DEVI uint32_t hadd2(uint32_t a, uint32_t b) { uint32_t r; asm("add.rn.f16x2 %0, %1, %2;" : "=r"(r) : "r"(a), "r"(b)); return r; }
DEVI uint32_t hmax2(uint32_t a, uint32_t b) { uint32_t r; asm("max.f16x2 %0, %1, %2;" : "=r"(r) : "r"(a), "r"(b)); return r; }
DEVI uint32_t add_bf16x2(uint32_t a, uint32_t b) { uint32_t r; asm("add.rn.bf16x2 %0, %1, %2;" : "=r"(r) : "r"(a), "r"(b)); return r; }

DEVI uint32_t slab_off(uint32_t base, int w, uint32_t lane) { return base + (16 * w + (lane >> 2)) * 80 + (lane & 3) * 4; }
DEVI void release_x(uint32_t sb, int half, int w, uint32_t lane) {
  if (lane == 0) {
    if (w == 0) mbar_expect(sb + ch::BAR_X0 + half * 8, 20480);
    mbar_arrive_cluster(mapa(sb + ch::BAR_XF, half));
  }
}
#define TSYNC 1
#define KORD 0
#define X0E 0
#define X0D_ 0
#define X1E 1
#define KS2 0
#define SKIPT 0
DEVI void store_slabs(uint32_t sb, int s, int h, int j) {
  bf16* kvp = g_kv + ((size_t)(s * NH + h) * 2 * DH + 64 * j) * NKEY;
  fence_async();
  bulk_store(kvp, sb + ch::KT, SLAB);
  bulk_store(kvp + DH * NKEY, sb + ch::VT, SLAB);
  asm volatile("cp.async.bulk.commit_group;" ::: "memory");
}

template <int MODE>
DEVI void tokens_partial(uint32_t sb, uint32_t dst, const uint32_t* W, uint32_t xdesc, int w, uint32_t lane) {
  float d[16];
#pragma unroll
  for (int i = 0; i < 16; i++) d[i] = 0.f;
  wg_fence();
  if (!((SKIPT >> (MODE == 3 ? 1 : MODE)) & 1)) Unroll<20, 40, 0>::kbulk(d, W - 80, xdesc);
  wg_commit();
  if (MODE == 1) bar_sync(12, 384);
  if (!KS2 && MODE == 2) bar_sync(11, 256);
  wg_wait<0>();
  if (!KS2 && (MODE == 1 || MODE == 3)) release_x(sb, 1, w, lane);
  if (MODE == 1) bar_sync(13, 384);
  if (KS2 && MODE == 2) release_x(sb, 1, w, lane);
  dst += sb + w * 512 + opq(lane) * 16;
#pragma unroll
  for (int i = 0; i < 4; i++)
    sts128(dst + i * 2048, __float_as_uint(d[4 * i]), __float_as_uint(d[4 * i + 1]), __float_as_uint(d[4 * i + 2]), __float_as_uint(d[4 * i + 3]));
  if (KS2 && MODE == 2) bar_arrive(11, 256);
}
#define LSH 0
#define KPK 16
template <bool LOOP>
DEVI void tokens_finish(uint32_t sb, const uint32_t* W, uint32_t xdesc, int w, uint32_t lane, int s = 0, const CUtensorMap* mx = nullptr) {
  const uint32_t ln = opq(lane), t16 = sb + w * 512 + ln * 16, slab = sb + slab_off(16, w, ln);
  float d[16]; uint32_t e[4][4];
#pragma unroll
  for (int i = 0; i < 16; i++) d[i] = 0.f;
  wg_fence();
  if (!(LOOP && (SKIPT & 8))) Unroll<0, 20, 0>::kbulk(d, W + 80, xdesc);
  wg_commit();
  if (!KS2 && !KORD && LOOP) bar_arrive(6, 256);
  if (LOOP && LSH == 2 && s < 0) bar_sync(8, 256);
  if (!LOOP) {
    bar_sync(8, 256);
    if (w == 3 && lane == 0) { mbar_expect(sb + ch::BAR_X1, 20480); tma3d(sb + ch::XB + 20480, mx, 0, SEG, 5, sb + ch::BAR_X1); }
    __syncwarp();
  }
#pragma unroll
  for (int i = 0; i < 4; i++) lds128(e[i], t16 + ch::QS + i * 2048);
  wg_wait<0>();
  uint32_t u[8];
#pragma unroll
  for (int i = 0; i < 4; i++) {
    u[2 * i] = pack_bf16(d[4 * i] + __uint_as_float(e[i][0]), d[4 * i + 1] + __uint_as_float(e[i][1]));
    u[2 * i + 1] = pack_bf16(d[4 * i + 2] + __uint_as_float(e[i][2]), d[4 * i + 3] + __uint_as_float(e[i][3]));
  }
  wg_fence();
  if (!(LOOP && (SKIPT & 16))) Unroll<0, 6, 0>::kbulk(d, W, xdesc);
#pragma unroll
  for (int i = 0; i < 4; i++) { sts32(slab + ch::VT + i * 16, u[2 * i]); sts32(slab + ch::VT + i * 16 + 640, u[2 * i + 1]); }
  if (KS2) {
    if (!(LOOP && (SKIPT & 16))) Unroll<6, KPK>::kbulk(d, W, xdesc);
    if (LOOP) bar_sync(11, 256);
  }
#pragma unroll
  for (int i = 0; i < 4; i++) lds128(e[i], t16 + ch::PK + i * 2048);
  if (!KS2) {
    if (!(LOOP && (SKIPT & 16))) Unroll<6, KPK>::kbulk(d, W, xdesc);
    if (LOOP) asm volatile("bar.arrive 11, 256;" : "+r"(e[0][0]), "+r"(e[1][0]), "+r"(e[2][0]), "+r"(e[3][0]) :: "memory");
  }
  if (!(LOOP && (SKIPT & 16))) Unroll<KPK, 20>::kbulk(d, W, xdesc);
  wg_commit(); wg_wait<0>();
  release_x(sb, 0, w, lane);
  if (LOOP) E1(7, __float_as_uint(d[0]));
#pragma unroll
  for (int i = 0; i < 4; i++) {
    sts32(slab + ch::KT + i * 16, pack_bf16(d[4 * i] + __uint_as_float(e[i][0]), d[4 * i + 1] + __uint_as_float(e[i][1])));
    sts32(slab + ch::KT + i * 16 + 640, pack_bf16(d[4 * i + 2] + __uint_as_float(e[i][2]), d[4 * i + 3] + __uint_as_float(e[i][3])));
  }
}

DEVI uint32_t afrag_off(int w, uint32_t lane) { return ((lane >> 4) * 8 + (lane & 7)) * 128 + (((w * 2 + ((lane >> 3) & 1)) ^ (lane & 7)) << 4); }
#define NF 5
#define WQR 0
DEVI void ldwq(uint32_t (&f)[4], uint32_t a) { if (WQR) lds128(f, a); else ldsm4t(f, a); }
DEVI void proj_stage(uint32_t (&f)[NF][4], uint32_t qa) {
#pragma unroll
  for (int i = 0; i < NF; i++) ldwq(f[i], qa + i * 2048);
}
template <int WG>
DEVI void proj_mem(float (&q)[4], float (&k)[4], float (&v)[4], uint32_t (&f)[NF][4], const uint32_t* W, uint32_t qa, uint32_t ba, uint32_t sb, int w, int s) {
  uint32_t b[2][4];
  const int wg = WG; (void)wg; (void)sb; (void)w; (void)s;
#pragma unroll
  for (int i = 0; i < 4; i++) q[i] = k[i] = v[i] = 0.f;
  bar_sync(1, 384);
  ldsm4t(b[0], ba);
  if (WG == 0) E1(8, b[0][0]);
  if (WG == 1) { TSX(TSD(5, b[0][0])); }
#pragma unroll
  for (int k2 = 0; k2 < 10; k2++) {
    if (WG == 1 && k2 + 1 == 2 * ARH) { TSX(TSD(7, __float_as_uint(v[0]))); }
    if (k2 + 1 == 2 * ARH) bar_sync(3, 384);
    if (k2 < 9) ldsm4t(b[(k2 + 1) & 1], ba + (k2 + 1) * 512);
    if (WG == 1 && k2 + 1 == 2 * ARH) { TSX(TSD(6, b[(k2 + 1) & 1][0])); }
    if (WG == 0 && k2 + 1 == 2 * ARH) { TSX(TSD(7, __float_as_uint(v[0]))); }
    mma16816(q, f[(2 * k2) % NF], b[k2 & 1][0], b[k2 & 1][1]);
    if (2 * k2 + NF < 20) ldwq(f[(2 * k2) % NF], qa + (2 * k2 + NF) * 2048);
    mma16816(k, &W[k2 * 8], b[k2 & 1][0], b[k2 & 1][1]);
    mma16816(v, &W[80 + k2 * 8], b[k2 & 1][0], b[k2 & 1][1]);
    mma16816(q, f[(2 * k2 + 1) % NF], b[k2 & 1][2], b[k2 & 1][3]);
    if (2 * k2 + 1 + NF < 20) ldwq(f[(2 * k2 + 1) % NF], qa + (2 * k2 + 1 + NF) * 2048);
    mma16816(k, &W[k2 * 8 + 4], b[k2 & 1][2], b[k2 & 1][3]);
    mma16816(v, &W[84 + k2 * 8], b[k2 & 1][2], b[k2 & 1][3]);
  }
}

template <bool BAR>
DEVI void wo_tile_smem(uint32_t sb, uint32_t fa, uint32_t ob, int par, const char* p, const char* px, bool last, float& sc) {
  uint32_t f[6][4], b[2][4];
  float c0[4] = {0.f, 0.f, 0.f, 0.f}, c1[4] = {0.f, 0.f, 0.f, 0.f};
#pragma unroll
  for (int k = 0; k < 6; k++) lds128(f[k], fa + k * 512);
  if (BAR) bar_sync(9, 384);
  ldsm4t(b[0], ob); ldsm4t(b[1], ob + 512);
  sc = __uint_as_float(lds32(sb + ch::MX + 16));
  float2 iv = lds64f(sb + ch::INV + (opq(threadIdx.x) & 3) * 8);
  iv.x *= sc; iv.y *= sc;
  mma16816(c0, f[0], b[0][0], b[0][1]); mma16816(c1, f[1], b[0][2], b[0][3]);
  mma16816(c0, f[2], b[1][0], b[1][1]); mma16816(c1, f[3], b[1][2], b[1][3]);
#pragma unroll
  for (int k = 0; k < 4; k++) lds128(f[k], fa + (6 + k) * 512);
  mbar_wait(sb + ch::BAR_O, par);
  ldsm4t(b[0], ob + 1024); ldsm4t(b[1], ob + 1536);
  mma16816(c0, f[4], b[0][0], b[0][1]); mma16816(c1, f[5], b[0][2], b[0][3]);
  lds128(f[4], fa + 10 * 512); lds128(f[5], fa + 11 * 512);
  ldsm4t(b[0], ob + 2048);
  mma16816(c0, f[0], b[1][0], b[1][1]); mma16816(c1, f[1], b[1][2], b[1][3]);
  ldsm4t(b[1], ob + 2560);
  mma16816(c0, f[2], b[0][0], b[0][1]); mma16816(c1, f[3], b[0][2], b[0][3]);
  mma16816(c0, f[4], b[1][0], b[1][1]); mma16816(c1, f[5], b[1][2], b[1][3]);
  const uint32_t w0 = pack_f16((c0[0] + c1[0]) * iv.x, (c0[1] + c1[1]) * iv.y), w1 = pack_f16((c0[2] + c1[2]) * iv.x, (c0[3] + c1[3]) * iv.y);
  wo_red(p, w0, w1, last);
  wo_red_extra_p(px, w0, w1, last ? 31u : 0u);
}

#define LNFIRST 0
DEVI void chain_prepare(const bf16* __restrict__ x) {
  const int t = threadIdx.x, lane = t & 31, r0 = blockIdx.x * 11 + (t >> 5);
  asm volatile("griddepcontrol.wait;" ::: "memory");
  uint2 u[2][5];
#pragma unroll
  for (int i = 0; i < 10; i++) u[i / 5][i % 5] = ld64_h<(PEF & 4) != 0>(x + min(r0 + (i / 5) * 1056, S_LEN - 1) * DM + (i % 5) * 128 + lane * 4);
#pragma unroll
  for (int rr = 0; rr < 2; rr++) {
    float v[20];
#pragma unroll
    for (int i = 0; i < 5; i++) {
      v[4 * i] = __uint_as_float(u[rr][i].x << 16); v[4 * i + 1] = __uint_as_float(u[rr][i].x & 0xFFFF0000u);
      v[4 * i + 2] = __uint_as_float(u[rr][i].y << 16); v[4 * i + 3] = __uint_as_float(u[rr][i].y & 0xFFFF0000u);
    }
    if (r0 + rr * 1056 < S_LEN) ln_row(v, g_xn + (r0 + rr * 1056) * DM, lane);
  }
}
#define LNF 0
#define PWIN 3
#define PWIN1 4
#define PQP 0
#define PQN 1
#define PQL 0
#define PQB 0
#define PQM 3
#define LASTG 1
#define PSPL 1
DEVI void load_weights(uint32_t (&W)[160], uint32_t sb, int G, int w, int j, int layer) {
  using namespace ch;
  const uint32_t lane = threadIdx.x & 31;
  const uint32_t wa = sb + G * 40960 + afrag_off(w, lane);
#pragma unroll 1
  for (int i = 0; i < 5; i++) mbar_wait_long(sb + PB + i * 8, 0);
  if (threadIdx.x == 0) PT(0, 10);
#pragma unroll
  for (int kk = 0; kk < 20; kk++) ldsm4t_p(&W[80 + kk * 4], wa + 81920 + kk * 2048);
  uint32_t m = 0;
#pragma unroll
  for (int kk = 0; kk < 20; kk++) m = mag4(m, &W[80 + kk * 4]);
  publish_max(sb + WMX, m);
  bar_sync(8, 256);
  if (threadIdx.x == 0) mbar_arrive(sb + BAR_W1);
#pragma unroll 1
  for (int i = 7; i < 12; i++) mbar_wait_long(sb + PB + i * 8, 0);
  if (threadIdx.x == 0) PT(0, 9);
#pragma unroll
  for (int kk = 0; kk < 20; kk++) ldsm4t_p(&W[kk * 4], wa + kk * 2048);
  loaded(W[79]);
  bar_sync(8, 256);
  if (threadIdx.x == 0) mbar_arrive(sb + BAR_WK);
  m = 0;
  mbar_wait_long(sb + PB + (G == 0 ? 13 : 6) * 8, 0);
  if (threadIdx.x == 0) PT(0, 11);
  const uint32_t src = (G == 0 ? sb + WOF : sb + WOSTAGE + 2 * 24576) + afrag_off(w, lane);
  if (G == 1) {
    for (int kk = 0; kk < 12; kk++) { uint32_t f[4]; ldsm4t(f, src + kk * 2048); m = mag4(m, f); }
    publish_max(sb + WMX + 4, m);
    bar_sync(7, 384);
  }
  if (G == 1 || w < 2) {
    for (int kk = 0; kk < 12; kk++) {
      uint32_t f[4];
      ldsm4t(f, src + ((kk + 4 * j) % 12) * 2048);
      sts128(sb + WOF + ((G == 0 ? 4 + w : w) * 12 + kk) * 512 + lane * 16, f[0], f[1], f[2], f[3]);
      if (G == 0) m = mag4(m, f);
    }
  }
  if (G == 0) { publish_max(sb + WMX + 4, m); bar_sync(7, 384); }
  bar_sync(7, 384);
}
DEVI void arrange_wq(uint32_t sb, int G, int w, int layer) {
  using namespace ch;
  const uint32_t lane = threadIdx.x & 31;
  mbar_wait_long(sb + BAR_W2, 0);
  if (threadIdx.x == 0) PT(0, 15);
  if (WQR) {
    const uint32_t src = sb + WQ + G * 40960 + afrag_off(w, lane), dst = sb + WQ + G * 40960 + w * 512 + lane * 16;
#pragma unroll 1
    for (int r = 0; r < 5; r++) {
      uint32_t f[4][4];
#pragma unroll
      for (int i = 0; i < 4; i++) ldsm4t(f[i], src + (r * 4 + i) * 2048);
      bar_sync(14 + G, 128);
#pragma unroll
      for (int i = 0; i < 4; i++) sts128(dst + (r * 4 + i) * 2048, f[i][0], f[i][1], f[i][2], f[i][3]);
    }
    __syncwarp();
  }
}

namespace tl {
constexpr uint32_t FULL = 225280, EMPTY = FULL + 56;
#define TSL0 10
constexpr int RT0 = 13, SL0 = TSL0;
}
DEVI uint32_t fresh_tid() { uint32_t t; asm volatile("mov.u32 %0, %%tid.x;" : "=r"(t)); return t; }
DEVI int fresh_cta() { uint32_t t; asm volatile("mov.u32 %0, %%ctaid.x;" : "=r"(t)); const uint32_t h = t * 86 >> 8; return (t - h * 3) * 32 + h; }
DEVI void ldcg128(uint32_t (&r)[4], const void* p) { asm volatile("ld.global.cg.v4.u32 {%0,%1,%2,%3}, [%4];" : "=r"(r[0]), "=r"(r[1]), "=r"(r[2]), "=r"(r[3]) : "l"(p) : "memory"); }
template <bool EF> DEVI void ldcg128_h(uint32_t (&r)[4], const void* p) {
  if (EF) asm volatile("ld.global.cg.L2::cache_hint.v4.u32 {%0,%1,%2,%3}, [%4], %5;" : "=r"(r[0]), "=r"(r[1]), "=r"(r[2]), "=r"(r[3]) : "l"(p), "l"(stream_policy()) : "memory");
  else ldcg128(r, p);
}
#define TNST 3
#define TCV 0
#define TPOS 2
#define CEF 1
#define TEF 1
template <bool EF> DEVI void tma2d_h(uint32_t dst, const CUtensorMap* m, int c0, int c1, uint32_t bar) {
  if (EF) asm volatile("cp.async.bulk.tensor.2d.shared::cluster.global.mbarrier::complete_tx::bytes.L2::cache_hint [%0], [%1, {%3, %4}], [%2], %5;"
                       :: "r"(dst), "l"(m), "r"(bar), "r"(c0), "r"(c1), "l"(stream_policy()) : "memory");
  else tma2d(dst, m, c0, c1, bar);
}
DEVI void tail_load(uint32_t sb, Sync* sy, const CUtensorMap* moa, const CUtensorMap* mwo, int layer) {
  using namespace tl;
  (void)layer;
  const int i = fresh_cta(), a = i & 3, b = (i & 31) >> 2, rt = RT0 + (i >> 5);
  const bool last = rt == 15;
  const int nst = last ? 7 : TNST, npre = last ? 7 : 0;
  const uint32_t ab = last ? 8192 : 16384, stage = ab + 20480;
#pragma unroll 1
  for (int g = 0; g < npre; g++) { mbar_expect(sb + FULL + g * 8, stage); tma3d(sb + g * stage + ab, mwo, 0, (b * 12 + g) * 64, a * 5, sb + FULL + g * 8); }
  spin_count(&sy->o[rt * 16 + b], last ? 4 : 8);
  if (!last) XT(i, 0);
  fence_flag_to_bulk();
  int st = 0, par = 1;
#pragma unroll 1
  for (int g = 0; g < (last ? 24 : 12); g++) {
    const uint32_t dst = sb + st * stage, fb = sb + FULL + st * 8;
    const int k = (b * 12 + (g < 12 ? g : g < 19 ? g - 7 : g - 19)) * 64;
    if (g == 12) { spin_count(&sy->o[15 * 16 + 8 + b], 4); XT(i, 0); fence_flag_to_bulk(); }
    if (g >= npre) {
      mbar_wait_long(sb + EMPTY + st * 8, par);
      mbar_expect(fb, g >= 12 && g < 19 ? ab : stage);
      if (g < 12 || g >= 19) tma3d(dst + ab, mwo, 0, k, a * 5, fb);
    }
    tma2d_h<TEF>(dst, moa, k, rt * 128 + (g >= 12) * 64, fb);
    if (!last) tma2d_h<TEF>(dst + 8192, moa, k, rt * 128 + 64, fb);
    if (++st == nst) { st = 0; par ^= 1; }
  }
}
DEVI void tail_sum(uint32_t sb, Sync* sy, const bf16* __restrict__ xin, int layer) {
  using namespace tl;
  const int ct = fresh_tid(), lane = ct & 31, cw = __shfl_sync(0xffffffffu, ct >> 7, 0), w = ct >> 5 & 3;
  const int i = TCV ? __shfl_sync(0xffffffffu, fresh_cta(), 0) : blockIdx.x % 3 * 32 + blockIdx.x / 3, a = i & 3, b = (i & 31) >> 2, rt = RT0 + (i >> 5);
  const bool last = rt == 15;
  const uint32_t nst = last ? 7 : TNST, stage = last ? 28672 : 36864, ao = last ? 0 : cw * 8192, bo = stage - 20480, ost = sb + (last ? 200704 : 184320 + cw * 20480);
  float d[80];
#pragma unroll
  for (int n = 0; n < 80; n++) d[n] = 0.f;
  bar_sync(14, 288);
  if (last && cw) bar_sync(6, 256);
  uint32_t st = last && cw ? 5 : 0, par = last && cw, prev = 0;
#pragma unroll 1
  for (int c = 0; c < 12; c++) {
    mbar_wait_long(sb + FULL + st * 8, par);
    if (c == 0 && ct == 128) XT(i, 1);
    const uint64_t da = mkdesc(sb + st * stage + ao, 16, 1024, 1), db = mkdesc(sb + st * stage + bo, 4096, 512, 2);
    wg_fence();
#pragma unroll
    for (int k = 0; k < 4; k++) wgmma_n160_nt(d, da + k * 2, db + k * 64, c | k);
    wg_commit();
    if (c > 0) { wg_wait<1>(); if (lane == 0) mbar_arrive(prev); }
    prev = sb + EMPTY + st * 8;
    if (++st == nst) { st = 0; par ^= 1; }
  }
  if (last && !cw) bar_arrive(6, 256);
  const int rl = last ? cw * 64 + b * 8 + (ct >> 4 & 7) : b * 16 + (ct >> 4), q = ct & 15, r = rt * 128 + rl;
  const int c0 = r * DM + a * 160 + q * 8, c1 = c0 + 128 - (q & 12) * 8;
  uint32_t u[9][2][4];
  ldcg128_h<(LEF & 4) != 0>(u[8][0], xin + c0); ldcg128_h<(LEF & 4) != 0>(u[8][1], xin + c1);
  if (last && cw) bar_sync(5, 256);
  wg_wait<0>();
  if (lane == 0) mbar_arrive(prev);
  const uint32_t orow = w * 16 + (lane & 15), ob = ost + orow * 64;
#pragma unroll
  for (int n = 0; n < 10; n++)
    stsm4(ob + (n >> 1) * 4096 + ((((n & 1) * 2 + (lane >> 4)) ^ ((orow >> 1) & 3)) << 4), pack_bf16(d[8 * n], d[8 * n + 1]), pack_bf16(d[8 * n + 2], d[8 * n + 3]),
          pack_bf16(d[8 * n + 4], d[8 * n + 5]), pack_bf16(d[8 * n + 6], d[8 * n + 7]));
  fence_async();
  bar_sync(7 + cw, 128);
  const int sl0 = SL0 * 8 + (rt - RT0) * 64 + a * 16;
  if ((ct & 127) == 0) {
    bulk_store(g_sl + (size_t)(sl0 + cw * 8 + b) * 10240, ost, 20480);
    asm volatile("cp.async.bulk.commit_group; cp.async.bulk.wait_group 0;" ::: "memory");
    XT(i, 2 + cw);
    publish_bulk<WFEN>(&sy->wcnt[(rt * 4 + a) * 2 + cw]);
  }
  if ((ct & 127) == 32) spin_count(&sy->wcnt[(rt * 4 + a) * 2 + (rl >> 6)], 8);
  __syncwarp();
  bar_sync(7 + cw, 128);
  const bf16* sl = g_sl + (size_t)(sl0 + (rl >> 6) * 8) * 10240 + (rl & 63) * 32 + (((q & 3) ^ (rl >> 1 & 3)) << 3);
#pragma unroll
  for (int n = 0; n < 8; n++) { ldcg128_h<(LEF & 2) != 0>(u[n][0], sl + n * 10240 + (q >> 2) * 2048); ldcg128_h<(LEF & 2) != 0>(u[n][1], sl + n * 10240 + 8192); }
  if (last && !cw) bar_arrive(5, 256);
  if (ct == 128 && last) XT(128 + (i & 31), 0);
  sched_fence(layer >> 4);
  const uint32_t id = (lane >> 2) == (lane & 3) * 2 ? 0x3F80u : (lane >> 2) == (lane & 3) * 2 + 1 ? 0x3F800000u : 0u;
  float y[4][4], s1 = 0.f, s2 = 0.f;
#pragma unroll
  for (int e = 0; e < 16; e++) y[e >> 2][e & 3] = 0.f;
#pragma unroll
  for (int n = 0; n < 9; n++)
#pragma unroll
    for (int m = 0; m < 2; m++) { mma16816(y[2 * m], u[n][m], id, 0u); mma16816(y[2 * m + 1], u[n][m], 0u, id); }
#pragma unroll
  for (int m = 0; m < 2; m++) {
    const bool on = !m || q < 4;
    uint32_t z[4];
    float t1 = 0.f, t2 = 0.f;
#pragma unroll
    for (int e = 0; e < 4; e++) {
      z[e] = pack_bf16(y[2 * m + (e >> 1)][(e & 1) * 2], y[2 * m + (e >> 1)][(e & 1) * 2 + 1]);
      const float lo = __uint_as_float(z[e] << 16), hi = __uint_as_float(z[e] & 0xFFFF0000u);
      t1 += lo + hi; t2 = fmaf(lo, lo, fmaf(hi, hi, t2));
    }
    if (on) { s1 += t1; s2 += t2; }
    asm volatile("{.reg .pred p; setp.ne.u32 p, %5, 0; @p st.global.v4.u32 [%0], {%1,%2,%3,%4};}"
                 :: "l"(g_xa + (m ? c1 : c0)), "r"(z[0]), "r"(z[1]), "r"(z[2]), "r"(z[3]), "r"((uint32_t)on) : "memory");
  }
#pragma unroll
  for (int o = 1; o < 16; o <<= 1) { s1 += __shfl_xor_sync(0xffffffffu, s1, o); s2 += __shfl_xor_sync(0xffffffffu, s2, o); }
  asm volatile("{.reg .pred p; setp.ne.u32 p, %3, 0; @p red.relaxed.gpu.global.add.v2.f32 [%0], {%1,%2};}"
               :: "l"(&sy->rstat[r]), "f"(s1), "f"(s2), "r"((uint32_t)(q == 0)) : "memory");
  if (ct == 128 && last) XT(128 + (i & 31), 1);
  if (BFL) {
    bar_sync(7 + cw, 128);
    if ((ct & 127) == 0) red_release(&sy->pro[1 + rt - RT0]);
    if (ct == 128 && last) XT(128 + (i & 31), 2);
    __syncwarp();
  }
}

__global__ void __cluster_dims__(3, 1, 1) __launch_bounds__(384, 1)
chain_kernel(const __grid_constant__ CUtensorMap mq, const __grid_constant__ CUtensorMap mk, const __grid_constant__ CUtensorMap mv,
             const __grid_constant__ CUtensorMap mo, const __grid_constant__ CUtensorMap mx, const bf16* __restrict__ mem0, const bf16* __restrict__ xin, uint32_t zero, int layer
             , const __grid_constant__ CUtensorMap moa, const __grid_constant__ CUtensorMap mwo
             ) {
  using namespace ch;
  extern __shared__ __align__(1024) uint8_t smraw[];
  const uint32_t sb = smem_u32(smraw);
  const int tid = threadIdx.x;
  const int wg = __shfl_sync(0xffffffffu, tid >> 7, 0), w = __shfl_sync(0xffffffffu, (tid >> 5) & 3, 0);
  int h, j;
  asm("mov.u32 %0, %%clusterid.x;" : "=r"(h));
  asm("mov.u32 %0, %%cluster_ctarank;" : "=r"(j));
  h = __shfl_sync(0xffffffffu, h, 0); j = __shfl_sync(0xffffffffu, j, 0);
  const int T0 = j == 0 ? 0 : (j == 1 ? 14 : 27), NT = j == 0 ? 14 : 13;
  const uint32_t PD = PD_, XD = XD_, X1D = X1D_;
  constexpr uint32_t CS = 0, UP = 0, DMIN = 0, FL = 0, SD = 0;

  if (tid == 0) {
    mbar_init(sb + BAR_W1, 1); mbar_init(sb + BAR_W2, 1); mbar_init(sb + BAR_X0, 1); mbar_init(sb + BAR_X1, 1);
    mbar_init(sb + BAR_S, 6); mbar_init(sb + BAR_O, 1); mbar_init(sb + BAR_WK, 1); mbar_init(sb + BAR_XF, 12);
    for (int i = 0; i < 14; i++) mbar_init(sb + PB + i * 8, 1);
    sts64(sb + WMX, 0, 0);
    asm volatile("fence.mbarrier_init.release.cluster;" ::: "memory");
    mbar_expect(sb + BAR_W2, 81920);
    mbar_expect(sb + BAR_S, 1280); mbar_expect(sb + BAR_O, 2048);
  }
  asm volatile("griddepcontrol.launch_dependents;");
  GT(0, 0);
  __syncthreads();
  asm volatile("barrier.cluster.arrive.relaxed.aligned;" ::: "memory");
  asm volatile("barrier.cluster.wait.aligned;" ::: "memory");
  if (tid == 0) PT(0, 0);
  const char* arb = (const char*)g_ar;
  const uint32_t xdesc = desc_lo(sb + XB, 16);

  if (wg < 2) {
    asm volatile("setmaxnreg.inc.sync.aligned.u32 208;");
    if (!(BLN && layer) && !(WLN >> layer & 1)) chain_prepare(xin);
    if (WLN != 3) bar_arrive(9, 352);
    uint32_t W[160];
    load_weights(W, sb, wg, w, j, layer);
    float inv_sc = 1.0f;
    if (wg == 0) {
      const uint32_t lane = lane_id();
      code_pad<PAD0>(zero);
      mbar_wait_long(sb + BAR_X0, 0);
      if (tid == 0) PT(0, 12);
      if (LSH == 1) bar_sync(8, 256);
      if (!LSH) {
        tokens_finish<false>(sb, W, xdesc, w, lane, 0, &mx);
        if (tid == 0) PT(0, 13);
        if (!KS2) bar_arrive(8, 256);
        arrange_wq(sb, 0, w, layer);
      }
#pragma unroll 1
      for (int s = LSH ? -1 : 0; s < NSEG; s++) {
        float sc = 1.0f;
        if (!LSH || s >= 0) {
        uint32_t A0[2];
        {
          float q[4], k[4], v[4];
          const uint32_t ln = opq(lane), t16 = w * 512 + ln * 16;
          uint32_t f[NF][4], wq = sb + WQ + (WQR ? t16 : afrag_off(w, ln)), ba = sb + MEMB + ln * 16;
          proj_stage(f, wq);
          PIN(ba);
          proj_mem<0>(q, k, v, f, W, wq, ba, sb, w, s);
          const uint32_t qd = sb + QS + w * 256 + ln * 4;
          sts32(qd, pack_bf16(q[0] * inv_sc, q[1] * inv_sc)); sts32(qd + 128, pack_bf16(q[2] * inv_sc, q[3] * inv_sc));
          sts32(qd + 2048, pack_bf16(k[0] * inv_sc, k[1] * inv_sc)); sts32(qd + 2048 + 128, pack_bf16(k[2] * inv_sc, k[3] * inv_sc));
          sts128(sb + EX + t16, __float_as_uint(k[0]), __float_as_uint(k[1]), __float_as_uint(k[2]), __float_as_uint(k[3]));
          E1(1, __float_as_uint(v[0]) ^ __float_as_uint(q[0]));
          uint32_t qa = sb + QS + ((ln >> 3) & 1) * 1024 + ((ln >> 4) * 8 + (ln & 7)) * 16;
          PIN(qa);
          TS(0);
          bar_sync(2, 384);
          if (w == 3 && s < NSEG - 1) {
            uint32_t b0[4], b1[4], c0[4], c1[4];
            const uint32_t ka = sb + KP + ln * 16;
            ldsm4t(b0, ka); ldsm4t(c0, ka + 1024); ldsm4t(b1, ka + 512); ldsm4t(c1, ka + 1536);
#pragma unroll
            for (int i = 0; i < 4; i++) { b0[i] = add_bf16x2(b0[i], c0[i]); b1[i] = add_bf16x2(b1[i], c1[i]); }
            score_tile(sb, qa, b0, b1, Peers(sb, j), SX + j * 640 + ln * 4, ln);
          }
          uint32_t e[4];
          lds128(e, sb + EX + 2048 + t16);
          A0[0] = pack_bf16((v[0] + __uint_as_float(e[0])) * inv_sc, (v[1] + __uint_as_float(e[1])) * inv_sc);
          A0[1] = pack_bf16((v[2] + __uint_as_float(e[2])) * inv_sc, (v[3] + __uint_as_float(e[3])) * inv_sc);
          const uint32_t slab = slab_off(VT, w, ln);
          sts32(sb + slab, A0[0]); sts32(sb + slab + 640, A0[1]);
          bar_arrive(12, 384);
        }
        if (s == NSEG - 1) break;
        {
          const uint32_t ln = opq(lane);
          const uint32_t va = sb + VT + (16 * w + (ln & 15)) * 80 + 16 + (ln >> 4) * 16;
          const uint32_t sa = sb + SX + ln * 4, off = OB + w * 256 + ln * 4;
          const Peers pe(sb, j);
          uint32_t f1[4], f2[4];
          ldsm4(f1, va); ldsm4(f2, va + 32);
          TSX(TS(1));
          mbar_wait(sb + BAR_S, s & 1);
          TS(2);
          uint32_t u[3][5];
#pragma unroll
          for (int i = 0; i < 15; i++) u[i / 5][i % 5] = lds32(sa + (i % 5) * 128 + (i / 5) * 640);
          E1(2, u[0][0]);
          sched_fence(zero);
          uint32_t hs[5];
#pragma unroll
          for (int i = 0; i < 5; i++) hs[i] = hadd2(hadd2(u[0][i], u[1][i]), u[2][i]);
          uint32_t m2 = hmax2(hmax2(hmax2(hs[0], hs[1]), hmax2(hs[2], hs[3])), hs[4]);
          asm volatile("bar.arrive 13, 384;" : "+r"(m2) :: "memory");
          m2 = hmax2(m2, __byte_perm(m2, 0, 0x1032));
          m2 = hmax2(m2, __shfl_xor_sync(0xffffffffu, m2, 1));
          m2 = hmax2(m2, __shfl_xor_sync(0xffffffffu, m2, 2));
          TSX(TSD(3, m2));
          const float m4 = -4.0f * __low2float(*reinterpret_cast<__half2*>(&m2));
          uint32_t P[5];
#pragma unroll
          for (int i = 0; i < 5; i++) {
            const float2 x = __half22float2(*reinterpret_cast<__half2*>(&hs[i]));
            P[i] = pack_bf16(ex2(fmaf(x.x, 4.0f, m4)), ex2(fmaf(x.y, 4.0f, m4)));
          }
          float o[4] = {0.f, 0.f, 0.f, 0.f}, o2[4] = {0.f, 0.f, 0.f, 0.f}, o3[4] = {0.f, 0.f, 0.f, 0.f};
          mma16816(o2, f1, P[1], P[2]); mma1688(o, A0[0], A0[1], P[0]); mma16816(o3, f2, P[3], P[4]);
          const uint32_t w0 = pack_bf16((o[0] + o2[0]) + o3[0], (o[1] + o2[1]) + o3[1]), w1 = pack_bf16((o[2] + o2[2]) + o3[2], (o[3] + o2[3]) + o3[3]);
#pragma unroll
          for (int r = 0; r < 2; r++) { st_async32(pe.a[r] + off + (2 - r) * 1024, w0, pe.a[r] + BAR_O); st_async32(pe.a[r] + off + (2 - r) * 1024 + 128, w1, pe.a[r] + BAR_O); }
          E1(3, w0 ^ w1);
          sts32(sb + off, w0); sts32(sb + off + 128, w1);
          if (w == 3) {
            float z[4] = {0.f, 0.f, 0.f, 0.f}, z2[4] = {0.f, 0.f, 0.f, 0.f};
            const uint32_t one[4] = {0x3F803F80u, 0x3F803F80u, 0x3F803F80u, 0x3F803F80u};
            mma1688(z, one[0], one[1], P[0]); mma16816(z2, one, P[1], P[2]); mma16816(z, one, P[3], P[4]);
            if (ln < 4) sts64(sb + INV + ln * 8, __float_as_uint(rcp(z[0] + z2[0])), __float_as_uint(rcp(z[1] + z2[1])));
          }
          TS(4);
        }
        if (12 + w < NT) {
          const uint32_t ln = opq(lane);
          const char* pr = arb + ar_tile_off(T0 + 12 + w) + ln * 4; const char* px = arb + ar_extra_off(T0 + 12 + w);
          PINL(pr);
          wo_tile_smem<true>(sb, sb + WOF + (4 + w) * 6144 + ln * 16, sb + OB + ln * 16, s & 1, pr, px, ln == 31, sc);
        } else {
          bar_sync(9, 384);
          sc = __uint_as_float(lds32(sb + MX + 16));
          if (w == 3 && lane == 0) {
            mbar_expect(sb + BAR_S, 1280);
            if (!KS2 && !X1E && j == 1 && s + 2 < NSEG) {
              mbar_wait(sb + BAR_XF, s & 1);
              tma3d_mc(sb + XB + 20480, &mx, 0, (s + 2) * SEG, 5, sb + BAR_X1, 7);
            }
            mbar_wait(sb + BAR_O, s & 1);
            mbar_expect(sb + BAR_O, 2048);
          }
          __syncwarp();
        }
        TSX(TS(5));
        if (w == 1) SS(0);
        mbar_wait(sb + BAR_X0, (s + 1) & 1);
        if (w == 1) SS(1);
        bar_sync(4, 384);
        if (w == 1) SS(2);
        arb += AR_STEP_BYTES;
        }
        tokens_finish<true>(sb, W, xdesc, w, lane, s);
        TS(6);
        if (LSH && s < 0) {
          if (tid == 0) PT(0, 13);
          arrange_wq(sb, 0, w, layer);
        }
        inv_sc = __uint_as_float(0x7F000000u - __float_as_uint(sc));
      }
    } else {
      const uint32_t lane = lane_id();
      static_assert(!X0E && !KS2, "prologue");
      code_pad<PAD1>(zero);
#pragma unroll 1
      for (int pass = 0; pass < (LSH ? 1 : 2); pass++) {
        mbar_wait_long(sb + BAR_X1, pass);
        if (pass) bar_sync(8, 256);
        tokens_partial<0>(sb, PK, W, xdesc, w, lane);
        if (pass) break;
        mbar_wait(sb + BAR_X1, 0);
        tokens_partial<0>(sb, QS, W + 80, xdesc, w, lane);
        bar_sync(8, 256);
      }
      if (LSH) {
        if (w == 3 && lane == 0) { mbar_expect(sb + BAR_X1, 20480); tma3d(sb + XB + 20480, &mx, 0, SEG, 5, sb + BAR_X1); }
        __syncwarp();
      } else {
        if (tid == 128) PT(0, 14);
        arrange_wq(sb, 1, w, layer);
      }
#pragma unroll 1
      for (int s = LSH ? -1 : 0; s < NSEG; s++) {
        float sc = 1.0f;
        if (!LSH || s >= 0) {
        {
          float q[4], k[4], v[4];
          const uint32_t ln = opq(lane), t16 = w * 512 + ln * 16;
          uint32_t f[NF][4], wq = sb + WQ + 40960 + (WQR ? t16 : afrag_off(w, ln)), ba = sb + MEMB + 5120 + ln * 16;
          proj_stage(f, wq);
          PIN(ba);
          proj_mem<1>(q, k, v, f, W, wq, ba, sb, w, s);
          const uint32_t qd = sb + QS + 1024 + w * 256 + ln * 4;
          sts32(qd, pack_bf16(q[0] * inv_sc, q[1] * inv_sc)); sts32(qd + 128, pack_bf16(q[2] * inv_sc, q[3] * inv_sc));
          sts32(qd + 2048, pack_bf16(k[0] * inv_sc, k[1] * inv_sc)); sts32(qd + 2048 + 128, pack_bf16(k[2] * inv_sc, k[3] * inv_sc));
          sts128(sb + EX + 2048 + t16, __float_as_uint(v[0]), __float_as_uint(v[1]), __float_as_uint(v[2]), __float_as_uint(v[3]));
          TSX(TS(0));
          bar_sync(2, 384);
          uint32_t e[4];
          lds128(e, sb + EX + t16);
          const uint32_t slab = slab_off(KT, w, ln);
          sts32(sb + slab, pack_bf16((k[0] + __uint_as_float(e[0])) * inv_sc, (k[1] + __uint_as_float(e[1])) * inv_sc));
          sts32(sb + slab + 640, pack_bf16((k[2] + __uint_as_float(e[2])) * inv_sc, (k[3] + __uint_as_float(e[3])) * inv_sc));
        }
        if (s == NSEG - 1) { bar_arrive(12, 384); break; }
        if (w == 1) SS(3);
        if (KS2) mbar_wait(sb + BAR_X1, (s + 1) & 1);
        if (w == 1) SS(4);
        if (VL) {
          bar_arrive(12, 384); bar_arrive(13, 384);
          bar_sync(9, 384);
          tokens_partial<3>(sb, QS, W + 80, xdesc, w, lane);
        } else {
          bar_sync(5, 288);
          TSX(TS(1));
          tokens_partial<1>(sb, QS, W + 80, xdesc, w, lane);
        }
        if (!KS2 && X1E && j == 1 && w == 3 && s + 2 < NSEG) {
          if (opq(lane) == 0) {
            mbar_wait(sb + BAR_XF, s & 1);
            tma3d_mc(sb + XB + 20480, &mx, 0, (s + 2) * SEG, 5, sb + BAR_X1, 7);
          }
          __syncwarp();
        }
        TS(2);
        {
          const uint32_t ln = opq(lane);
          const char* pr = arb + ar_tile_off(T0 + 8 + w) + ln * 4; const char* px = arb + ar_extra_off(T0 + 8 + w);
          PINL(pr);
          wo_tile_smem<!VL>(sb, sb + WOF + w * 6144 + ln * 16, sb + OB + ln * 16, s & 1, pr, px, ln == 31, sc);
        }
        if (KS2) bar_sync(4, 384);
        else if (KORD) {
          if (s + 2 < NSEG) mbar_wait(sb + BAR_X1, s & 1);
          bar_sync(4, 384);
        } else {
          bar_arrive(4, 384);
        }
        arb += AR_STEP_BYTES;
        }
        if (!KS2 && !KORD) {
          if (s + 2 < NSEG) { if (LSH && s < 0) mbar_wait_long(sb + BAR_X1, 1); else mbar_wait(sb + BAR_X1, s & 1); }
          bar_sync(6, 256);
        }
        tokens_partial<2>(sb, PK, W, xdesc, w, lane);
        if (LSH && s < 0) {
          if (tid == 128) PT(0, 14);
          arrange_wq(sb, 1, w, layer);
        }
        if (X0E && j == 0 && w == 2 && s + 2 < NSEG) {
          if (opq(lane) == 0) {
            mbar_wait(sb + BAR_XF, (s + 1) & 1);
            const uint32_t t9 = clk32();
            while (clk32() - t9 < X0D_) {}
            tma3d_mc(sb + XB, &mx, 0, (s + 2) * SEG, 0, sb + BAR_X0, 7);
          }
          __syncwarp();
        }
        if (KS2 && j == 1 && w == 0 && s + 2 < NSEG) {
          if (opq(lane) == 0) {
            mbar_wait(sb + BAR_XF, s & 1);
            tma3d_mc(sb + XB + 20480, &mx, 0, (s + 2) * SEG, 5, sb + BAR_X1, 7);
          }
          __syncwarp();
        }
        TS(4);
        inv_sc = __uint_as_float(0x7F000000u - __float_as_uint(sc));
      }
    }
    asm volatile("barrier.cluster.arrive.relaxed.aligned;" ::: "memory");
    tail_sum(sb, &g_sync[layer], xin, layer);
  } else {
    asm volatile("setmaxnreg.dec.sync.aligned.u32 88;");
    const uint32_t lane = lane_id();
    uint32_t W[44];
    if (tid - 256 < 80) asm volatile("prefetch.global.L2 [%0];" :: "l"(mem0 + (tid - 256) * 64) : "memory");
    if (w == 3) {
      if (layer && LNF == 1) bar_sync(10, 64);
      const int win = layer ? PWIN1 : PWIN;
#pragma unroll
      for (int part = 0; part < 2; part++) {
        if (lane == 0) {
#pragma unroll
          for (int i = part ? 2 : 0; i < (part ? 14 : 2); i++) {
            const uint32_t bar = sb + PB + i * 8;
            if (i >= win) mbar_wait_long(bar - win * 8, 0);
            if (i == 12) mbar_wait_long(sb + BAR_W1, 0);
            if (PQP && layer && i >= PQP && i < PQP + 5 / PQN + (5 % PQN != 0))
              for (int n = (i - PQP) * PQN; n < min((i - PQP + 1) * PQN, 5); n++)
                asm volatile("cp.async.bulk.prefetch.tensor.2d.L2.global [%0, {%1, %2}];" :: "l"(&mq), "r"(h * DH + 64 * j), "r"(n * 128) : "memory");
            if (i < 5 || (i >= 7 && i < 12)) {
              mbar_expect(bar, 16384);
              if (i < 5) tma2d_h<CEF>(sb + 81920 + i * 16384, &mv, h * DH + 64 * j, i * 128, bar);
              else tma2d_h<CEF>(sb + (i - 7) * 16384, &mk, h * DH + 64 * j, (i - 7) * 128, bar);
            } else {
              const int bx = i < 7 ? i - 4 : (i - 12) * 3;
              mbar_expect(bar, 24576);
              tma2d(bx < 3 ? sb + WOSTAGE + bx * 24576 : sb + WOF, &mo, T0 * 16 + 64 * bx, h * DH, bar);
            }
          }
        }
        __syncwarp();
        if (part == 0 && layer && LNF == 2) bar_sync(10, 64);
      }
      if (lane == 0) {
        if (PQB && (PQL >> layer & 1)) for (int i = 2; i < 2 + PQM; i++) tma2d_prefetch(&mq, h * DH + 64 * j, i * 128);
        mbar_wait_long(sb + BAR_WK, 0);
        for (int i = 0; i < 2; i++) tma2d(sb + WQ + i * 16384, &mq, h * DH + 64 * j, i * 128, sb + BAR_W2);
        if (!PQB && (PQL >> layer & 1)) for (int i = 2; i < 2 + PQM; i++) tma2d_prefetch(&mq, h * DH + 64 * j, i * 128);
      }
      __syncwarp();
    } else {
      if (!(BLN && layer) && !(WLN >> layer & 1)) {
        chain_prepare(xin);
        for (int i = blockIdx.x * 96 + tid - 256; i < (NSEG - 1) * 24 * 32; i += 96 * 96) ((uint4*)g_ar)[(i >> 5) * 64 + (i & 31)] = make_uint4(0, 0, 0, 0);
      } else if (BLN && w == 0) asm volatile("griddepcontrol.wait;" ::: "memory");
      if (WLN != 3) bar_sync(9, 352);
    }
    PT(0, 1);
    if (w == 0) {
      if (lane == 0) {
        if (layer) sts32(sb + MX + 24, __ldcg(&g_kw));
        if (!(WLN >> layer & 1)) red_release(&g_sync[layer].pro[0]);
        else if (layer && blockIdx.x == 0) {
          asm volatile("griddepcontrol.wait;" ::: "memory");
          if (WREL) red_release(&g_sync[1].pro[1]);
          else asm volatile("red.relaxed.gpu.global.add.u32 [%0], 1;" :: "l"(&g_sync[1].pro[1]) : "memory");
        }
      }
      PT(0, 2);
      __syncwarp();
      if (layer && LNF) bar_arrive(10, 64);
    }
    if (!(PSPL && layer) && !(WLN & 1) && tid == 256) spin_count(&g_sync[layer].pro[0], 96);
    __syncwarp();
    PT(0, 3);
    mbar_wait_long(sb + PB + 5 * 8, 0); mbar_wait_long(sb + PB + 12 * 8, 0);
    PT(0, 4);
    {
      const int i = lane >> 3, r = lane & 7;
      uint32_t m = 0;
#pragma unroll
      for (int kk = 0; kk < 12; kk++)
#pragma unroll
        for (int tt = 0; tt < 2; tt++) {
          const int tl = 2 * w + tt;
          const uint32_t src = sb + WOSTAGE + (tl >> 2) * 24576 + (((kk + 4 * j) % 12) * 16 + (i >> 1) * 8 + r) * 128 + ((((tl & 3) * 2 + (i & 1)) ^ r) << 4);
          const int q = kk * 2 + tt;
          if (q >= 13) { ldsm4t_p(&W[(q - 13) * 4], src); m = mag4(m, &W[(q - 13) * 4]); }
          else { uint32_t f[4]; ldsm4t(f, src); sts128(sb + (q < 12 ? WOF2 + (w * 12 + q) * 512 : WOF3 + w * 512) + lane * 16, f[0], f[1], f[2], f[3]); m = mag4(m, f); }
        }
      publish_max(sb + WMX + 4, m);
    }
    bar_sync(7, 384);
    PT(0, 5);
    if (tid == 256 && !layer) {
      const float2 mm = lds64f(sb + WMX);
      asm volatile("st.relaxed.gpu.global.u32 [%0], %1;" :: "l"(&g_sync[layer].wmax[blockIdx.x]), "r"(0x10000u | (__float_as_uint(mm.x) >> 7 << 8) | (__float_as_uint(mm.y) >> 7)) : "memory");
    }
    uint32_t m0[3][8];
#pragma unroll
    for (int i = 0; i < 24; i++) m0[i >> 3][i & 7] = __ldg((const uint32_t*)(mem0 + (i & 7) * DM) + min(tid - 256 + (i >> 3) * 128, DM / 2 - 1));
    if (tid == 352) {
      if (BLN) asm volatile("griddepcontrol.wait;" ::: "memory");
      else if (WLN >> layer & 1) spin_count(&g_sync[layer].pro[2], 4);
      else if (PSPL && layer) spin_count(&g_sync[layer].pro[0], 96);
      if (XFEN == 0) asm volatile("fence.proxy.async;" ::: "memory");
      if (XFEN == 1) asm volatile("fence.proxy.async.global;" ::: "memory");
      mbar_expect(sb + BAR_X1, 20480); tma3d(sb + XB + 20480, &mx, 0, 0, 5, sb + BAR_X1);
      mbar_expect(sb + BAR_X0, 20480); tma3d(sb + XB, &mx, 0, 0, 0, sb + BAR_X0);
      for (int i = 2; i < 5; i++) tma2d(sb + WQ + i * 16384, &mq, h * DH + 64 * j, i * 128, sb + BAR_W2);
    }
    __syncwarp();
    bar_sync(7, 384);
    PT(0, 6);
    uint32_t wv[3];
    if (w == 0 && !layer)
#pragma unroll
      for (int i = 0; i < 3; i++) asm volatile("ld.relaxed.gpu.global.u32 %0, [%1];" : "=r"(wv[i]) : "l"(&g_sync[layer].wmax[lane + i * 32]) : "memory");
    {
      int em;
      uint32_t m = 0;
#pragma unroll
      for (int i = 0; i < 3; i++) {
        const int p = tid - 256 + i * 128;
        if (p < DM / 2) {
          uint32_t lo[4], hi[4];
#pragma unroll
          for (int q = 0; q < 4; q++) { lo[q] = __byte_perm(m0[i][2 * q], m0[i][2 * q + 1], 0x5410); hi[q] = __byte_perm(m0[i][2 * q], m0[i][2 * q + 1], 0x7632); }
          sts128(sb + MEMB + p * 32, lo[0], lo[1], lo[2], lo[3]); sts128(sb + MEMB + p * 32 + 16, hi[0], hi[1], hi[2], hi[3]);
        }
#pragma unroll
        for (int q = 0; q < 8; q++) m = __vmaxu2(m, m0[i][q] & 0x7FFF7FFFu);
      }
      em = __reduce_max_sync(0xffffffffu, (int)(max(m & 0xFFFFu, m >> 16) >> 7) - 126);
      if (lane == 0) sts32(sb + MX + w * 4, em);
    }
    if ((WLN >> layer & 1) && tid == 352) spin_count(&g_sync[layer].pro[0], 128);
    __syncwarp();
    PT(0, 7);
    bar_arrive(1, 384);
    bar_sync(3, 384);
    if (w == 0 && !layer) {
      for (int n = 0; n < 4000000 && !__all_sync(0xffffffffu, (wv[0] & wv[1] & wv[2]) >> 16); n++) {
#pragma unroll
        for (int i = 0; i < 3; i++) asm volatile("ld.relaxed.gpu.global.u32 %0, [%1];" : "=r"(wv[i]) : "l"(&g_sync[layer].wmax[lane + i * 32]) : "memory");
      }
      const int ev = __reduce_max_sync(0xffffffffu, max(max(wv[0] >> 8 & 255, wv[1] >> 8 & 255), wv[2] >> 8 & 255));
      const int eo = __reduce_max_sync(0xffffffffu, max(max(wv[0] & 255, wv[1] & 255), wv[2] & 255));
      if (lane == 0) {
        sts32(sb + MX + 24, 245 - ev - eo);
        if (blockIdx.x == 0) g_kw = 245 - ev - eo;
      }
      __syncwarp();
    }
    int dly = PD;
    PT(0, 8);
    for (int s = 0; s < NSEG; s++) {
      const uint32_t t0 = clk32();
      TS(0);
      {
        uint32_t b0[4], b1[4];
        const uint32_t ln = opq(lane);
        const uint32_t ka = sb + KT + ln * 80 + (1 + w) * 16;
        ldsm4t(b0, ka); ldsm4t(b1, ka + 2560);
        if (w == 0 && ln == 0 && s + 1 < NSEG) {
          if (!X0E && j == 0) {
            mbar_wait(sb + BAR_XF, s & 1);
            while (clk32() - t0 < XD) {}
            tma3d_mc(sb + XB, &mx, 0, (s + 1) * SEG, 0, sb + BAR_X0, 7);
          }
          if (s + 2 < NSEG - 1 && !(FL & 2)) asm volatile("prefetch.global.L2 [%0];" :: "l"(arb + 2 * AR_STEP_BYTES + ar_line_off(h * 3 + j)) : "memory");
          if (PFW && layer == 0 && s >= PFW && s < PFW + 10) tma2d_prefetch(s & 1 ? &mk : &mv, h * DH + 64 * j, ((s - PFW) >> 1) * 128);
          if (j == 2 && h == (s & 31) && s + 3 < NSEG) { tma3d_prefetch(&mx, 0, (s + 3) * SEG, 0); tma3d_prefetch(&mx, 0, (s + 3) * SEG, 5); }
        }
        __syncwarp();
        uint32_t qa = sb + QS + ((ln >> 3) & 1) * 1024 + ((ln >> 4) * 8 + (ln & 7)) * 16, off = SX + j * 640 + (1 + w) * 128 + ln * 4;
        PIN(qa); PIN(off);
        bar_sync(2, 384);
        if (s == NSEG - 1) break;
        score_tile(sb, qa, b0, b1, Peers(sb, j), off, ln);
        bar_sync(12, 384);
        if (SD) bar_sync(13, 384);
        if (w == 1 && ln == 0 && !(FL & 1)) {
          store_slabs(sb, s, h, j);
        }

        __syncwarp();
      }
      if (w == 0) {
        uint32_t v[4]; lds128(v, sb + MX);
        const int kw = lds32(sb + MX + 24);
        const int em = max(max(max((int)v[0], (int)v[1]), max((int)v[2], (int)v[3])), 1);
        const int e = min(max(kw - em, -120), 120);
        if (opq(lane) == 0) { sts32(sb + MX + 16, (uint32_t)(e + 127) << 23); sts32(sb + MX + 20, 0u); }
      }
      if (!SD) bar_sync(13, 384);
      uint32_t tref;
      {
        float c0[4] = {0.f, 0.f, 0.f, 0.f}, c1[4] = {0.f, 0.f, 0.f, 0.f}, d0[4] = {0.f, 0.f, 0.f, 0.f}, d1[4] = {0.f, 0.f, 0.f, 0.f};
        uint32_t f[4][4], b[2][4];
        const uint32_t ln = opq(lane);
        const uint32_t fa = sb + WOF2 + w * 6144 + ln * 16, ob = sb + OB + ln * 16;
#pragma unroll
        for (int i = 0; i < 4; i++) lds128(f[i], fa + i * 512);
        if (w == 1) SS(5);
        asm volatile("cp.async.bulk.wait_group.read 0;" ::: "memory");
        if (w == 1) SS(6);
        bar_sync(9, 384);
        ldsm4t(b[0], ob); ldsm4t(b[1], ob + 512);
        mma16816(c0, f[0], b[0][0], b[0][1]); mma16816(c1, f[1], b[0][0], b[0][1]);
        lds128(f[0], fa + 2048); lds128(f[1], fa + 2560);
        mma16816(d0, f[2], b[0][2], b[0][3]); mma16816(d1, f[3], b[0][2], b[0][3]);
        lds128(f[2], fa + 3072); lds128(f[3], fa + 3584);
        mma16816(c0, f[0], b[1][0], b[1][1]); mma16816(c1, f[1], b[1][0], b[1][1]);
        mma16816(d0, f[2], b[1][2], b[1][3]); mma16816(d1, f[3], b[1][2], b[1][3]);
#pragma unroll
        for (int i = 0; i < 4; i++) lds128(f[i], fa + (8 + i) * 512);
        mbar_wait(sb + BAR_O, s & 1);
        ldsm4t(b[0], ob + 1024);
        E1(4, b[0][0]);
        mma16816(c0, f[0], b[0][0], b[0][1]); mma16816(c1, f[1], b[0][0], b[0][1]);
        mma16816(d0, f[2], b[0][2], b[0][3]); mma16816(d1, f[3], b[0][2], b[0][3]);
        ldsm4t(b[0], ob + 1536); lds128(f[0], sb + WOF3 + w * 512 + ln * 16); ldsm4t(f[1], ob + 2048); ldsm4t(f[2], ob + 2560);
        float2 iv = lds64f(sb + INV + (ln & 3) * 8);
        const float sc = __uint_as_float(lds32(sb + MX + 16));
        sched_fence(zero);
        mma16816(c1, &W[0], b[0][0], b[0][1]); mma16816(d0, &W[4], b[0][2], b[0][3]); mma16816(d1, &W[8], b[0][2], b[0][3]);
        mma16816(c0, f[0], b[0][0], b[0][1]);
        const char* pr = arb + ar_tile_off(T0 + 2 * w) + ln * 4;
        PINL(pr);
        iv.x *= sc; iv.y *= sc;
        mma16816(c1, &W[16], f[1][0], f[1][1]); mma16816(d0, &W[20], f[1][2], f[1][3]); mma16816(d1, &W[24], f[1][2], f[1][3]);
        mma16816(c0, &W[12], f[1][0], f[1][1]);
        mma16816(c1, &W[32], f[2][0], f[2][1]); mma16816(d0, &W[36], f[2][2], f[2][3]); mma16816(d1, &W[40], f[2][2], f[2][3]);
        mma16816(c0, &W[28], f[2][0], f[2][1]);
        const uint32_t w2 = pack_f16((c1[0] + d1[0]) * iv.x, (c1[1] + d1[1]) * iv.y), w3 = pack_f16((c1[2] + d1[2]) * iv.x, (c1[3] + d1[3]) * iv.y);
        wo_red(pr + ((T0 & 1) ? 768 : 256), w2, w3, ln == 31);
        const uint32_t w0 = pack_f16((c0[0] + d0[0]) * iv.x, (c0[1] + d0[1]) * iv.y), w1 = pack_f16((c0[2] + d0[2]) * iv.x, (c0[3] + d0[3]) * iv.y);
        E1(5, w0 ^ w2);
        wo_red(pr, w0, w1, ln == 31);
        wo_red_extra_p(arb + ar_extra_off(T0 + 2 * w + 1), w2, w3, ln);
        wo_red_extra_p(arb + ar_extra_off(T0 + 2 * w), w0, w1, ln);
        if (TSYNC) bar_sync(4, 384); else bar_arrive(4, 384);
        tref = clk32();
      }
      TSV(2, tref); TS(3);
      if (w == 1 && opq(lane) == 0) {
        asm volatile("cp.async.bulk.wait_group 0;" ::: "memory");
        publish_bulk<0>(&g_sync[layer].kv[s * NH + h]);
      }
      __syncwarp();
      {
        const uint32_t m = ar_read(arb, sb, w, lane, zero, tref, dly, s);
        dly = lds32(sb + MX + 20) ? dly + (int)UP : max(dly - (int)CS, (int)DMIN);
        if (w == 3) TSV(1, dly);
        const int em = __reduce_max_sync(0xffffffffu, (int)(max(m & 0xFFFFu, m >> 16) >> 10) - 13 + 127 - (int)(lds32(sb + MX + 16) >> 23));
        if (opq(lane) == 0) sts32(sb + MX + w * 4, em);
      }
      arb += AR_STEP_BYTES;
    }
    asm volatile("barrier.cluster.arrive.relaxed.aligned;" ::: "memory");
    if (fresh_tid() >= 352) {
      if (fresh_tid() == 352) {
        asm volatile("prefetch.tensormap [%0];" :: "l"(&mwo) : "memory"); asm volatile("prefetch.tensormap [%0];" :: "l"(&moa) : "memory");
        const uint32_t n = fresh_cta() < 64 ? 8 : 4;
        for (int i = 0; i < 7; i++) { mbar_init(sb + tl::FULL + i * 8, 1); mbar_init(sb + tl::EMPTY + i * 8, n); }
        asm volatile("fence.mbarrier_init.release.cluster;" ::: "memory");
      }
      __syncwarp();
      bar_arrive(14, 288);
    }
    bar_sync(12, 384);
    if (LASTG) {
      bf16* kvp = g_kv + ((size_t)((NSEG - 1) * NH + h) * 2 * DH + 64 * j) * NKEY;
#pragma unroll
      for (int k = 0; k < 5; k++) {
        const int u = k * 128 + tid - 256;
        uint32_t v[4];
        lds128(v, sb + KT + u * 16);
        __stcg((uint4*)(kvp + (u < 320 ? u * 8 : DH * NKEY + (u - 320) * 8)), make_uint4(v[0], v[1], v[2], v[3]));
      }
      bar_sync(10, 128);
      if (tid == 256 + 32) {
        asm volatile("cp.async.bulk.wait_group 0;" ::: "memory");
        red_release(&g_sync[layer].kv[(NSEG - 1) * NH + h]);
        GT(0, 1);
        if (TPOS < 2) tail_load(sb, &g_sync[layer], &moa, &mwo, layer);
      }
      __syncwarp();

    } else if (tid == 256 + 32) {
      store_slabs(sb, NSEG - 1, h, j);
      asm volatile("cp.async.bulk.wait_group 0;" ::: "memory");
      publish_bulk<WFEN>(&g_sync[layer].kv[(NSEG - 1) * NH + h]);
    }
  }
  if (TPOS) {
    const uint32_t t = fresh_tid();
    uint32_t sb2 = smem_u32(smraw);
    if (TPOS == 3) sb2 += zero;
    if (TPOS >= 2 && t == 288) tail_load(sb2, &g_sync[layer], &moa, &mwo, layer);
    __syncwarp();
  }
  asm volatile("barrier.cluster.wait.aligned;" ::: "memory");
}

DEVI void bulk_load(uint32_t dst, const void* g, uint32_t bytes, uint32_t bar) {
  if (EVF & 2) asm volatile("cp.async.bulk.shared::cluster.global.mbarrier::complete_tx::bytes.L2::cache_hint [%0], [%1], %2, [%3], %4;" :: "r"(dst), "l"(g), "r"(bytes), "r"(bar), "l"(stream_policy()) : "memory");
  else asm volatile("cp.async.bulk.shared::cluster.global.mbarrier::complete_tx::bytes [%0], [%1], %2, [%3];" :: "r"(dst), "l"(g), "r"(bytes), "r"(bar) : "memory");
}
DEVI void bulk_load_plain(uint32_t dst, const void* g, uint32_t bytes, uint32_t bar) {
  asm volatile("cp.async.bulk.shared::cluster.global.mbarrier::complete_tx::bytes [%0], [%1], %2, [%3];" :: "r"(dst), "l"(g), "r"(bytes), "r"(bar) : "memory");
}
DEVI void tma3d_store(const CUtensorMap* m, uint32_t src, int c0, int c1, int c2) {
  if (EVF & 4) asm volatile("cp.async.bulk.tensor.3d.global.shared::cta.bulk_group.L2::cache_hint [%0, {%2, %3, %4}], [%1], %5;" :: "l"(m), "r"(src), "r"(c0), "r"(c1), "r"(c2), "l"(stream_policy()) : "memory");
  else asm volatile("cp.async.bulk.tensor.3d.global.shared::cta.bulk_group [%0, {%2, %3, %4}], [%1];" :: "l"(m), "r"(src), "r"(c0), "r"(c1), "r"(c2) : "memory");
}
namespace wk {
constexpr uint32_t STAGE = 40960, NST = 4, OST = NST * STAGE;
constexpr uint32_t MISC = OST + 49152;
constexpr uint32_t FULL = MISC, EMPTY = MISC + 32, TFULL = MISC + 64, TEMPTY = MISC + 80, TASK = MISC + 96;
constexpr uint32_t DONE = MISC + 104, FREE = MISC + 120, DTASK = MISC + 136, FIN = MISC + 144, DSLOT = MISC + 152;
constexpr uint32_t CGO = MISC + 160;
constexpr uint32_t LBAR = MISC + 168, TL = MISC + 176;
constexpr uint32_t SMEM = TL + 5136;
#define NP2 10
constexpr int NZ = 16, NP = NZ + 80 + NP2, NQ = 512;
#define S15 8
#define SPLITS rt < RT_SPLIT ? 1 : rt < 11 ? 2 : rt < 13 ? 4 : rt < 15 ? 8 : S15
__host__ __device__ constexpr int split(int rt) { return SPLITS; }
__host__ __device__ constexpr int count_w(int rt) { return rt < 0 ? 0 : 4 * split(rt) + count_w(rt - 1); }
constexpr int NW = count_w(15);
__host__ __device__ constexpr int first_slice(int rt) { return rt <= RT_SPLIT ? 0 : first_slice(rt - 1) + split(rt - 1); }
static_assert(first_slice(16) <= NSL, "slice buffer");
DEVI int slice_of(int rt) {
  constexpr int f9 = first_slice(9), f10 = first_slice(10), f11 = first_slice(11), f12 = first_slice(12), f13 = first_slice(13), f14 = first_slice(14), f15 = first_slice(15);
  return rt < 9 ? 0 : rt == 9 ? f9 : rt == 10 ? f10 : rt == 11 ? f11 : rt == 12 ? f12 : rt == 13 ? f13 : rt == 14 ? f14 : f15;
}
static_assert(RT_SPLIT >= 8, "slice_of");
enum { T_Q, T_W, T_P, T_END, T_G, T_F };
#define RG0 13
#define RG1 13
#define BKVZ (CTAIL ? 12 : 14)
#define PFB 0
#define WLD 2
#define OKEEP 13
#define OPF 0
#define SENT 1
#define FLATE 10
#define WGRID 0
#define PFRONT 0
#define PTAIL 0
#define WPRE 0
#define PFF (CTAIL ? 12 : 14)
#define PFACC 0
#define P2LATE 0
#define LAGK0 16
#define LAGK1 16
#define DEFW0 13
#define DEFW1 13
#define NWE0 0
#define NWE1 0
#define SLATE0 1
#define SLATE1 1
#define SLATE 1
#define FLAG 3
#define FWARM 0
#define SLEV 1
#define SLC 1
#define LFAST 1
#define SCOUT0 13
#define SCOUT1 13
#define NSCOUT 0
#define FVOL 1
#define FXT 10
#define FCGO 0
#define P1M 1
#define TMPF 1
#define ZPRE 1
#define CLQ 8
#define CLW 3
struct Task { int type, rt, a, b; };
DEVI int wtasks(int rt) { return 4 * split(rt); }
DEVI int lsplit(int rt) { return 31 - __clz(split(rt)); }
DEVI Task decode(int id) { return {id >> 24, (id >> 16) & 255, id & 255, (id >> 8) & 255}; }
struct __align__(16) TaskList { int n, tail0, late0, pad; uint32_t t[1280]; };
constexpr void add_w(TaskList& l, int rt, int i0 = 0, int i1 = 64) {
  for (int b = 0; b < split(rt); b++) for (int a = 0; a < 4; a++) if (b * 4 + a >= i0 && b * 4 + a < i1) l.t[l.n++] = (T_W << 24) | (rt << 16) | (b << 8) | a;
}
constexpr void add_f(TaskList& l, int rt, int i0 = 0, int i1 = 64) {
  if (rt >= 0 && split(rt) > 1) for (int a = 0; a < 4; a++) for (int b = 0; b < 128 / FROWS; b++)
    if (a * (128 / FROWS) + b >= i0 && a * (128 / FROWS) + b < i1) l.t[l.n++] = (T_F << 24) | (rt << 16) | (b << 8) | a;
}
#define FLATE1 FLATE
#define FLAG1 FLAG
constexpr TaskList make_list(int layer) {
  TaskList l = {};
  const int rg = layer == 0 ? RG0 : RG1, lagk = layer == 0 ? LAGK0 : LAGK1, defw = layer == 0 ? DEFW0 : DEFW1, nwe = layer == 0 ? NWE0 : NWE1;
  if (layer == 0) for (int i = NZ; i < (P2LATE ? NZ + 80 : NP) - PTAIL && i < NZ + PFRONT; i++) l.t[l.n++] = (T_P << 24) | i;
  for (int rt = 15; rt >= rg; rt--) for (int h = 0; h < NH; h++) l.t[l.n++] = (T_G << 24) | (rt << 16) | h;
  if (layer == 0) for (int i = NZ + PFRONT; i < (P2LATE ? NZ + 80 : NP) - PTAIL; i++) l.t[l.n++] = (T_P << 24) | i;
  for (int i = 0; i < NZ; i++) l.t[l.n++] = (T_P << 24) | i;
  if (layer == 0 && P2LATE) for (int i = NZ + 80; i < NP; i++) l.t[l.n++] = (T_P << 24) | i;
  for (int rt = 0; rt < 16; rt++) {
    if (rt == 15) l.tail0 = l.n;
    for (int h = 0; h < NH; h++) l.t[l.n++] = (T_Q << 24) | (rt << 16) | ((rt >= rg) << 8) | h;
    if (rt > 0 && rt - 1 < lagk && rt - 1 < defw) add_w(l, rt - 1);
    if (rt >= lagk && rt < defw) add_w(l, rt);
    if (rt == 14 && defw < 14) add_w(l, defw, 0, nwe);
    if (rt == (layer ? SCOUT1 : SCOUT0)) for (int i = 0; i < NSCOUT; i++) l.t[l.n++] = (T_END << 24) | 1;
    if (FWARM && rt - FLAG + 1 == RT_SPLIT) add_f(l, RT_SPLIT, 0, 1);
    const int flag = layer ? FLAG1 : FLAG;
    if (rt - flag < (layer ? FLATE1 : FLATE)) add_f(l, rt - flag, FWARM && rt - flag == RT_SPLIT ? 1 : 0);
  }
  if (layer == 0) for (int i = NP - PTAIL; i < NP; i++) l.t[l.n++] = (T_P << 24) | i;
  if (CTAIL) {
    l.late0 = 1 << 20;
    for (int rt = layer ? FLATE1 : FLATE; rt < tl::RT0; rt++) add_f(l, rt);
    return l;
  }
  constexpr int W15E = 4 * S15 - 32;
  if (SLATE) add_w(l, 15, 0, W15E);
  if (SLATE && (layer ? SLATE1 : SLATE0) == 2) {
    l.late0 = l.n;
    add_w(l, 14); add_w(l, 15, W15E); add_f(l, 10); add_f(l, 11);
    for (int rt = 12; rt < 16; rt++) add_f(l, rt);
    return l;
  } else if (SLATE) {
    l.late0 = l.n;
    add_w(l, 13); add_w(l, 14); add_w(l, 15, W15E);
  } else {
    for (int rt = defw; rt < 16; rt++) add_w(l, rt, rt == defw && defw < 14 ? nwe : 0);
  }
  for (int rt = FLATE; rt < 16; rt++) add_f(l, rt);
  return l;
}
__device__ const TaskList d_tasks[2] = {make_list(0), make_list(1)};
__host__ __device__ constexpr uint32_t first_task(int layer, int b) {
  if (layer == 0 && PTAIL < NP - NZ) { if (b < PFRONT) return (T_P << 24) | (NZ + b); b -= PFRONT; }
  return (T_G << 24) | ((15 - (b >> 5)) << 16) | (b & 31);
}
constexpr int NLATE = SLATE && !CTAIL ? 96 : 0;
static_assert(CTAIL || !BFL, "flags");
static_assert(!CTAIL || (first_slice(tl::RT0) == tl::SL0 && DEFW0 == tl::RT0 && DEFW1 == tl::RT0 && S15 == 8 && !WGRID && BSL && SLC && LASTG), "tail of the recurrence kernel");
__host__ __device__ constexpr uint32_t late_task(int layer, int i) {
  if ((layer ? SLATE1 : SLATE0) == 2) return i < 64 ? (T_W << 24) | ((14 + (i >> 5)) << 16) | ((((i & 31) >> 2) + (i >> 5) * (S15 - 8)) << 8) | (i & 3)
                                                    : (T_F << 24) | ((6 + (i >> 4)) << 16) | ((i & 3) << 8) | ((i & 15) >> 2);
  return (T_W << 24) | ((13 + (i >> 5)) << 16) | ((((i & 31) >> 2) + (i >> 6) * (S15 - 8)) << 8) | (i & 3);
}
constexpr bool check_first() {
  for (int layer = 0; layer < 2; layer++) {
    const TaskList l = make_list(layer);
    for (int b = 0; b < 64; b++) if (l.t[b] != first_task(layer, b)) return false;
    for (int b = 0; b < NLATE; b++) if (l.t[l.late0 + b] != late_task(layer, b)) return false;
  }
  return true;
}
static_assert(check_first(), "first_task does not match the list");
}

#define WQP 0
#define WQP_D 0
#define PFR 0
#define PFR1 PFR
#define PFFL 0
#define FSB4 1
#define XKEEP 16
#define WEF 1
#define WTR 1
DEVI void pass_stage(uint32_t sb, uint32_t it, int lane) {
  mbar_wait_long(sb + wk::FULL + (it % wk::NST) * 8, (it / wk::NST) & 1);
  if (lane == 0) mbar_arrive(sb + wk::EMPTY + (it % wk::NST) * 8);
}
#define AT(i, x)
template <int NT>
DEVI void attend(uint32_t sb, const uint32_t (&q)[48], int cw, int w, int lane, uint32_t itk, uint32_t itv, uint32_t mid, uint32_t nd) {
  using namespace wk;
  const int g = lane >> 2, t = lane & 3;
  AT(0, q[0]);
  float sc[NT][4];
#pragma unroll
  for (int i = 0; i < NT * 4; i++) sc[i >> 2][i & 3] = 0.f;
  const uint32_t ka = sb + (itk % NST) * STAGE + (w >> 1) * 15360 + lane * 80;
#pragma unroll
  for (int k2 = 0; k2 < 6; k2++) {
    uint32_t b[NT][4];
#pragma unroll
    for (int n = 0; n < NT; n++) ldsm4t(b[n], ka + k2 * 2560 + n * 16);
#pragma unroll
    for (int n = 0; n < NT; n++) mma16816(sc[n], &q[k2 * 8], b[n][0], b[n][1]);
#pragma unroll
    for (int n = 0; n < NT; n++) mma16816(sc[n], &q[k2 * 8 + 4], b[n][2], b[n][3]);
  }
  AT(1, __float_as_uint(sc[NT - 1][0]) ^ __float_as_uint(sc[0][0]));
  __syncwarp();
  if (lane == 0) mbar_arrive(sb + EMPTY + (itk % NST) * 8);
  const float cs = 0.07216878364870322f * 1.4426950408889634f;
  const int r0 = NMEM + (NT == 5 ? 16 : 0) + g;
  float m0 = -INFINITY, m1 = -INFINITY;
#pragma unroll
  for (int n = 0; n < NT; n++)
#pragma unroll
    for (int e = 0; e < 2; e++) {
      const int key = n * 8 + 2 * t + e;
      sc[n][e] = (n < NT - 2 || key <= r0) ? sc[n][e] * cs : -INFINITY; sc[n][2 + e] = (n < NT - 1 || key <= r0 + 8) ? sc[n][2 + e] * cs : -INFINITY;
      m0 = fmaxf(m0, sc[n][e]); m1 = fmaxf(m1, sc[n][2 + e]);
    }
  m0 = fmaxf(m0, __shfl_xor_sync(0xffffffffu, m0, 1)); m1 = fmaxf(m1, __shfl_xor_sync(0xffffffffu, m1, 1));
  m0 = fmaxf(m0, __shfl_xor_sync(0xffffffffu, m0, 2)); m1 = fmaxf(m1, __shfl_xor_sync(0xffffffffu, m1, 2));
  uint32_t P[2 * NT]; float s0 = 0.f, s1 = 0.f;
#pragma unroll
  for (int n = 0; n < NT; n++) {
    const float a = ex2(sc[n][0] - m0), b = ex2(sc[n][1] - m0), c = ex2(sc[n][2] - m1), e = ex2(sc[n][3] - m1);
    s0 += a + b; s1 += c + e; P[2 * n] = pack_bf16(a, b); P[2 * n + 1] = pack_bf16(c, e);
  }
  s0 += __shfl_xor_sync(0xffffffffu, s0, 1); s1 += __shfl_xor_sync(0xffffffffu, s1, 1);
  s0 += __shfl_xor_sync(0xffffffffu, s0, 2); s1 += __shfl_xor_sync(0xffffffffu, s1, 2);
  const float i0 = rcp(s0), i1 = rcp(s1);
  AT(2, __float_as_uint(i0) ^ __float_as_uint(i1));
  mbar_wait_long(sb + FREE + cw * 8, (nd & 1) ^ 1);
  AT(3, 0);
  if (mid != 0xFFFFFFFFu) pass_stage(sb, mid, lane);
  mbar_wait_long(sb + FULL + (itv % NST) * 8, (itv / NST) & 1);
  AT(4, 0);
  const uint32_t vb = sb + (itv % NST) * STAGE + (w >> 1) * 15360;
  const uint32_t va = vb + (lane & 7) * 80 + (lane >> 3) * 16, vc = vb + lane * 80 + 64;
  const uint32_t orow = w * 16 + (lane & 15), ob = sb + OST + cw * 24576 + orow * 128;
#pragma unroll
  for (int n8 = 0; n8 < 3; n8++) {
    uint32_t b[8][4], c[2][4];
    float o[8][4];
#pragma unroll
    for (int i = 0; i < 8; i++) { ldsm4(b[i], va + (n8 * 8 + i) * 640); o[i][0] = o[i][1] = o[i][2] = o[i][3] = 0.f; }
    if (NT == 5) { ldsm4(c[0], vc + n8 * 5120); ldsm4(c[1], vc + n8 * 5120 + 2560); }
#pragma unroll
    for (int i = 0; i < 8; i++) mma16816(o[i], &P[0], b[i][0], b[i][1]);
#pragma unroll
    for (int i = 0; i < 8; i++) { if (NT == 5) mma16816(o[i], &P[4], b[i][2], b[i][3]); else mma1688(o[i], P[4], P[5], b[i][2]); }
    if (NT == 5)
#pragma unroll
      for (int i = 0; i < 8; i++) mma1688(o[i], P[2 * NT - 2], P[2 * NT - 1], c[i >> 2][i & 3]);
#pragma unroll
    for (int i = 0; i < 4; i++)
      stsm4(ob + n8 * 8192 + (((i * 2 + (lane >> 4)) ^ (orow & 7)) << 4), pack_bf16(o[2 * i][0] * i0, o[2 * i][1] * i0), pack_bf16(o[2 * i][2] * i1, o[2 * i][3] * i1),
            pack_bf16(o[2 * i + 1][0] * i0, o[2 * i + 1][1] * i0), pack_bf16(o[2 * i + 1][2] * i1, o[2 * i + 1][3] * i1));
  }
  __syncwarp();
  AT(5, 0);
  if (lane == 0) mbar_arrive(sb + EMPTY + (itv % NST) * 8);
}

__global__ void __launch_bounds__(384, 1)
worker_kernel(int layer, Sync* sy, const bf16* __restrict__ xin, const bf16* __restrict__ wphi, const bf16* __restrict__ wo2,
              const __grid_constant__ CUtensorMap mx, const __grid_constant__ CUtensorMap mq, const __grid_constant__ CUtensorMap moa,
              const __grid_constant__ CUtensorMap mos, const __grid_constant__ CUtensorMap mwo, const __grid_constant__ CUtensorMap mxa,
              const __grid_constant__ CUtensorMap macc, const __grid_constant__ CUtensorMap mwb) {
  using namespace wk;
  extern __shared__ __align__(1024) uint8_t smraw[];
  const uint32_t sb = smem_u32(smraw);
  const int tid = threadIdx.x, lane = tid & 31;
  const int wg = __shfl_sync(0xffffffffu, tid >> 7, 0), w = __shfl_sync(0xffffffffu, (tid >> 5) & 3, 0);
  constexpr int WF = 0;
  if (!WLD) asm volatile("griddepcontrol.launch_dependents;");
  GT(1, 0);
  const int nstat = WGRID ? 0 : min(max((int)gridDim.x - (CTAIL ? 0 : 96), 0), 64);
  int idx0 = 0;
  const int nl = min((int)gridDim.x - nstat, NLATE);
  if (tid == 96 && (int)blockIdx.x >= nstat + nl) idx0 = atomicAdd(&sy->head, 1);
  int id0 = -1;
  uint32_t flag0 = 0;
  if (LFAST && tid == 0 && (int)blockIdx.x >= nstat && (int)blockIdx.x < nstat + nl) {
    if (TMPF) { asm volatile("prefetch.tensormap [%0];" :: "l"(&mwo) : "memory"); asm volatile("prefetch.tensormap [%0];" :: "l"(&moa) : "memory"); }
    id0 = late_task(layer, blockIdx.x - nstat);
    flag0 = ld_acquire(&sy->o[(id0 >> 16 & 255) * 16 + (id0 >> 8 & 255)]);
  }
  if (tid == 0) {
    sts64(sb + FIN, 0, 0);
    for (int i = 0; i < NST; i++) { mbar_init(sb + FULL + i * 8, 1); mbar_init(sb + EMPTY + i * 8, 8); }
    for (int i = 0; i < 2; i++) { mbar_init(sb + TFULL + i * 8, 1); mbar_init(sb + TEMPTY + i * 8, 9); mbar_init(sb + DONE + i * 8, 128); mbar_init(sb + FREE + i * 8, 1); }
    mbar_init(sb + CGO, 1); mbar_init(sb + LBAR, 1);
    asm volatile("fence.mbarrier_init.release.cluster;" ::: "memory");
    mbar_expect(sb + LBAR, sizeof(TaskList));
    bulk_load_plain(sb + TL, &d_tasks[layer], sizeof(TaskList), sb + LBAR);
  }
  if (WQP && layer && tid == 64 && blockIdx.x >= 4) {
    if (WQP_D) __nanosleep(WQP_D);
    for (int i = blockIdx.x - 4; i < WQP * 32; i += gridDim.x - 4) tma3d_prefetch(&mq, 0, i / 32 * 64, i % 32 * 3);
  }
  uint32_t early = 0;
  if (wg == 0) {
    asm volatile("setmaxnreg.dec.sync.aligned.u32 40;");
    if (LFAST && w == 0) bar_arrive(0, 384); else bar_sync(0, 384);
    if (tid == 96) {
      uint32_t nres = 0;
      bool tail = false;
      int ntask = 0, tail0 = 0, late0 = 0;
      for (uint32_t nt = 0;; nt++) {
        mbar_wait_long(sb + TEMPTY + (nt & 1) * 8, ((nt >> 1) & 1) ^ 1);
        if (nt) mbar_wait_long(sb + CGO, (nt - 1) & 1);
        if (tail) for (int i = 0; i < 4000000 && (lds32(sb + FIN) < nres || lds32(sb + FIN + 4) < nres); i++) {}
        int id;
        if (nt == 0 && (int)blockIdx.x < nstat) id = first_task(layer, blockIdx.x);
        else if (nt == 0 && (int)blockIdx.x < nstat + nl) { id = late_task(layer, blockIdx.x - nstat); tail = true; }
        else {
          const int idx = nstat + (nt ? atomicAdd(&sy->head, 1) : idx0);
          if (!ntask) { mbar_wait_long(sb + LBAR, 0); ntask = lds32(sb + TL); tail0 = lds32(sb + TL + 4); late0 = lds32(sb + TL + 8); }
          const int e = !SLATE || idx < late0 ? idx : idx + nl;
          id = e < ntask ? lds32(sb + TL + 16 + e * 4) : T_END << 24;
          tail = idx >= tail0;
        }
        sts32(sb + TASK + (nt & 1) * 4, id);
        mbar_arrive(sb + TFULL + (nt & 1) * 8);
        if (WLD == 1 && (id >> 24) == T_F && (id >> 16 & 255) >= FLATE) asm volatile("griddepcontrol.launch_dependents;");
        if ((id >> 24) == T_END) {
          if (WLD) asm volatile("griddepcontrol.launch_dependents;");
          early = id & 1;
          break;
        }
        nres += (id >> 24) < T_P;
      }
    } else if (tid == 0) {
      uint32_t it = 0;
      bool have_xn = false, have_zero = false;
      if (TMPF && !LFAST && (int)blockIdx.x >= nstat) {
        asm volatile("prefetch.tensormap [%0];" :: "l"(&mwo) : "memory");
        asm volatile("prefetch.tensormap [%0];" :: "l"(&moa) : "memory");
      }
      if (!BSL && ZPRE && (int)blockIdx.x >= nstat) have_zero = ld_acquire(&sy->zeroed) >= NZ;
      for (uint32_t nt = 0;; nt++) {
        int id = id0;
        if (nt || id0 < 0) {
          mbar_wait_long(sb + TFULL + (nt & 1) * 8, (nt >> 1) & 1);
          id = lds32(sb + TASK + (nt & 1) * 4);
        }
        const Task tk = decode(id);
        if (nt == 0) WS(1, tk.type);
        mbar_arrive(sb + TEMPTY + (nt & 1) * 8);
        if (tk.type == T_END) {
          if (PFB && blockIdx.x < 128) {
            asm volatile("cp.async.bulk.prefetch.L2.global [%0], 19200;" :: "l"((const char*)g_wb1 + blockIdx.x * 19200) : "memory");
            asm volatile("cp.async.bulk.prefetch.L2.global [%0], 6400;" :: "l"((const char*)g_wb2 + blockIdx.x * 6400) : "memory");
          }
          early = id & 1;
          GT(1, 1); break;
        }
        if (PFR && tk.type == T_Q && tk.rt == (layer ? PFR1 : PFR)) {
          for (int i = 0; i < 5; i++) asm volatile("cp.async.bulk.prefetch.L2.global [%0], 15360;" :: "l"((const char*)g_wb1 + (tk.a * 5 + i) * 15360) : "memory");
          for (int i = 0; i < 2; i++) asm volatile("cp.async.bulk.prefetch.L2.global [%0], 12800;" :: "l"((const char*)g_wb2 + (tk.a * 2 + i) * 12800) : "memory");
          asm volatile("cp.async.bulk.prefetch.L2.global [%0], 2400;" :: "l"((const char*)g_cs + tk.a * 2400) : "memory");
        }
        if (tk.type == T_Q && tk.b) {
          for (int c = 0; c < 4; c++, it++) {
            const uint32_t st = it % NST, a = sb + st * STAGE, fb = sb + FULL + st * 8;
            if (!(c & 1)) {
              wait_count_t(&sy->kv[(tk.rt * 4 + c + 1) * NH + tk.a], 3, tk.rt == 15 && c == 2); fence_flag_to_bulk();
              if (LASTG && tk.rt == 15 && c == 2) asm volatile("fence.proxy.async.global;" ::: "memory");
            }
            if (OPF && c == 0 && tk.rt == 15)
              for (int n = 0; n < OPF; n++) tma3d_prefetch(&mos, 0, 13 * 128 + n * 64, tk.a * 3);
            if (c == 2) mbar_arrive(sb + CGO);
            mbar_wait_long(sb + EMPTY + st * 8, ((it / NST) & 1) ^ 1);
            mbar_expect(fb, 30720);
            const bf16* src = g_kv + ((size_t)((tk.rt * 4 + (c & 2)) * NH + tk.a) * 2 + (c & 1)) * DH * NKEY;
            bulk_load(a, src, 15360, fb);
            bulk_load(a + 15360, src + (size_t)NH * 2 * DH * NKEY, 15360, fb);
          }
        } else if (tk.type == T_G) {
          if (!have_xn) { spin_count(&sy->pro[0], NPRO); asm volatile("fence.proxy.async;" ::: "memory"); have_xn = true; }
          for (int c = 0; c < 10; c++, it++) {
            const uint32_t st = it % NST, a = sb + st * STAGE, fb = sb + FULL + st * 8;
            if (c == CLQ) mbar_arrive(sb + CGO);
            mbar_wait_long(sb + EMPTY + st * 8, ((it / NST) & 1) ^ 1);
            mbar_expect(fb, 40960);
            tma2d_h<(WEF & 2) != 0>(a, &mx, c * 64, tk.rt * 128, fb);
            tma3d(a + 16384, &mq, 0, c * 64, tk.a * 3, fb);
          }
        } else if (tk.type == T_Q) {
          if (!have_xn) { spin_count(&sy->pro[0], NPRO); asm volatile("fence.proxy.async;" ::: "memory"); have_xn = true; }
          bool have_kv = false;
          for (int c = (WF & 2) ? 8 : 0; c < 14; c++, it++) {
            const uint32_t st = it % NST, a = sb + st * STAGE, fb = sb + FULL + st * 8;
            if (c == CLQ) mbar_arrive(sb + CGO);
            if (c >= 4 && !have_kv) {
              const uint32_t* fl = &sy->kv[(tk.rt * 4 + 3) * NH + tk.a];
              if (c == 10) wait_count(fl, 3);
              if (c == 10 || ld_acquire(fl) >= 3) { have_kv = true; fence_flag_to_bulk(); }
            }
            mbar_wait_long(sb + EMPTY + st * 8, ((it / NST) & 1) ^ 1);
            if (c < 10) {
              mbar_expect(fb, 40960);
              tma2d_h<(WEF & 2) != 0>(a, &mx, c * 64, tk.rt * 128, fb);
              tma3d(a + 16384, &mq, 0, c * 64, tk.a * 3, fb);
            } else {
              mbar_expect(fb, 30720);
              const bf16* src = g_kv + ((size_t)((tk.rt * 4 + (c & 1) * 2) * NH + tk.a) * 2 + ((c - 10) >> 1)) * DH * NKEY;
              bulk_load(a, src, 15360, fb);
              bulk_load(a + 15360, src + (size_t)NH * 2 * DH * NKEY, 15360, fb);
            }
          }
        } else if (tk.type == T_W) {
          const int nc = (WF & 1) ? 2 : 96 >> lsplit(tk.rt), c0 = tk.b * nc;
          if (!BSL && tk.rt >= RT_SPLIT && !have_zero) { wait_count(&sy->zeroed, NZ); have_zero = true; }
          const int npre = WPRE ? min(nc, (int)NST) : 0;
          for (int c = 0; c < npre; c++) {
            const uint32_t st = (it + c) % NST, fb = sb + FULL + st * 8;
            mbar_wait_long(sb + EMPTY + st * 8, (((it + c) / NST) & 1) ^ 1);
            mbar_expect(fb, 36864);
            tma3d(sb + st * STAGE + 16384, &mwo, 0, (c0 + c) * 64, tk.a * 5, fb);
          }
          if (nt || flag0 < (64u >> lsplit(tk.rt))) wait_count_t(&sy->o[tk.rt * 16 + tk.b], 64 >> lsplit(tk.rt), tk.rt == 15);
          if (tk.rt >= 13) XT((tk.rt - 13) * 32 + (tk.b >> (tk.rt == 15 && S15 == 16) & 7) * 4 + tk.a, 0);
          fence_flag_to_bulk();
          if (tk.rt >= 13) XT((tk.rt - 13) * 32 + (tk.b >> (tk.rt == 15 && S15 == 16) & 7) * 4 + tk.a, 1);
          for (int c = 0; c < nc; c++, it++) {
            const uint32_t st = it % NST, a = sb + st * STAGE, fb = sb + FULL + st * 8;
            if (c == max(nc - CLW, 0)) mbar_arrive(sb + CGO);
            if (c >= npre) {
              mbar_wait_long(sb + EMPTY + st * 8, ((it / NST) & 1) ^ 1);
              mbar_expect(fb, 36864);
              tma3d(a + 16384, &mwo, 0, (c0 + c) * 64, tk.a * 5, fb);
            }
            tma2d_h<(WEF & 1) != 0>(a, &moa, (c0 + c) * 64, tk.rt * 128, fb);
          }
        } else if (tk.type == T_P && tk.a >= NZ && tk.a < NZ + 80) {
          const uint32_t st = it % NST, a = sb + st * STAGE, fb = sb + FULL + st * 8;
          const int gq = (tk.a - NZ) / 10, k0 = (tk.a - NZ) % 10 * 64;
          mbar_arrive(sb + CGO);
          mbar_wait_long(sb + EMPTY + st * 8, ((it / NST) & 1) ^ 1);
          mbar_expect(fb, 30720 + 3200);
          for (int p = 0; p < 3; p++) tma2d_h<(PEF & 1) != 0>(a + p * 10240, &mwb, p * DM + gq * 80, k0, fb);
          bulk_load_plain(a + 30720, wphi + gq * 4 * BDH * BDH, 3200, fb);
          it++;
        } else if (tk.type != T_F) mbar_arrive(sb + CGO);
      }
    } else if (tid == 32 || tid == 64) {
      const int cw = (tid >> 5) - 1;
      for (uint32_t n = 0;; n++) {
        mbar_wait_long(sb + DONE + cw * 8, n & 1);
        const Task tk = decode(lds32(sb + DTASK + cw * 4));
        if (tk.type == T_END) {
          if (BFL) red_release(&sy->pad1[0]);
          early = tk.a; break;
        }
        if (tk.type == T_W && tk.rt == FXT) XT(128 + (tk.b & 1) * 4 + tk.a, cw);
        if (tk.type == T_Q && tk.rt >= OKEEP)
          asm volatile("cp.async.bulk.tensor.3d.global.shared::cta.bulk_group [%0, {%2, %3, %4}], [%1];" :: "l"(&mos), "r"(sb + OST + cw * 24576), "r"(0), "r"(tk.rt * 128 + cw * 64), "r"(tk.a * 3) : "memory");
        else if (tk.type == T_Q) tma3d_store(&mos, sb + OST + cw * 24576, 0, tk.rt * 128 + cw * 64, tk.a * 3);
        else if (split(tk.rt) == 1 && tk.rt >= XKEEP)
          asm volatile("cp.async.bulk.tensor.3d.global.shared::cta.bulk_group [%0, {%2, %3, %4}], [%1];" :: "l"(&mxa), "r"(sb + OST + cw * 24576), "r"(0), "r"(tk.rt * 128 + cw * 64), "r"(tk.a * 5) : "memory");
        else if (split(tk.rt) == 1) tma3d_store(&mxa, sb + OST + cw * 24576, 0, tk.rt * 128 + cw * 64, tk.a * 5);
        else if (BSL && SLC) {
          bf16* dst = g_sl + (size_t)(((slice_of(tk.rt) + tk.b) * 4 + tk.a) * 2 + cw) * 10240;
          if (SLEV) bulk_store(dst, sb + OST + cw * 24576, 20480);
          else asm volatile("cp.async.bulk.global.shared::cta.bulk_group [%0], [%1], 20480;" :: "l"(dst), "r"(sb + OST + cw * 24576) : "memory");
        }
        else if (BSL) tma3d_store(&macc, sb + OST + cw * 24576, 0, (slice_of(tk.rt) + tk.b) * 128 + cw * 64, tk.a * 5);
        else {
          const uint32_t slot = lds32(sb + DSLOT + cw * 4);
            asm volatile("cp.reduce.async.bulk.tensor.3d.global.shared::cta.add.tile.bulk_group [%0, {%2, %3, %4}], [%1];"
                         :: "l"(&macc), "r"(sb + slot * STAGE), "r"(0), "r"(layer * ACC_ROWS + (tk.rt - RT_SPLIT) * 128 + cw * 64), "r"(tk.a * 5) : "memory");
          asm volatile("cp.async.bulk.commit_group; cp.async.bulk.wait_group.read 0;" ::: "memory");
          asm volatile("mbarrier.arrive.shared::cta.b64 _, [%0], 8;" :: "r"(sb + EMPTY + slot * 8) : "memory");
        }
        asm volatile("cp.async.bulk.commit_group; cp.async.bulk.wait_group.read 0;" ::: "memory");
        mbar_arrive(sb + FREE + cw * 8);
        if (tk.type == T_Q && tk.rt == 15) XT(96 + tk.a, cw);
        asm volatile("cp.async.bulk.wait_group 0;" ::: "memory");
        if (tk.type == T_Q && tk.rt == 15) XT(96 + tk.a, 2 + cw);
        if (tk.type == T_W && tk.rt >= 13) XT((tk.rt - 13) * 32 + (tk.b >> (tk.rt == 15 && S15 == 16) & 7) * 4 + tk.a, 2 + cw);
        if (tk.type == T_W && tk.rt == FXT) XT(128 + (tk.b & 1) * 4 + tk.a, 2 + cw);
        if (tk.type == T_Q) {
          const int sl = tk.rt * 16 + (tk.a >> (5 - lsplit(tk.rt))) + (CTAIL && tk.rt == 15 ? cw * 8 : 0);
          publish_bulk<WFEN>(&sy->o[sl]);
        } else if (split(tk.rt) > 1) {
          publish_bulk<WFEN>(&sy->wcnt[(tk.rt * 4 + tk.a) * 2 + cw]);
        }
        sts32(sb + FIN + cw * 4, n + 1);
      }
    }
  } else {
    asm volatile("setmaxnreg.inc.sync.aligned.u32 232;");
    bar_sync(0, 384);
    const int cw = wg - 1, g = lane >> 2, t = lane & 3, ct = tid - 128;
    if (WLN >> layer & 1) {
      if (layer) { if (ct == 0) spin_count(&sy->pro[1], 1); bar_sync(3, 256); }
      uint2 u[2][10];
      const bf16* x = xin + (ct >> 5) * 2 * DM + lane * 4;
      int un = blockIdx.x, n = 0;
#pragma unroll
      for (int i = 0; i < 10; i++) u[1][i] = ld64_h<(PEF & 8) != 0>(x + un * 16 * DM + i * 128);
#pragma unroll 1
      for (; un < 128; un += gridDim.x, n++) {
#pragma unroll
        for (int i = 0; i < 10; i++) { u[0][i] = u[1][i]; u[1][i] = ld64_h<(PEF & 8) != 0>(x + min(un + (int)gridDim.x, 127) * 16 * DM + i * 128); }
#pragma unroll
        for (int rr = 0; rr < 2; rr++) {
          float v[20];
#pragma unroll
          for (int i = 0; i < 5; i++) {
            const uint2 e = u[0][rr * 5 + i];
            v[4 * i] = __uint_as_float(e.x << 16); v[4 * i + 1] = __uint_as_float(e.x & 0xFFFF0000u);
            v[4 * i + 2] = __uint_as_float(e.y << 16); v[4 * i + 3] = __uint_as_float(e.y & 0xFFFF0000u);
          }
          ln_row(v, g_xn + (un * 16 + (ct >> 5) * 2 + rr) * DM, lane);
        }
        if (un < 4) {
          bar_sync(3, 256);
          if (ct == 0) red_release(&sy->pro[2]);
          __syncwarp();
        }
      }
      for (int i = blockIdx.x * 256 + ct; i < (NSEG - 1) * 24 * 32; i += gridDim.x * 256) ((uint4*)g_ar)[(i >> 5) * 64 + (i & 31)] = make_uint4(0, 0, 0, 0);
      bar_sync(3, 256);
      if (ct == 0) asm volatile("red.release.gpu.global.add.u32 [%0], %1;" :: "l"(&sy->pro[0]), "r"(n) : "memory");
      __syncwarp();
    }
    uint32_t it = 0, nd = 0;
    for (uint32_t nt = 0;; nt++) {
      mbar_wait_long(sb + TFULL + (nt & 1) * 8, (nt >> 1) & 1);
      const int tid_ = __shfl_sync(0xffffffffu, (int)lds32(sb + TASK + (nt & 1) * 4), 0);
      const Task tk = decode(tid_);
      if (nt == 0 && ct == 0) WS(2, tid_);
      __syncwarp();
      if (lane == 0) mbar_arrive(sb + TEMPTY + (nt & 1) * 8);
      if (tk.type == T_END) {
        mbar_wait_long(sb + FREE + cw * 8, (nd & 1) ^ 1);
        if (ct == cw * 128) sts32(sb + DTASK + cw * 4, tid_);
        mbar_arrive(sb + DONE + cw * 8);
        early = tid_ & 1;
        break;
      }
      if (tk.type == T_Q || tk.type == T_G) {
        if (PFACC && tk.type == T_Q && tk.rt >= RT_SPLIT && ct == 32)
          asm volatile("cp.async.bulk.prefetch.L2.global [%0], 10240;" :: "l"(g_acc + (size_t)(layer * ACC_ROWS + (tk.rt - RT_SPLIT) * 128 + tk.a * 4) * DM) : "memory");
        uint32_t q[48];
        uint4* qf = g_qf + (size_t)(tk.rt * NH + tk.a) * 12 * 256 + ct;
        if (tk.type == T_Q && tk.b) {
          if ((ct & 127) == 0) wait_count(&sy->gst[tk.rt * NH + tk.a], 2);
          bar_sync(1 + cw, 128);
#pragma unroll
          for (int i = 0; i < 12; i++) {
            if (LEF & 8) ldcg128_h<true>(*(uint32_t(*)[4])&q[4 * i], qf + i * 256);
            else { const uint4 u = __ldcg(qf + i * 256); q[4 * i] = u.x; q[4 * i + 1] = u.y; q[4 * i + 2] = u.z; q[4 * i + 3] = u.w; }
          }
        } else {
          float d[96];
#pragma unroll
          for (int i = 0; i < 96; i++) d[i] = 0.f;
          for (int c = 0; c < ((WF & 2) ? 2 : 10); c++, it++) {
            const uint32_t st = it % NST, a = sb + st * STAGE;
            mbar_wait_long(sb + FULL + st * 8, (it / NST) & 1);
            if (c == 0) TM(0);
            const uint64_t da = mkdesc(a + cw * 8192, 16, 1024, 1), db = mkdesc(a + 16384, 8192, 1024, 1);
            wg_fence();
#pragma unroll
            for (int k = 0; k < 4; k++) wgmma_n192_nt(d, da + k * 2, db + k * 128, c | k);
            wg_commit();
            if (c > 0) { wg_wait<1>(); if (lane == 0) mbar_arrive(sb + EMPTY + ((it - 1) % NST) * 8); }
          }
          wg_wait<0>();
          if (lane == 0) mbar_arrive(sb + EMPTY + ((it - 1) % NST) * 8);
#pragma unroll
          for (int i = 0; i < 48; i++) q[i] = pack_bf16(d[2 * i], d[2 * i + 1]);
        }
        TM(1);
        if (tk.type == T_G) {
#pragma unroll
          for (int i = 0; i < 12; i++) {
            if (LEF & 16) asm volatile("st.global.cg.L2::cache_hint.v4.u32 [%0], {%1,%2,%3,%4}, %5;" :: "l"(qf + i * 256), "r"(q[4 * i]), "r"(q[4 * i + 1]), "r"(q[4 * i + 2]), "r"(q[4 * i + 3]), "l"(stream_policy()) : "memory");
            else __stcg(qf + i * 256, make_uint4(q[4 * i], q[4 * i + 1], q[4 * i + 2], q[4 * i + 3]));
          }
          bar_sync(1 + cw, 128);
          if ((ct & 127) == 0) red_release(&sy->gst[tk.rt * NH + tk.a]);
          __syncwarp();
          TM(2); TM(3);
          continue;
        }
        const uint32_t itk = tk.b ? it + 2 * cw : it + cw, itv = tk.b ? itk + 1 : it + 2 + cw;
        if (cw == 1) { pass_stage(sb, it, lane); if (tk.b) pass_stage(sb, it + 1, lane); }
        mbar_wait_long(sb + FULL + (itk % NST) * 8, (itk / NST) & 1);
        TM(2);
        const uint32_t mid = tk.b ? 0xFFFFFFFFu : itk + 1;
        if (w & 1) attend<5>(sb, q, cw, w, lane, itk, itv, mid, nd); else attend<3>(sb, q, cw, w, lane, itk, itv, mid, nd);
        if (!CTAIL && cw == 0) { if (tk.b) pass_stage(sb, it + 2, lane); pass_stage(sb, it + 3, lane); }
        if (ct == cw * 128) sts32(sb + DTASK + cw * 4, tid_);
        fence_async();
        mbar_arrive(sb + DONE + cw * 8);
        if (CTAIL && cw == 0) { if (tk.b) pass_stage(sb, it + 2, lane); pass_stage(sb, it + 3, lane); }
        it += 4;
        nd++;
        TM(3);
      } else if (tk.type == T_W) {
        float d[80];
#pragma unroll
        for (int i = 0; i < 80; i++) d[i] = 0.f;
        const int nc = (WF & 1) ? 2 : 96 >> lsplit(tk.rt);
        const int off = (tk.rt * 128 + cw * 64 + w * 16 + g) * DM + tk.a * 160 + 2 * t;
        const bool whole = BSL || split(tk.rt) == 1;
        uint32_t res[40];
        if (WTR) {
          const int ln = opq(lane);
          const bf16* x = xin + (tk.rt * 128 + cw * 64 + w * 16) * DM + tk.a * 160;
#pragma unroll
          for (int i = 0; i < 40; i++) res[i] = 0;
          if (split(tk.rt) == 1)
#pragma unroll
            for (int i = 0; i < 10; i++)
              ldcg128_h<(LEF & 4) != 0>(*(uint32_t(*)[4])&res[4 * i], i < 8 ? x + (2 * i + (ln >> 4)) * DM + (ln & 15) * 8 : x + ((i - 8) * 8 + (ln >> 2)) * DM + 128 + (ln & 3) * 8);
        } else
#pragma unroll
        for (int i = 0; i < 40; i++) res[i] = split(tk.rt) == 1 ? *(const uint32_t*)(xin + off + (i >> 1) * 8 + (i & 1) * 8 * DM) : 0u;
        for (int c = 0; c < nc; c++, it++) {
          const uint32_t st = it % NST, a = sb + st * STAGE;
          mbar_wait_long(sb + FULL + st * 8, (it / NST) & 1);
          if (c == 0) TM(0);
          const uint64_t da = mkdesc(a + cw * 8192, 16, 1024, 1), db = mkdesc(a + 16384, 4096, 512, 2);
          wg_fence();
#pragma unroll
          for (int k = 0; k < 4; k++) wgmma_n160_nt(d, da + k * 2, db + k * 64, c | k);
          wg_commit();
          if (c > 0) { wg_wait<1>(); if (lane == 0 && (whole || c < nc - 1)) mbar_arrive(sb + EMPTY + ((it - 1) % NST) * 8); }
        }
        wg_wait<0>();
        if (lane == 0 && whole) mbar_arrive(sb + EMPTY + ((it - 1) % NST) * 8);
        TM(1);
        mbar_wait_long(sb + FREE + cw * 8, (nd & 1) ^ 1);
        TM(2);
        if (whole) {
          const uint32_t orow = w * 16 + (lane & 15), ob = sb + OST + cw * 24576 + orow * 64;
          float s1[2] = {0.f, 0.f}, s2[2] = {0.f, 0.f};
          if (WTR && split(tk.rt) == 1) {
            const uint32_t ln = opq(lane), tb = sb + OST + cw * 24576 + w * 1024;
#pragma unroll
            for (int i = 0; i < 10; i++)
              sts128(i < 8 ? tb + (2 * i + (ln >> 4)) * 64 + (ln >> 2 & 3) * 4096 + (((ln & 3) ^ (i & 3)) << 4) : tb + ((i - 8) * 8 + (ln >> 2)) * 64 + 16384 + (((ln & 3) ^ (ln >> 3)) << 4),
                     res[4 * i], res[4 * i + 1], res[4 * i + 2], res[4 * i + 3]);
            __syncwarp();
#pragma unroll
            for (int i2 = 0; i2 < 10; i2++) ldsm4(*(uint32_t(*)[4])&res[4 * i2], ob + (i2 >> 1) * 4096 + ((((i2 & 1) * 2 + (lane >> 4)) ^ ((orow >> 1) & 3)) << 4));
            __syncwarp();
          }
#pragma unroll
          for (int i2 = 0; i2 < 10; i2++) {
            uint32_t u[4];
#pragma unroll
            for (int e = 0; e < 4; e++) {
              const int i = 2 * i2 + (e >> 1);
              const uint32_t x = res[4 * i2 + e];
              u[e] = pack_bf16(d[4 * i + (e & 1) * 2] + __uint_as_float(x << 16), d[4 * i + (e & 1) * 2 + 1] + __uint_as_float(x & 0xFFFF0000u));
              const float lo = __uint_as_float(u[e] << 16), hi = __uint_as_float(u[e] & 0xFFFF0000u);
              s1[e & 1] += lo + hi; s2[e & 1] = fmaf(lo, lo, fmaf(hi, hi, s2[e & 1]));
            }
            stsm4(ob + (i2 >> 1) * 4096 + ((((i2 & 1) * 2 + (lane >> 4)) ^ ((orow >> 1) & 3)) << 4), u[0], u[1], u[2], u[3]);
          }
          fence_async();
          if (split(tk.rt) == 1)
#pragma unroll
          for (int e = 0; e < 2; e++) {
            s1[e] += __shfl_xor_sync(0xffffffffu, s1[e], 1); s2[e] += __shfl_xor_sync(0xffffffffu, s2[e], 1);
            s1[e] += __shfl_xor_sync(0xffffffffu, s1[e], 2); s2[e] += __shfl_xor_sync(0xffffffffu, s2[e], 2);
            if (t == 0) red_add2(&sy->rstat[tk.rt * 128 + cw * 64 + w * 16 + g + 8 * e], s1[e], s2[e]);
          }
        } else {
          bar_sync(3, 256);
          const uint32_t slot = (it - 2 + cw) % NST, a = sb + slot * STAGE + (w * 16 + g) * 128 + (t & 1) * 8;
#pragma unroll
          for (int i = 0; i < 20; i++) {
            const uint32_t o = a + (i >> 2) * 8192 + ((((i & 3) * 2 + (t >> 1)) ^ g) << 4);
            sts64(o, __float_as_uint(d[4 * i]), __float_as_uint(d[4 * i + 1])); sts64(o + 1024, __float_as_uint(d[4 * i + 2]), __float_as_uint(d[4 * i + 3]));
          }
          if (ct == cw * 128) sts32(sb + DSLOT + cw * 4, slot);
          fence_async();
        }
        if (ct == cw * 128) sts32(sb + DTASK + cw * 4, tid_);
        mbar_arrive(sb + DONE + cw * 8);
        nd++;
        TM(3);
      } else if (BSL && tk.type == T_F) {
        if (tk.rt == BKVZ && tk.b < 2) for (int i = ct; i < NH * BF * 6 / 8; i += 256) ((uint4*)g_bkv)[(tk.a * 2 + tk.b) * (NH * BF * 6 / 8) + i] = make_uint4(0, 0, 0, 0);
        if (PFF && !PFFL && tk.rt == PFF && tk.b < 2 && ct == 32) {
          const int q = tk.a * 2 + tk.b;
          for (int i = 0; i < 20; i++) asm volatile("cp.async.bulk.prefetch.L2.global [%0], 15360;" :: "l"((const char*)g_wb1 + (q * 20 + i) * 15360) : "memory");
          for (int i = 0; i < 8; i++) asm volatile("cp.async.bulk.prefetch.L2.global [%0], 12800;" :: "l"((const char*)g_wb2 + (q * 8 + i) * 12800) : "memory");
          asm volatile("cp.async.bulk.prefetch.L2.global [%0], 9600;" :: "l"((const char*)g_cs + q * 9600) : "memory");
        }
        constexpr int LPR = 256 / FROWS, NU = (20 + LPR - 1) / LPR;
        const int cq = opq(ct), rl = tk.b * FROWS + cq / LPR, q = cq % LPR, r = tk.rt * 128 + rl, c0 = tk.a * 160 + q * 8;
        if (ct == 0) { wait_count_t(&sy->wcnt[(tk.rt * 4 + tk.a) * 2 + tk.b * FROWS / 64], split(tk.rt), TIGHT == 1 && tk.rt >= 13); if (!FCGO) mbar_arrive(sb + CGO); }
        if (ct == 0 && tk.rt == FXT) XT(136 + tk.a * 4 + tk.b, 1);
        uint4 x[NU];
#pragma unroll
        for (int i = 0; i < NU; i++) x[i] = ldcg_if_h<(LEF & 4) != 0>(xin + r * DM + c0 + i * LPR * 8, i * LPR + q < 20);
        bar_sync(3, 256);
        float a[NU][8];
#pragma unroll
        for (int i = 0; i < NU; i++) {
          a[i][0] = __uint_as_float(x[i].x << 16); a[i][1] = __uint_as_float(x[i].x & 0xFFFF0000u); a[i][2] = __uint_as_float(x[i].y << 16); a[i][3] = __uint_as_float(x[i].y & 0xFFFF0000u);
          a[i][4] = __uint_as_float(x[i].z << 16); a[i][5] = __uint_as_float(x[i].z & 0xFFFF0000u); a[i][6] = __uint_as_float(x[i].w << 16); a[i][7] = __uint_as_float(x[i].w & 0xFFFF0000u);
        }
        float y[NU][8];
#pragma unroll
        for (int i = 0; i < NU * 8; i++) y[i >> 3][i & 7] = 0.f;
        const bf16* sl = SLC ? g_sl + (size_t)((slice_of(tk.rt) * 4 + tk.a) * 2 + (rl >> 6)) * 10240 + (q >> 2) * 2048 + (rl & 63) * 32 + (((q & 3) ^ (rl >> 1 & 3)) << 3)
                             : g_sl + (size_t)(slice_of(tk.rt) * 128 + rl) * DM + c0;
        constexpr int US = SLC ? LPR / 4 * 2048 : LPR * 8;
        constexpr int SB = FROWS == 64 || (CTAIL && FSB4) ? 4 : 8;
        for (int b0 = 0; b0 < split(tk.rt); b0 += SB) {
          uint4 u[SB][NU];
#pragma unroll
          for (int b = 0; b < SB; b++)
#pragma unroll
            for (int i = 0; i < NU; i++)
              if (FVOL) u[b][i] = ldcg_if_h<(LEF & 1) != 0>(sl + (size_t)(b0 + b) * 128 * DM + i * US, b0 + b < split(tk.rt) && i * LPR + q < 20);
              else u[b][i] = b0 + b < split(tk.rt) && i * LPR + q < 20 ? __ldcg((const uint4*)(sl + (size_t)(b0 + b) * 128 * DM + i * US)) : make_uint4(0, 0, 0, 0);
          if (FVOL) sched_fence(layer >> 4);
#pragma unroll
          for (int b = 0; b < SB; b++)
#pragma unroll
            for (int i = 0; i < NU; i++) {
              y[i][0] += __uint_as_float(u[b][i].x << 16); y[i][1] += __uint_as_float(u[b][i].x & 0xFFFF0000u); y[i][2] += __uint_as_float(u[b][i].y << 16); y[i][3] += __uint_as_float(u[b][i].y & 0xFFFF0000u);
              y[i][4] += __uint_as_float(u[b][i].z << 16); y[i][5] += __uint_as_float(u[b][i].z & 0xFFFF0000u); y[i][6] += __uint_as_float(u[b][i].w << 16); y[i][7] += __uint_as_float(u[b][i].w & 0xFFFF0000u);
            }
        }
        if (PFF && PFFL && tk.rt == PFF && tk.b < 2 && ct == 32) {
          loaded(__float_as_uint(y[0][0]));
          const int q = tk.a * 2 + tk.b;
          for (int i = 0; i < 20; i++) asm volatile("cp.async.bulk.prefetch.L2.global [%0], 15360;" :: "l"((const char*)g_wb1 + (q * 20 + i) * 15360) : "memory");
          for (int i = 0; i < 8; i++) asm volatile("cp.async.bulk.prefetch.L2.global [%0], 12800;" :: "l"((const char*)g_wb2 + (q * 8 + i) * 12800) : "memory");
          asm volatile("cp.async.bulk.prefetch.L2.global [%0], 9600;" :: "l"((const char*)g_cs + q * 9600) : "memory");
        }
        if (FCGO && ct == 0) { loaded(__float_as_uint(y[0][0])); mbar_arrive(sb + CGO); }
        float s1 = 0.f, s2 = 0.f;
#pragma unroll
        for (int i = 0; i < NU; i++) {
          uint32_t z[4];
#pragma unroll
          for (int e = 0; e < 4; e++) {
            z[e] = pack_bf16(a[i][2 * e] + y[i][2 * e], a[i][2 * e + 1] + y[i][2 * e + 1]);
            const float lo = __uint_as_float(z[e] << 16), hi = __uint_as_float(z[e] & 0xFFFF0000u);
            s1 += lo + hi; s2 = fmaf(lo, lo, fmaf(hi, hi, s2));
          }
          asm volatile("{.reg .pred p; setp.ne.u32 p, %5, 0; @p st.global.v4.u32 [%0], {%1,%2,%3,%4};}"
                       :: "l"(g_xa + r * DM + c0 + i * LPR * 8), "r"(z[0]), "r"(z[1]), "r"(z[2]), "r"(z[3]), "r"((uint32_t)(i * LPR + q < 20)) : "memory");
        }
#pragma unroll
        for (int o = 1; o < LPR; o <<= 1) { s1 += __shfl_xor_sync(0xffffffffu, s1, o); s2 += __shfl_xor_sync(0xffffffffu, s2, o); }
        asm volatile("{.reg .pred p; setp.ne.u32 p, %3, 0; @p red.relaxed.gpu.global.add.v2.f32 [%0], {%1,%2};}"
                     :: "l"(&sy->rstat[r]), "f"(s1), "f"(s2), "r"((uint32_t)(q == 0)) : "memory");
        if (ct == 0 && tk.rt == FXT) XT(136 + tk.a * 4 + tk.b, 2);
        TM(0); TM(1); TM(2); TM(3);
      } else if (tk.type == T_F) {
        if (tk.rt == BKVZ) for (int i = ct; i < NH * BF * 6 / 8; i += 256) ((uint4*)g_bkv)[(tk.a * 2 + tk.b) * (NH * BF * 6 / 8) + i] = make_uint4(0, 0, 0, 0);
        if (PFF && tk.rt == PFF && ct == 32) {
          const int q = tk.a * 2 + tk.b;
          for (int i = 0; i < 20; i++) asm volatile("cp.async.bulk.prefetch.L2.global [%0], 15360;" :: "l"((const char*)g_wb1 + (q * 20 + i) * 15360) : "memory");
          for (int i = 0; i < 8; i++) asm volatile("cp.async.bulk.prefetch.L2.global [%0], 12800;" :: "l"((const char*)g_wb2 + (q * 8 + i) * 12800) : "memory");
          asm volatile("cp.async.bulk.prefetch.L2.global [%0], 9600;" :: "l"((const char*)g_cs + q * 9600) : "memory");
        }
        if (ct == 0) { wait_count(&sy->wcnt[(tk.rt * 4 + tk.a) * 2 + tk.b], split(tk.rt)); mbar_arrive(sb + CGO); }
        const int r = tk.rt * 128 + tk.b * 64 + (ct >> 2), c0 = tk.a * 160 + (ct & 3) * 4;
        uint2 x[10];
#pragma unroll
        for (int i = 0; i < 10; i++) x[i] = __ldg((const uint2*)(xin + r * DM + c0 + i * 16));
        bar_sync(3, 256);
        float4 a[10];
#pragma unroll
        for (int i = 0; i < 10; i++) a[i] = __ldcg((const float4*)(g_acc + (layer * ACC_ROWS + r - RT_SPLIT * 128) * DM + c0 + i * 16));
        float s1 = 0.f, s2 = 0.f;
#pragma unroll
        for (int i = 0; i < 10; i++) {
          const uint2 z = make_uint2(pack_bf16(a[i].x + __uint_as_float(x[i].x << 16), a[i].y + __uint_as_float(x[i].x & 0xFFFF0000u)),
                                     pack_bf16(a[i].z + __uint_as_float(x[i].y << 16), a[i].w + __uint_as_float(x[i].y & 0xFFFF0000u)));
          *(uint2*)(g_xa + r * DM + c0 + i * 16) = z;
          const float v0 = __uint_as_float(z.x << 16), v1 = __uint_as_float(z.x & 0xFFFF0000u), v2 = __uint_as_float(z.y << 16), v3 = __uint_as_float(z.y & 0xFFFF0000u);
          s1 += (v0 + v1) + (v2 + v3); s2 = fmaf(v0, v0, fmaf(v1, v1, fmaf(v2, v2, fmaf(v3, v3, s2))));
        }
        s1 += __shfl_xor_sync(0xffffffffu, s1, 1); s2 += __shfl_xor_sync(0xffffffffu, s2, 1);
        s1 += __shfl_xor_sync(0xffffffffu, s1, 2); s2 += __shfl_xor_sync(0xffffffffu, s2, 2);
        if ((ct & 3) == 0) red_add2(&sy->rstat[r], s1, s2);
        TM(0); TM(1); TM(2); TM(3);
      } else if (tk.a < NZ) {
        if (!BSL) for (int i = ct; i < ACC_ROWS * DM / 4 / NZ; i += 256) ((uint4*)(g_acc + layer * ACC_ROWS * DM))[tk.a * (ACC_ROWS * DM / 4 / NZ) + i] = make_uint4(0, 0, 0, 0);
        if (layer == 1) {
          if (ct == 0) wait_count(&sy->pro[0], NPRO);
          bar_sync(3, 256);
        }
        for (int i = tk.a * 256 + ct; i < (int)(sizeof(Sync) / 16); i += NZ * 256) ((uint4*)&g_sync[layer ^ 1])[i] = make_uint4(0, 0, 0, 0);
        bar_sync(3, 256);
        if (ct == 0) red_release(&sy->zeroed);
        __syncwarp();
      } else if (tk.a >= NZ + 80) {
        const int c = tk.a - NZ - 80, cq = opq(ct);
        uint4 u[20];
#pragma unroll
        for (int i = 0; i < 20; i++) u[i] = (PEF & 1) ? ldcg_if_h<true>((const uint4*)(wo2 + c * 64 * DM) + i * 256 + cq, true) : __ldg((const uint4*)(wo2 + c * 64 * DM) + i * 256 + cq);
#pragma unroll
        for (int i = 0; i < 20; i++) {
          const int p = i * 256 + cq, kr = p / 80, n8 = p % 80, gq = n8 / 10;
          st128_h<(PEF & 2) != 0>(&g_wb2[(gq * 10 + c) * 640 + (n8 % 10 >> 1) * 128 + kr * 2 + ((n8 & 1) ^ (kr >> 2 & 1))], u[i]);
        }
      } else if (P1M) {
        const int gq = (tk.a - NZ) / 10, k0 = (tk.a - NZ) % 10 * 64;
        const uint32_t ln = opq(lane), gg = ln >> 2, tt = ln & 3, wi = opq(ct >> 5);
        const uint32_t T = sb + OST, stg = sb + (it % NST) * STAGE;
        mbar_wait_long(sb + FULL + (it % NST) * 8, (it / NST) & 1);
        uint32_t a0[4], a1[4], a0k[2], a1k;
        {
          const uint32_t pa = stg + 30720 + w * 800 + tt * 80 + gg * 2;
          auto pr = [&](int d, int f) { uint32_t lo, hi;
            asm volatile("ld.shared.u16 %0, [%1];" : "=r"(lo) : "r"(pa + d * 40 + f * 2) : "memory");
            asm volatile("ld.shared.u16 %0, [%1];" : "=r"(hi) : "r"(pa + d * 40 + 40 + f * 2) : "memory");
            return lo | hi << 16; };
          a0[0] = pr(0, 0); a0[1] = pr(0, 8); a0[2] = pr(8, 0); a0[3] = pr(8, 8);
          const int d2 = tt < 2 ? 16 : 0, f2 = gg < 4 ? 16 : 0;
          a0k[0] = pr(d2, 0); a0k[1] = pr(d2, 8);
          a1[0] = pr(0, f2); a1[2] = pr(8, f2); a1k = pr(d2, f2);
          a1[1] = a1[3] = 0;
          if (tt >= 2) a0k[0] = a0k[1] = a1k = 0;
          if (gg >= 4) a1[0] = a1[2] = a1k = 0;
        }
        float c[8][2][4];
        const uint32_t pb = stg + cw * 10240 + gg * 160 + w * 40 + tt * 4;
#pragma unroll
        for (int nt = 0; nt < 8; nt++) {
          const uint32_t b0 = lds32(pb + nt * 1280), b1 = lds32(pb + nt * 1280 + 16);
          uint32_t b2 = lds32(pb + nt * 1280 + (tt < 2 ? 32 : 0));
          if (tt >= 2) b2 = 0;
#pragma unroll
          for (int i = 0; i < 8; i++) c[nt][i >> 2][i & 3] = 0.f;
          mma16816(c[nt][0], a0, b0, b1); mma16816(c[nt][1], a1, b0, b1);
          mma1688(c[nt][0], a0k[0], a0k[1], b2); mma1688(c[nt][1], a1k, 0u, b2);
        }
        uint32_t v[3][4];
        const uint32_t pv = stg + 20480 + (wi * 8 + (ln & 7)) * 160 + (ln >> 3) * 16;
        ldsm4t(v[0], pv); ldsm4t(v[1], pv + 64); ldsm4t(v[2], pv + (ln >> 4 ? 96 : 128));
        mbar_wait_long(sb + FREE + cw * 8, (nd & 1) ^ 1);
        loaded(v[2][3]);
        bar_sync(3, 256);
        if (lane == 0) mbar_arrive(sb + EMPTY + (it % NST) * 8);
        it++;
        {
          const uint32_t n0 = cw * 80 + w * 2 + (gg >> 1) * 8 + (gg & 1);
#pragma unroll
          for (int q = 0; q < 3; q++) {
            const uint32_t n = n0 + q * 32, ro = T + n * 128 + tt * 4, sw = (n >> 3 & 3) * 2 + (n & 1);
            if (q < 2 || gg < 4)
#pragma unroll
              for (int nt = 0; nt < 8; nt++) sts32(ro + ((nt ^ sw) << 4), pack_bf16(c[nt][q >> 1][(q & 1) * 2], c[nt][q >> 1][(q & 1) * 2 + 1]));
          }
#pragma unroll
          for (int i = 0; i < 10; i++) sts32(T + (160 + i * 8 + gg) * 128 + ((wi ^ gg) << 4) + tt * 4, v[i >> 2][i & 3]);
        }
        bar_sync(3, 256);
        const int cq = opq(ct);
        for (int i = cq; i < 240 * 8; i += 256) {
          const uint32_t n = i >> 3, sw = n < 160 ? (n >> 3 & 3) * 2 + (n & 1) : n & 7;
          uint32_t u[4]; lds128(u, T + n * 128 + (((i & 7) ^ sw) << 4));
          st128_h<(PEF & 2) != 0>(g_wb1 + (gq * 240 + n) * DM + k0 + (i & 7) * 8, make_uint4(u[0], u[1], u[2], u[3]));
        }
        if (cq < 240) {
          float cs = 0.f;
#pragma unroll
          for (int i = 0; i < 8; i++) {
            uint32_t u[4]; lds128(u, T + cq * 128 + (((i + cq) & 7) << 4));
#pragma unroll
            for (int e = 0; e < 4; e++) cs += __uint_as_float(u[e] << 16) + __uint_as_float(u[e] & 0xFFFF0000u);
          }
          g_cs[(k0 >> 6) * 3 * DM + gq * 240 + cq] = cs;
        }
        bar_sync(3, 256);
      } else {
        const int gq = (tk.a - NZ) / 10, k0 = (tk.a - NZ) % 10 * 64, r = ct & 63, hh = ct >> 6;
        bf16* T = (bf16*)(smraw + OST);
        float* ph = (float*)(smraw + OST + 30720);
        const uint32_t stg = sb + (it % NST) * STAGE;
        mbar_wait_long(sb + FULL + (it % NST) * 8, (it / NST) & 1);
        uint2 u[3][5];
#pragma unroll
        for (int i = 0; i < 15; i++) { const float2 v = lds64f(stg + (i / 5) * 10240 + r * 160 + hh * 40 + (i % 5) * 8); u[i / 5][i % 5] = make_uint2(__float_as_uint(v.x), __float_as_uint(v.y)); }
        uint32_t pv[4];
#pragma unroll
        for (int i = 0; i < 4; i++) pv[i] = lds32(stg + 30720 + min(ct + i * 256, 799) * 4);
        mbar_wait_long(sb + FREE + cw * 8, (nd & 1) ^ 1);
        loaded(u[2][4].x); loaded(pv[3]);
        bar_sync(3, 256);
        if (lane == 0) mbar_arrive(sb + EMPTY + (it % NST) * 8);
        it++;
#pragma unroll
        for (int i = 0; i < 4; i++) if (ct + i * 256 < 800) *(float2*)(ph + (ct + i * 256) * 2) = make_float2(__uint_as_float(pv[i] << 16), __uint_as_float(pv[i] & 0xFFFF0000u));
        bar_sync(3, 256);
#pragma unroll
        for (int part = 0; part < 2; part++) {
          float a[BDH];
#pragma unroll
          for (int i = 0; i < 5; i++) {
            a[4 * i] = __uint_as_float(u[part][i].x << 16); a[4 * i + 1] = __uint_as_float(u[part][i].x & 0xFFFF0000u);
            a[4 * i + 2] = __uint_as_float(u[part][i].y << 16); a[4 * i + 3] = __uint_as_float(u[part][i].y & 0xFFFF0000u);
          }
#pragma unroll 1
          for (int f4 = 0; f4 < 5; f4++) {
            float4 q = make_float4(0.f, 0.f, 0.f, 0.f);
#pragma unroll
            for (int dd = 0; dd < BDH; dd++) {
              const float4 p = *(const float4*)(ph + (hh * BDH + dd) * BDH + f4 * 4);
              q.x = fmaf(a[dd], p.x, q.x); q.y = fmaf(a[dd], p.y, q.y); q.z = fmaf(a[dd], p.z, q.z); q.w = fmaf(a[dd], p.w, q.w);
            }
            bf16* dst = T + (part * 80 + f4 * 16 + hh * 2) * 64 + r;
            dst[0] = __float2bfloat16(q.x); dst[64] = __float2bfloat16(q.y); dst[8 * 64] = __float2bfloat16(q.z); dst[9 * 64] = __float2bfloat16(q.w);
          }
        }
#pragma unroll
        for (int i = 0; i < 5; i++) {
          uint16_t* dst = (uint16_t*)T + (160 + hh * BDH + i * 4) * 64 + r;
          dst[0] = (uint16_t)u[2][i].x; dst[64] = (uint16_t)(u[2][i].x >> 16); dst[128] = (uint16_t)u[2][i].y; dst[192] = (uint16_t)(u[2][i].y >> 16);
        }
        bar_sync(3, 256);
        for (int i = ct; i < 240 * 8; i += 256) *(uint4*)(g_wb1 + (gq * 240 + (i >> 3)) * DM + k0 + (i & 7) * 8) = *(const uint4*)(T + i * 8);
        if (ct < 240) {
          float cs = 0.f;
#pragma unroll
          for (int i = 0; i < 8; i++) {
            const uint4 v = *(const uint4*)(T + ct * 64 + ((i + ct) & 7) * 8);
            const uint32_t vv[4] = {v.x, v.y, v.z, v.w};
#pragma unroll
            for (int e = 0; e < 4; e++) cs += __uint_as_float(vv[e] << 16) + __uint_as_float(vv[e] & 0xFFFF0000u);
          }
          g_cs[(k0 >> 6) * 3 * DM + gq * 240 + ct] = cs;
        }
        bar_sync(3, 256);
      }
    }
  }
  __syncwarp();
  if (CTAIL ? SENT && blockIdx.x == 0 : !__shfl_sync(0xffffffffu, early, 0)) asm volatile("griddepcontrol.wait;" ::: "memory");
}

#define KVREL 0
#define KVF 0
#define PFA_N 2
#define PFA_DELAY 500
#define PFA_LIMIT 30000
#define PFL 2
#define RESP 1
#define BTR 2
#define PFQ 0
#define PFQ_C 9
#define PFQ_N 8
#define PFQ_S 0
#define KVO 1
#define BOG 0
#define BWP 0
#define BWN 4
#define BEF 0
#define PFL_X 0
#define PFL_W2 4
#define PFL_C2 3
#define PFE 0
#define PFE_S 0
#define PFL_B 5
#define PFL_C 9
#define PFL_D 0
#define PFL_S 0
#define PFL_ORD 0x0312
#define PFB_KV 1
#define PFB_DELAY 2000
#define PFA_ORD 0x0312
#define PFA_SLEEP 0
#define BTPF 0
#define BHALF 0
#define LDL8 3
#define W2E 1
#define PREFETCH_A 0
namespace bk {
constexpr uint32_t STAGE = 47104, NST = 4;
constexpr uint32_t W2 = 0, A2 = 102400;
constexpr uint32_t PHI = 102400, VS = PHI + 128 * 336, KVS = PHI;
constexpr uint32_t OS = A2 + 65536;
constexpr uint32_t PHQ = NST * STAGE;
constexpr uint32_t CS = PHQ;
constexpr uint32_t MISC = PHQ + 128 * 336;
constexpr int NST2 = 7;
constexpr uint32_t FULL = MISC, EMPTY = MISC + 32, EMPTY2 = MISC + 64, BW2 = MISC + 128, BOK = MISC + 136, BKR = MISC + 144, BKV = MISC + 152, FULL2 = MISC + 160;
constexpr uint32_t SMEM = MISC + 256;
}
DEVI void feature_map(const float* d, uint32_t dst) {
#pragma unroll
  for (int r = 0; r < 2; r++) {
    const float l2e = 1.4426950408889634f;
    float mx = d[2 * r], mn = d[2 * r];
#pragma unroll
    for (int i = 1; i < 20; i++) { const float x = d[(i >> 1) * 4 + 2 * r + (i & 1)]; mx = fmaxf(mx, x); mn = fminf(mn, x); }
    mx *= l2e; mn *= l2e;
    float p[20], n[20], sp = 0.f, sn = 0.f;
#pragma unroll
    for (int i = 0; i < 20; i++) {
      const float x = d[(i >> 1) * 4 + 2 * r + (i & 1)];
      p[i] = ex2(fmaf(x, l2e, -mx)); n[i] = ex2(fmaf(x, -l2e, mn)); sp += p[i]; sn += n[i];
    }
    sp = rcp(sp); sn = rcp(sn);
#pragma unroll
    for (int i = 0; i < 5; i++)
      sts128(dst + r * 8 * 336 + i * 16, pack_bf16(p[4 * i] * sp, n[4 * i] * sn), pack_bf16(p[4 * i + 1] * sp, n[4 * i + 1] * sn),
             pack_bf16(p[4 * i + 2] * sp, n[4 * i + 2] * sn), pack_bf16(p[4 * i + 3] * sp, n[4 * i + 3] * sn));
  }
}

__global__ void __launch_bounds__(384, 1)
layerb_kernel(int layer, uint32_t nw2, Sync* sy, const bf16* __restrict__ xin, bf16* __restrict__ out, const void* wa0, const void* wa1, const void* wa2, const void* wa3,
              const __grid_constant__ CUtensorMap mx, const __grid_constant__ CUtensorMap mw1, const __grid_constant__ CUtensorMap mo,
              const __grid_constant__ CUtensorMap mos) {
  using namespace bk;
  extern __shared__ __align__(1024) uint8_t smraw[];
  const uint32_t sb = smem_u32(smraw);
  const int tid = threadIdx.x, lane = tid & 31;
  const int wg = __shfl_sync(0xffffffffu, tid >> 7, 0), w = __shfl_sync(0xffffffffu, (tid >> 5) & 3, 0);
  const int rt = CTAIL ? 15 - (blockIdx.x >> 3) : blockIdx.x >> 3, gq = blockIdx.x & 7;
  if (blockIdx.x >= 128) {
    asm volatile("griddepcontrol.launch_dependents;");
    if (BLN && tid >= 32) {
      asm volatile("griddepcontrol.wait;" ::: "memory");
      for (int i = (blockIdx.x - 128) * 352 + tid - 32; i < (NSEG - 1) * 24 * 32; i += (gridDim.x - 128) * 352) ((uint4*)g_ar)[(i >> 5) * 64 + (i & 31)] = make_uint4(0, 0, 0, 0);
    }
    if (tid == 0) {
      asm volatile("griddepcontrol.wait;" ::: "memory");
      const uint32_t t0 = clk32();
      __nanosleep(PFA_DELAY);
      const int nc = gridDim.x - 128;
      for (int i = blockIdx.x - 128; i < PFA_N * 480 && clk32() - t0 < PFA_LIMIT; i += nc) {
        const int m = PFA_ORD >> (i / 480 * 4) & 3;
        const char* p = (const char*)(m == 0 ? wa0 : m == 1 ? wa1 : m == 2 ? wa2 : wa3) + (size_t)(i % 480) * 16384;
        asm volatile("cp.async.bulk.prefetch.L2.global [%0], 16384;" :: "l"(p) : "memory");
        if (PFA_SLEEP) __nanosleep(PFA_SLEEP);
      }
    }
    return;
  }
  if (tid == 0) {
    for (int i = 0; i < NST; i++) { mbar_init(sb + FULL + i * 8, 1); mbar_init(sb + EMPTY + i * 8, 8); }
    for (int i = 0; i < NST2; i++) { mbar_init(sb + FULL2 + i * 8, 1); mbar_init(sb + EMPTY2 + i * 8, 8); }
    mbar_init(sb + BW2, 1); mbar_init(sb + BOK, 256); mbar_init(sb + BKV, 1); mbar_init(sb + BKR, 1);
    asm volatile("fence.mbarrier_init.release.cluster;" ::: "memory");
  }
  if (!LDL8) asm volatile("griddepcontrol.launch_dependents;");
  if (wg == 0) {
    asm volatile("setmaxnreg.dec.sync.aligned.u32 40;");
    bar_sync(0, 384);
    if (tid == 32 && layer == 0 && PREFETCH_A) {
      asm volatile("griddepcontrol.wait;" ::: "memory");
      __nanosleep(PFB_DELAY);
      for (int i = 0; i < 32; i++) {
        const char* p = (const char*)(PFB_KV ? (i < 16 ? wa2 : wa1) : (i < 16 ? wa3 : wa0)) + (size_t)blockIdx.x * 61440 + (i & 15) * 3840;
        asm volatile("cp.async.bulk.prefetch.L2.global [%0], 3840;" :: "l"(p) : "memory");
        __nanosleep(PREFETCH_A);
      }
    }
    if (PFL && w == 1 && !layer) {
      for (int c = PFL_C % NST; c <= PFL_C; c += NST) mbar_wait_long(sb + FULL + PFL_C % NST * 8, c / NST & 1);
      if (PFL_D) __nanosleep(PFL_D);
      uint32_t acc = 0;
#pragma unroll 1
      for (int i = 0; i < PFL * 15 / PFL_B - PFL_X; i++) {
        const int m = PFL_ORD >> (i / (15 / PFL_B) * 4) & 3;
        if (PFL_W2 && i == PFL_W2) mbar_wait_long(sb + FULL2 + PFL_C2 * 8, 0);
        const char* p = (const char*)(m == 0 ? wa0 : m == 1 ? wa1 : m == 2 ? wa2 : wa3) + (blockIdx.x * 15 + i % (15 / PFL_B) * PFL_B) * 4096 + lane * 128;
        uint32_t v[PFL_B];
#pragma unroll
        for (int n = 0; n < PFL_B; n++) asm volatile("ld.global.cg.L2::128B.u32 %0, [%1];" : "=r"(v[n]) : "l"(p + n * 4096) : "memory");
#pragma unroll
        for (int n = 0; n < PFL_B; n++) acc |= v[n];
        if (PFL_S) __nanosleep(PFL_S);
        loaded(acc);
      }
    }
    if (PFQ && tid == 96 && !layer) {
      if (PFQ == 1) for (int c = PFQ_C % NST; c <= PFQ_C; c += NST) mbar_wait_long(sb + FULL + PFQ_C % NST * 8, c / NST & 1);
      if (PFQ == 2) mbar_wait_long(sb + FULL2 + PFQ_C * 8, 0);
      if (PFQ == 3) mbar_wait_long(sb + BKR, 0);
      if (PFQ == 4) mbar_wait_long(sb + BOK, 0);
#pragma unroll 1
      for (int i = 0; i < PFQ_N; i++) {
        asm volatile("cp.async.bulk.prefetch.L2.global [%0], 7680;" :: "l"((const char*)(i < 8 ? wa0 : wa3) + (blockIdx.x * 8 + (i & 7)) * 7680) : "memory");
        if (PFQ_S) __nanosleep(PFQ_S);
      }
    }
    if (PFE && tid == 96 && !layer && blockIdx.x < 32) {
#pragma unroll 1
      for (int i = 0; i < PFE * 15; i++) {
        const int m = PFL_ORD >> (i / 15 * 4) & 3;
        const char* p = (const char*)(m == 0 ? wa0 : m == 1 ? wa1 : m == 2 ? wa2 : wa3) + (blockIdx.x * 15 + i % 15) * 16384;
        asm volatile("cp.async.bulk.prefetch.L2.global [%0], 16384;" :: "l"(p) : "memory");
        if (PFE_S) __nanosleep(PFE_S);
      }
    }
    if (BLN && w == 3 && layer) {
      asm volatile("griddepcontrol.wait;" ::: "memory");
      uint4* p = (uint4*)g_bst + blockIdx.x * 64 + lane;
      p[0] = p[32] = make_uint4(0, 0, 0, 0);
    }
    if (w == 2) {
      bar_sync(4, 288);
      if (lane == 0) {
        if (KVREL) red_release(&sy->bkv_cnt[gq]);
        spin_count(&sy->bkv_cnt[gq], 16);
        mbar_arrive(sb + BKR);
      }
    }
    if (tid == 0) {
      if (BTPF) {
        asm volatile("prefetch.tensormap [%0];" :: "l"(&mx) : "memory"); asm volatile("prefetch.tensormap [%0];" :: "l"(&mw1) : "memory");
        asm volatile("prefetch.tensormap [%0];" :: "l"(&mos) : "memory"); asm volatile("prefetch.tensormap [%0];" :: "l"(&mo) : "memory");
      }
      const int npre = BFL ? (rt >= tl::RT0 ? NST : 0) : (BWP >> layer & 1) ? BWN : 0;
      if (!BFL)
#pragma unroll 1
        for (int c = 0; c < npre; c++) { mbar_expect(sb + FULL + c * 8, STAGE); tma2d(sb + c * STAGE + 16384, &mw1, c * 64, gq * 240, sb + FULL + c * 8); }
      if (BFL) { wait_count(&sy->pad1[0], nw2); asm volatile("fence.proxy.async.global;" ::: "memory"); }
      else asm volatile("griddepcontrol.wait;" ::: "memory");
      GT(2, 0);
      if (BFL && npre) {
#pragma unroll 1
        for (int c = 0; c < (int)NST; c++) { mbar_expect(sb + FULL + c * 8, STAGE); tma2d(sb + c * STAGE + 16384, &mw1, c * 64, gq * 240, sb + FULL + c * 8); }
        spin_count(&sy->pro[1 + rt - tl::RT0], 64);
        asm volatile("fence.proxy.async.global;" ::: "memory");
      }
#pragma unroll 1
      for (int c = 0; c < 10; c++) {
        const uint32_t st = c % NST, a = sb + st * STAGE, fb = sb + FULL + st * 8;
        if (c >= npre) {
          mbar_wait_long(sb + EMPTY + st * 8, ((c / NST) & 1) ^ 1);
          mbar_expect(fb, STAGE - (BHALF & 1) * 8192);
        }
        tma2d_h<(BEF & 2) != 0>(a, &mx, c * 64, rt * 128, fb);
        if (c >= npre) tma2d_h<(BEF & 1) != 0>(a + 16384, &mw1, c * 64, gq * 240, fb);
      }
      mbar_wait_long(sb + BKV, 0);
      mbar_expect(sb + BW2, 102400);
      PT(1, 0);
      for (int c = 0; c < 2; c++) { if (BEF & 16) bulk_load(sb + W2 + c * 51200, g_wb2 + gq * 6400 + c * 3200, 51200, sb + BW2); else bulk_load_plain(sb + W2 + c * 51200, g_wb2 + gq * 6400 + c * 3200, 51200, sb + BW2); }
      mbar_wait_long(sb + BOK, 0);
      if (BOG) red_release(&sy->bo_cnt[rt]);
      else {
        asm volatile("cp.async.bulk.tensor.2d.global.shared::cta.bulk_group [%0, {%2, %3}], [%1];" :: "l"(&mos), "r"(sb + OS), "r"(gq * 80), "r"(rt * 128) : "memory");
        asm volatile("cp.async.bulk.commit_group; cp.async.bulk.wait_group 0;" ::: "memory");
        publish_bulk<WFEN>(&sy->bo_cnt[rt]);
      }
      spin_count(&sy->bo_cnt[rt], 8);
      if (BOG) asm volatile("fence.proxy.async.global;" ::: "memory"); else fence_flag_to_bulk();
#pragma unroll 1
      for (int c = 0; c < 10; c++) {
        const uint32_t st = c < NST2 ? c : c - NST2, fb = sb + FULL2 + st * 8;
        if (c >= NST2) mbar_wait_long(sb + EMPTY2 + st * 8, 0);
        mbar_expect(fb, 16384 - (BHALF >> 1 & 1) * 8192);
        tma2d_h<(BEF & 4) != 0>(sb + A2 + st * 16384, &mo, c * 64, rt * 128, fb);
      }
    }
  } else {
    asm volatile("setmaxnreg.inc.sync.aligned.u32 232;");
    bar_sync(0, 384);
    if (!BFL) asm volatile("griddepcontrol.wait;" ::: "memory");
    const int cw = wg - 1, g = lane >> 2, t = lane & 3, ct = tid - 128;
    const int row = cw * 64 + w * 16 + g;
    float rs[2], ms[2], cv[10];
    if (BFL) {
      mbar_wait_long(sb + FULL, 0);
#pragma unroll
      for (int e = 0; e < 2; e++) asm volatile("ld.global.cg.v2.f32 {%0,%1}, [%2];" : "=f"(ms[e]), "=f"(rs[e]) : "l"(&sy->rstat[rt * 128 + row + 8 * e]) : "memory");
#pragma unroll
      for (int i = 0; i < 10; i++) asm volatile("ld.global.cg.f32 %0, [%1];" : "=f"(cv[i]) : "l"(g_cs + i * 3 * DM + gq * 240 + min(ct, 239)) : "memory");
    } else {
      float cs = 0.f;
      if (ct < 240) {
#pragma unroll
        for (int i = 0; i < 10; i++) cs += __ldcg(g_cs + i * 3 * DM + gq * 240 + ct);
      }
      if (!CTAIL)
#pragma unroll
      for (int e = 0; e < 2; e++) {
        const float2 st = __ldcg(&sy->rstat[rt * 128 + row + 8 * e]);
        const float m = st.x * (1.0f / DM);
        rs[e] = rsqrtf(fmaxf(st.y * (1.0f / DM) - m * m, 0.f) + 1e-5f);
        ms[e] = -m * rs[e];
      }
      if (ct < 240) sts32(sb + CS + ct * 4, __float_as_uint(cs));
      bar_sync(3, 256);
      if (CTAIL) {
        mbar_wait_long(sb + FULL, 0);
#pragma unroll
        for (int e = 0; e < 2; e++) asm volatile("ld.global.cg.v2.f32 {%0,%1}, [%2];" : "=f"(ms[e]), "=f"(rs[e]) : "l"(&sy->rstat[rt * 128 + row + 8 * e]) : "memory");
      }
    }
    uint32_t res[20];
    const int off = (rt * 128 + row) * DM + gq * 80 + 2 * t;
    {
      float d[120];
#pragma unroll
      for (int i = 0; i < 120; i++) d[i] = 0.f;
      for (int c = 0; c < 10; c++) {
        const uint32_t st = c % NST, a = sb + st * STAGE;
        mbar_wait_long(sb + FULL + st * 8, (c / NST) & 1);
        if (c == 0 && ct == 0) PT(1, 15);
        const uint64_t da = mkdesc(a + cw * 8192, 16, 1024, 1), db = mkdesc(a + 16384, 16, 1024, 1);
        wg_fence();
#pragma unroll
        for (int k = 0; k < 4; k++) wgmma_n240_nn(d, da + k * 2, db + k * 2, c | k);
        wg_commit();
        if (c > 0) { wg_wait<1>(); if (lane == 0) mbar_arrive(sb + EMPTY + ((c - 1) % NST) * 8); }
        if (BFL && c == 8) {
          float cs = 0.f;
#pragma unroll
          for (int i = 0; i < 10; i++) cs += cv[i];
          if (ct < 240) sts32(sb + CS + ct * 4, __float_as_uint(cs));
        }
      }
      if (BFL) bar_sync(3, 256);
      wg_wait<0>();
      if (lane == 0) mbar_arrive(sb + EMPTY + (9 % NST) * 8);
      if (ct == 0) PT(1, 2);
      if (CTAIL)
#pragma unroll
      for (int e = 0; e < 2; e++) {
        const float m = ms[e] * (1.0f / DM);
        rs[e] = rsqrtf(fmaxf(rs[e] * (1.0f / DM) - m * m, 0.f) + 1e-5f);
        ms[e] = -m * rs[e];
      }
#pragma unroll
      for (int i = 0; i < 30; i++) {
        const float2 c = lds64f(sb + CS + (8 * i + 2 * t) * 4);
        d[4 * i] = fmaf(c.x, ms[0], d[4 * i] * rs[0]); d[4 * i + 1] = fmaf(c.y, ms[0], d[4 * i + 1] * rs[0]);
        d[4 * i + 2] = fmaf(c.x, ms[1], d[4 * i + 2] * rs[1]); d[4 * i + 3] = fmaf(c.y, ms[1], d[4 * i + 3] * rs[1]);
      }
      if (ct == 0) PT(1, 11);
      bar_sync(3, 256);
      if (W2E && ct == 0) mbar_arrive(sb + BKV);
      feature_map(&d[40], sb + PHI + row * 336 + t * 80);
      if (ct == 0) PT(1, 12);
#pragma unroll
      for (int i = 0; i < 10; i++) {
        const int c = i * 8 + 2 * t;
        const uint32_t a = sb + VS + row * 208 + (c / 20) * 48 + (c % 20) * 2;
        sts32(a, pack_bf16(d[80 + 4 * i], d[81 + 4 * i])); sts32(a + 8 * 208, pack_bf16(d[82 + 4 * i], d[83 + 4 * i]));
      }
      { const uint32_t a = sb + VS + row * 208 + t * 48 + 40; sts64(a, 0x3F80u, 0u); sts64(a + 8 * 208, 0x3F80u, 0u); }
      bar_sync(3, 256);
      if (ct == 0) PT(1, 13);
      {
        float kv[5][4];
#pragma unroll
        for (int i = 0; i < 20; i++) kv[i >> 2][i & 3] = 0.f;
        const uint32_t pa = sb + PHI + ((lane >> 4) * 8 + (lane & 7)) * 336 + w * 80 + ((lane >> 3) & 1) * 16;
        const uint32_t va = sb + VS + lane * 208 + w * 48;
#pragma unroll
        for (int k2 = 0; k2 < 4; k2++) {
          uint32_t b[3][4];
#pragma unroll
          for (int n = 0; n < 3; n++) ldsm4t(b[n], va + k2 * 32 * 208 + n * 16);
#pragma unroll
          for (int kk = 0; kk < 2; kk++) {
            uint32_t a[4], a2[4];
            ldsm4t(a, pa + (k2 * 32 + kk * 16) * 336 + cw * 32);
            ldsm4t(a2, pa + (k2 * 32 + kk * 16) * 336 + 64);
#pragma unroll
            for (int n = 0; n < 3; n++) mma16816(kv[n], a, b[n][2 * kk], b[n][2 * kk + 1]);
            if (cw == 0) { mma16816(kv[3], a2, b[0][2 * kk], b[0][2 * kk + 1]); mma16816(kv[4], a2, b[1][2 * kk], b[1][2 * kk + 1]); }
            else mma16816(kv[3], a2, b[2][2 * kk], b[2][2 * kk + 1]);
          }
        }
        float* p = g_bkv + ((gq * 4 + w) * BF + g) * 24 + 2 * t;
        PINF(kv[0][0]); PINF(kv[3][0]);
        if (ct == 0) PT(1, 14);
        if (KVO) {
          float* f = g_bkv + (gq * 4 + w) * BF * 24;
#pragma unroll
          for (int n = 0; n < 3; n++)
            asm volatile("red.relaxed.gpu.global.add.v4.f32 [%0], {%1,%2,%3,%4};" :: "l"(f + (cw * 3 + n) * 128 + lane * 4), "f"(kv[n][0]), "f"(kv[n][1]), "f"(kv[n][2]), "f"(kv[n][3]) : "memory");
          asm volatile("red.relaxed.gpu.global.add.v2.f32 [%0], {%1,%2};" :: "l"(f + 768 + cw * 128 + lane * 2), "f"(kv[3][0]), "f"(kv[3][1]) : "memory");
          if (cw == 0) asm volatile("red.relaxed.gpu.global.add.v2.f32 [%0], {%1,%2};" :: "l"(f + 768 + 64 + lane * 2), "f"(kv[4][0]), "f"(kv[4][1]) : "memory");
        } else {
#pragma unroll
        for (int n = 0; n < 3; n++) {
          asm volatile("red.relaxed.gpu.global.add.v2.f32 [%0], {%1,%2};" :: "l"(p + cw * 16 * 24 + n * 8), "f"(kv[n][0]), "f"(kv[n][1]) : "memory");
          asm volatile("red.relaxed.gpu.global.add.v2.f32 [%0], {%1,%2};" :: "l"(p + (cw * 16 + 8) * 24 + n * 8), "f"(kv[n][2]), "f"(kv[n][3]) : "memory");
        }
        asm volatile("red.relaxed.gpu.global.add.v2.f32 [%0], {%1,%2};" :: "l"(p + 32 * 24 + cw * 16), "f"(kv[3][0]), "f"(kv[3][1]) : "memory");
        if (cw == 0) asm volatile("red.relaxed.gpu.global.add.v2.f32 [%0], {%1,%2};" :: "l"(p + 32 * 24 + 8), "f"(kv[4][0]), "f"(kv[4][1]) : "memory");
        }
      }
      if (ct == 0) PT(1, 3);
      if (LDL8 == 4) asm volatile("griddepcontrol.launch_dependents;");
      if (KVF == 1) __threadfence();
      bar_sync(4, 288);
      if (!KVREL) { if (ct == 0) red_release(&sy->bkv_cnt[gq]); __syncwarp(); }
      if (ct == 0) PT(1, 9);
      if (!W2E && ct == 0) mbar_arrive(sb + BKV);
      feature_map(&d[0], sb + PHQ + row * 336 + t * 80);
    }
    if (ct == 0) PT(1, 4);
    const int tw = (rt * 128 + cw * 64 + w * 16) * DM + gq * 80, to0 = tw + (lane >> 3) * DM + (lane & 7) * 8, to4 = tw + (lane >> 1) * DM + 64 + (lane & 1) * 8;
    auto load_res = [&]() {
      if (BTR == 2) {
#pragma unroll
        for (int i = 0; i < 5; i++) ldcg128_h<(BEF & 8) != 0>(*(uint32_t(*)[4])&res[4 * i], g_xa + (i < 4 ? to0 + i * 4 * DM : to4));
      } else {
#pragma unroll
        for (int i = 0; i < 10; i++) { res[2 * i] = __ldcg((const uint32_t*)(g_xa + off + i * 8)); res[2 * i + 1] = __ldcg((const uint32_t*)(g_xa + off + i * 8 + 8 * DM)); }
      }
    };
    if (RESP == 0) load_res();
    mbar_wait_long(sb + BKR, 0);
    if (LDL8 == 1) asm volatile("griddepcontrol.launch_dependents;");
    if (KVF == 2) __threadfence();
    if (KVF == 3) __nanosleep(1500);
    if (ct == 0) PT(1, 5);
    {
      float4 a[4];
#pragma unroll
      for (int i = 0; i < 4; i++) a[i] = __ldcg((const float4*)(g_bkv + gq * 4 * BF * 24) + min(ct + i * 256, 4 * BF * 6 - 1));
#pragma unroll
      for (int i = 0; i < 4; i++) {
        const int e = ct + i * 256;
        if (!KVO) { if (e < 4 * BF * 6) sts64(sb + KVS + e * 8, pack_bf16(a[i].x, a[i].y), pack_bf16(a[i].z, a[i].w)); }
        else if (e < 4 * BF * 6) {
          const int hh = (e >> 4) * 69 >> 10, r = e - hh * 240, tl = r >> 5, q = r - 192;
          const uint32_t hb = sb + KVS + hh * 1920;
          const uint32_t p0 = q < 0 ? hb + ((tl >= 3) * 16 + (r >> 2 & 7)) * 48 + (tl >= 3 ? tl - 3 : tl) * 16 + (r & 3) * 4 : hb + (32 + (q >> 1 & 7)) * 48 + (q >> 4) * 16 + (q & 1) * 8;
          sts32(p0, pack_bf16(a[i].x, a[i].y)); sts32(p0 + (q < 0 ? 8 * 48 : 4), pack_bf16(a[i].z, a[i].w));
        }
      }
    }
    if (RESP == 2) load_res();
    bar_sync(3, 256);
    {
      float o[4][3][4];
#pragma unroll
      for (int hh = 0; hh < 4; hh++) {
        uint32_t a0[4], a1[4], a2[2], c[4];
        const uint32_t qa = sb + PHQ + (cw * 64 + w * 16 + (lane & 15)) * 336 + hh * 80;
        ldsm4(a0, qa + (lane >> 4) * 16); ldsm4(a1, qa + 32 + (lane >> 4) * 16); ldsm2(a2, qa + 64);
        ldsm4t(c, sb + KVS + hh * 1920 + (32 + (lane & 7)) * 48 + min(lane >> 3, 2) * 16);
#pragma unroll
        for (int n = 0; n < 3; n++) {
          uint32_t b[4];
          ldsm4t(b, sb + KVS + hh * 1920 + lane * 48 + n * 16);
          o[hh][n][0] = o[hh][n][1] = o[hh][n][2] = o[hh][n][3] = 0.f;
          mma16816(o[hh][n], a0, b[0], b[1]); mma16816(o[hh][n], a1, b[2], b[3]); mma1688(o[hh][n], a2[0], a2[1], c[n]);
        }
      }
      const uint32_t oa = sb + OS + row * 160 + t * 4;
#pragma unroll
      for (int hh = 0; hh < 4; hh++) {
        const float i0 = __fdividef(1.0f, __shfl_sync(0xffffffffu, o[hh][2][0], (lane & 28) + 2) + 1e-6f);
        const float i1 = __fdividef(1.0f, __shfl_sync(0xffffffffu, o[hh][2][2], (lane & 28) + 2) + 1e-6f);
#pragma unroll
        for (int n = 0; n < 3; n++)
          if (n < 2 || t < 2) {
            sts32(oa + hh * 40 + n * 16, pack_bf16(o[hh][n][0] * i0, o[hh][n][1] * i0));
            sts32(oa + hh * 40 + n * 16 + 8 * 160, pack_bf16(o[hh][n][2] * i1, o[hh][n][3] * i1));
          }
      }
      if (BOG) {
        __syncwarp();
        uint32_t y[5][4];
#pragma unroll
        for (int i = 0; i < 5; i++) lds128(y[i], sb + OS + (cw * 64 + w * 16) * 160 + (i < 4 ? (i * 4 + (lane >> 3)) * 160 + (lane & 7) * 16 : (lane >> 1) * 160 + 128 + (lane & 1) * 16));
#pragma unroll
        for (int i = 0; i < 5; i++) *(uint4*)(g_bo + (i < 4 ? to0 + i * 4 * DM : to4)) = make_uint4(y[i][0], y[i][1], y[i][2], y[i][3]);
      }
      fence_async();
    }
    if (ct == 0) PT(1, 6);
    mbar_arrive(sb + BOK);
    if (RESP == 1) load_res();
    if (LDL8 == 2) asm volatile("griddepcontrol.launch_dependents;");
    float d[40];
#pragma unroll
    for (int i = 0; i < 40; i++) d[i] = 0.f;
    mbar_wait_long(sb + BW2, 0);
    for (int c = 0; c < 10; c++) {
      const uint32_t st = c % NST2;
      mbar_wait_long(sb + FULL2 + st * 8, c / NST2);
      if (ct == 0 && c == 0) PT(1, 7);
      if (LDL8 == 3 && c == 0) asm volatile("griddepcontrol.launch_dependents;");
      const uint64_t da = mkdesc(sb + A2 + st * 16384 + cw * 8192, 16, 1024, 1), db = mkdesc(sb + W2 + c * 10240, 2048, 256, 3);
      wg_fence();
#pragma unroll
      for (int k = 0; k < 4; k++) wgmma_n80_nt(d, da + k * 2, db + k * 32, c | k);
      wg_commit();
      if (c > 0 && c <= 10 - NST2) { wg_wait<1>(); if (lane == 0) mbar_arrive(sb + EMPTY2 + (c - 1) * 8); }
    }
    wg_wait<0>();
    if (ct == 0) PT(1, 10);
    if (BTR == 2) {
      const uint32_t tb = sb + A2 + (w >> 1) * 16384 + cw * 8192 + (w & 1) * 3072;
      bar_sync(5 + cw, 128);
#pragma unroll
      for (int i = 0; i < 5; i++)
        stsm4(tb + (lane & 15) * 176 + (2 * i + (lane >> 4)) * 16, pack_bf16(d[8 * i], d[8 * i + 1]), pack_bf16(d[8 * i + 2], d[8 * i + 3]), pack_bf16(d[8 * i + 4], d[8 * i + 5]), pack_bf16(d[8 * i + 6], d[8 * i + 7]));
      __syncwarp();
      float a[5][2];
#pragma unroll
      for (int i = 0; i < 5; i++) {
        uint32_t y[4];
        lds128(y, tb + (i < 4 ? (i * 4 + (lane >> 3)) * 176 + (lane & 7) * 16 : (lane >> 1) * 176 + 128 + (lane & 1) * 16));
        a[i][0] = a[i][1] = 0.f;
#pragma unroll
        for (int e = 0; e < 4; e++) {
          const uint32_t x = res[4 * i + e];
          const uint32_t z = res[4 * i + e] = pack_bf16(__uint_as_float(y[e] << 16) + __uint_as_float(x << 16), __uint_as_float(y[e] & 0xFFFF0000u) + __uint_as_float(x & 0xFFFF0000u));
          const float lo = __uint_as_float(z << 16), hi = __uint_as_float(z & 0xFFFF0000u);
          a[i][0] += lo + hi; a[i][1] = fmaf(lo, lo, fmaf(hi, hi, a[i][1]));
        }
        if (!BLN || layer) *(uint4*)(out + (i < 4 ? to0 + i * 4 * DM : to4)) = make_uint4(res[4 * i], res[4 * i + 1], res[4 * i + 2], res[4 * i + 3]);
      }
      if (BLN && !layer) {
        float2* bst = g_bst + (rt * 128 + cw * 64 + w * 16) * 8;
        const bool b0 = lane & 1, b1 = lane & 2;
        const int r = (lane & 3) * 4 + (lane >> 3);
        float s[2];
#pragma unroll
        for (int m = 0; m < 2; m++) {
          const float u0 = (b0 ? a[1][m] : a[0][m]) + __shfl_xor_sync(0xffffffffu, b0 ? a[0][m] : a[1][m], 1);
          const float u1 = (b0 ? a[3][m] : a[2][m]) + __shfl_xor_sync(0xffffffffu, b0 ? a[2][m] : a[3][m], 1);
          const float e = a[4][m] + __shfl_xor_sync(0xffffffffu, a[4][m], 1);
          s[m] = (b1 ? u1 : u0) + __shfl_xor_sync(0xffffffffu, b1 ? u0 : u1, 2);
          s[m] += __shfl_xor_sync(0xffffffffu, s[m], 4) + __shfl_sync(0xffffffffu, e, 2 * r);
        }
        asm volatile("{.reg .pred p; .reg .b64 v; setp.eq.u32 p, %3, 0; mov.b64 v, {%1,%2}; @p st.relaxed.gpu.global.b64 [%0], v;}"
                     :: "l"(bst + r * 8 + gq), "r"(__float_as_uint(s[0])), "r"(__float_as_uint(s[1]) | 0x80000000u), "r"(lane & 4) : "memory");
#pragma unroll
        for (int i = 0; i < 5; i++) *(uint4*)(out + (i < 4 ? to0 + i * 4 * DM : to4)) = make_uint4(res[4 * i], res[4 * i + 1], res[4 * i + 2], res[4 * i + 3]);
        if (ct == 0) PT(1, 8);
        uint32_t u[2][4];
        for (int n = 0; n < 4000000; n++) {
#pragma unroll
          for (int e = 0; e < 2; e++)
            asm volatile("{.reg .b64 a, b; ld.relaxed.gpu.global.v2.b64 {a, b}, [%4]; mov.b64 {%0,%1}, a; mov.b64 {%2,%3}, b;}"
                         : "=r"(u[e][0]), "=r"(u[e][1]), "=r"(u[e][2]), "=r"(u[e][3]) : "l"(bst + lane * 4 + e * 2) : "memory");
          if (__all_sync(0xffffffffu, (int)(u[0][1] & u[0][3] & u[1][1] & u[1][3]) < 0)) break;
        }
        float s1 = __uint_as_float(u[0][0]) + __uint_as_float(u[0][2]) + (__uint_as_float(u[1][0]) + __uint_as_float(u[1][2]));
        float s2 = __uint_as_float(u[0][1]) + __uint_as_float(u[0][3]) + (__uint_as_float(u[1][1]) + __uint_as_float(u[1][3]));
        s1 += __shfl_xor_sync(0xffffffffu, s1, 1); s2 += __shfl_xor_sync(0xffffffffu, s2, 1);
        const float m = s1 * (1.0f / DM), sc = rsqrtf(fmaxf(s2 * (-1.0f / DM) - m * m, 0.f) + 1e-5f), sh = -m * sc;
#pragma unroll
        for (int i = 0; i < 5; i++) {
          const float c = i < 4 ? __shfl_sync(0xffffffffu, sc, i * 8 + (lane >> 3) * 2) : sc, h = i < 4 ? __shfl_sync(0xffffffffu, sh, i * 8 + (lane >> 3) * 2) : sh;
          uint32_t z[4];
#pragma unroll
          for (int e = 0; e < 4; e++) z[e] = pack_bf16(fmaf(__uint_as_float(res[4 * i + e] << 16), c, h), fmaf(__uint_as_float(res[4 * i + e] & 0xFFFF0000u), c, h));
          *(uint4*)(g_xn + (i < 4 ? to0 + i * 4 * DM : to4)) = make_uint4(z[0], z[1], z[2], z[3]);
        }
      } else if (ct == 0) PT(1, 8);
    } else {
#pragma unroll
    for (int i = 0; i < 20; i++) res[i] = pack_bf16(d[2 * i] + __uint_as_float(res[i] << 16), d[2 * i + 1] + __uint_as_float(res[i] & 0xFFFF0000u));
    float2* bst = g_bst + (rt * 128 + row) * 8;
    if (BLN && !layer) {
      float a[4] = {0.f, 0.f, 0.f, 0.f};
#pragma unroll
      for (int i = 0; i < 20; i++) {
        const float lo = __uint_as_float(res[i] << 16), hi = __uint_as_float(res[i] & 0xFFFF0000u);
        a[(i & 1) * 2] += lo + hi; a[(i & 1) * 2 + 1] = fmaf(lo, lo, fmaf(hi, hi, a[(i & 1) * 2 + 1]));
      }
      const bool odd = t & 1;
      float s1 = (odd ? a[2] : a[0]) + __shfl_xor_sync(0xffffffffu, odd ? a[0] : a[2], 1), s2 = (odd ? a[3] : a[1]) + __shfl_xor_sync(0xffffffffu, odd ? a[1] : a[3], 1);
      s1 += __shfl_xor_sync(0xffffffffu, s1, 2); s2 += __shfl_xor_sync(0xffffffffu, s2, 2);
      asm volatile("{.reg .pred p; .reg .b64 v; setp.lt.u32 p, %3, 2; mov.b64 v, {%1,%2}; @p st.relaxed.gpu.global.b64 [%0], v;}"
                   :: "l"(bst + (t & 1) * 64 + gq), "r"(__float_as_uint(s1)), "r"(__float_as_uint(s2) | 0x80000000u), "r"(t) : "memory");
    }
    const uint32_t tb = sb + A2 + (w >> 1) * 16384 + cw * 8192 + (w & 1) * 3072;
    int go[5];
    if (BTR) {
      bar_sync(5 + cw, 128);
#pragma unroll
      for (int i = 0; i < 5; i++) stsm4(tb + (lane & 15) * 176 + (2 * i + (lane >> 4)) * 16, res[4 * i], res[4 * i + 1], res[4 * i + 2], res[4 * i + 3]);
      __syncwarp();
#pragma unroll
      for (int i = 0; i < 5; i++) {
        const int n = i * 32 + lane, r = n * 205 >> 11;
        lds128(*(uint32_t(*)[4])&res[4 * i], tb + n * 16 + r * 16);
        go[i] = (rt * 128 + cw * 64 + w * 16) * DM + gq * 80 + n * 8 + r * (DM - 80);
      }
#pragma unroll
      for (int i = 0; i < 5; i++) *(uint4*)(out + go[i]) = make_uint4(res[4 * i], res[4 * i + 1], res[4 * i + 2], res[4 * i + 3]);
    } else {
#pragma unroll
      for (int i = 0; i < 20; i++) *(uint32_t*)(out + off + (i >> 1) * 8 + (i & 1) * 8 * DM) = res[i];
    }
    if (ct == 0) PT(1, 8);
    if (BLN && !layer) {
      uint32_t u[2][4];
      for (int n = 0; n < 4000000; n++) {
#pragma unroll
        for (int e = 0; e < 2; e++)
          asm volatile("{.reg .b64 a, b; ld.relaxed.gpu.global.v2.b64 {a, b}, [%4]; mov.b64 {%0,%1}, a; mov.b64 {%2,%3}, b;}"
                       : "=r"(u[e][0]), "=r"(u[e][1]), "=r"(u[e][2]), "=r"(u[e][3]) : "l"(bst + e * 64 + 2 * t) : "memory");
        if (__all_sync(0xffffffffu, (int)(u[0][1] & u[0][3] & u[1][1] & u[1][3]) < 0)) break;
      }
#pragma unroll
      for (int e = 0; e < 2; e++) {
        float s1 = __uint_as_float(u[e][0]) + __uint_as_float(u[e][2]), s2 = __uint_as_float(u[e][1]) + __uint_as_float(u[e][3]);
#pragma unroll
        for (int o = 1; o < 4; o <<= 1) { s1 += __shfl_xor_sync(0xffffffffu, s1, o); s2 += __shfl_xor_sync(0xffffffffu, s2, o); }
        const float m = s1 * (1.0f / DM);
        rs[e] = rsqrtf(fmaxf(s2 * (-1.0f / DM) - m * m, 0.f) + 1e-5f);
        ms[e] = -m * rs[e];
      }
      if (BTR) {
        if (t < 2) sts64(tb + 2816 + (g + 8 * t) * 8, __float_as_uint(t ? rs[1] : rs[0]), __float_as_uint(t ? ms[1] : ms[0]));
        __syncwarp();
#pragma unroll
        for (int i = 0; i < 5; i++) {
          const float2 c = lds64f(tb + 2816 + ((i * 32 + lane) * 205 >> 11) * 8);
          uint32_t z[4];
#pragma unroll
          for (int e = 0; e < 4; e++) z[e] = pack_bf16(fmaf(__uint_as_float(res[4 * i + e] << 16), c.x, c.y), fmaf(__uint_as_float(res[4 * i + e] & 0xFFFF0000u), c.x, c.y));
          *(uint4*)(g_xn + go[i]) = make_uint4(z[0], z[1], z[2], z[3]);
        }
      } else
#pragma unroll
      for (int i = 0; i < 20; i++)
        *(uint32_t*)(g_xn + off + (i >> 1) * 8 + (i & 1) * 8 * DM) = pack_bf16(fmaf(__uint_as_float(res[i] << 16), rs[i & 1], ms[i & 1]), fmaf(__uint_as_float(res[i] & 0xFFFF0000u), rs[i & 1], ms[i & 1]));
    }
    }
    if (ct == 0) GT(2, 1);
  }
}

typedef CUresult (*EncodeFn)(CUtensorMap*, CUtensorMapDataType, cuuint32_t, void*, const cuuint64_t*, const cuuint64_t*, const cuuint32_t*,
                             const cuuint32_t*, CUtensorMapInterleave, CUtensorMapSwizzle, CUtensorMapL2promotion, CUtensorMapFloatOOBfill);
static EncodeFn g_enc = nullptr;
#define P128 1
static void make_map(CUtensorMap* m, const void* p, uint64_t cols, uint64_t rows, uint32_t bc, uint32_t br, bool swz = true, bool p128 = false) {
  cuuint64_t dims[2] = {cols, rows}; cuuint64_t strides[1] = {cols * 2}; cuuint32_t box[2] = {bc, br}; cuuint32_t es[2] = {1, 1};
  g_enc(m, CU_TENSOR_MAP_DATA_TYPE_BFLOAT16, 2, (void*)p, dims, strides, box, es, CU_TENSOR_MAP_INTERLEAVE_NONE, swz ? CU_TENSOR_MAP_SWIZZLE_128B : CU_TENSOR_MAP_SWIZZLE_NONE,
        p128 ? CU_TENSOR_MAP_L2_PROMOTION_L2_128B : CU_TENSOR_MAP_L2_PROMOTION_L2_256B, CU_TENSOR_MAP_FLOAT_OOB_FILL_NONE);
}
static void make_map3(CUtensorMap* m, const void* p, uint64_t cols, uint64_t rows, uint32_t cw, uint32_t br, uint32_t bch) {
  cuuint64_t dims[3] = {cw, rows, cols / cw}; cuuint64_t strides[2] = {cols * 2, cw * 2}; cuuint32_t box[3] = {cw, br, bch}; cuuint32_t es[3] = {1, 1, 1};
  g_enc(m, CU_TENSOR_MAP_DATA_TYPE_BFLOAT16, 3, (void*)p, dims, strides, box, es, CU_TENSOR_MAP_INTERLEAVE_NONE,
        cw == 64 ? CU_TENSOR_MAP_SWIZZLE_128B : cw == 32 ? CU_TENSOR_MAP_SWIZZLE_64B : CU_TENSOR_MAP_SWIZZLE_32B, CU_TENSOR_MAP_L2_PROMOTION_L2_256B, CU_TENSOR_MAP_FLOAT_OOB_FILL_NONE);
}
template <typename T> static void* sym(T& s) { void* p = nullptr; cudaGetSymbolAddress(&p, s); return p; }
template <typename... KA, typename... A>
static void launch(void (*k)(KA...), int grid, int smem, bool pdl, A... a) {
  cudaLaunchConfig_t cfg = {};
  cfg.gridDim = dim3(grid); cfg.blockDim = dim3(384); cfg.dynamicSmemBytes = smem; cfg.stream = cudaStreamPerThread;
  cudaLaunchAttribute at[1]; at[0].id = cudaLaunchAttributeProgrammaticStreamSerialization; at[0].val.programmaticStreamSerializationAllowed = 1;
  cfg.attrs = at; cfg.numAttrs = pdl ? 1 : 0;
  cudaLaunchKernelEx(&cfg, k, a...);
}

constexpr int dev_layers = 2, dev_pdl = 1;
#define EV(i)
extern "C" void kernel_launch(void* const* d_in, const int* in_sizes, int n_in, void* d_out, int out_size) {
  static int nsm = 0;
  if (!g_enc) {
    void* fn = nullptr; cudaDriverEntryPointQueryResult st;
    cudaGetDriverEntryPoint("cuTensorMapEncodeTiled", &fn, cudaEnableDefault, &st);
    g_enc = (EncodeFn)fn;
    cudaFuncSetAttribute(chain_kernel, cudaFuncAttributeMaxDynamicSharedMemorySize, ch::SMEM);
    cudaFuncSetAttribute(worker_kernel, cudaFuncAttributeMaxDynamicSharedMemorySize, wk::SMEM);
    cudaFuncSetAttribute(layerb_kernel, cudaFuncAttributeMaxDynamicSharedMemorySize, bk::SMEM);
    cudaDeviceGetAttribute(&nsm, cudaDevAttrMultiProcessorCount, 0);
  }
  CUtensorMap mq, mk, mv, mo, mx, wx, wq, woa, wos, wwo, wxa, wacc, wwb, bx, bw1, bo, bos;
  make_map(&mq, d_in[2], HD, DM, 64, 128, true, P128); make_map(&mk, d_in[3], HD, DM, 64, 128, true, P128); make_map(&mv, d_in[4], HD, DM, 64, 128, true, P128);
  make_map(&mo, d_in[5], DM, HD, 64, 192, true, P128); make_map3(&mx, sym(g_xn), DM, S_LEN, 64, 32, 5);
  make_map(&wx, sym(g_xn), DM, S_LEN, 64, 128); make_map3(&wq, d_in[2], HD, DM, 64, 64, 3);
  make_map(&woa, sym(g_o), HD, S_LEN, 64, 128); make_map3(&wos, sym(g_o), HD, S_LEN, 64, 64, 3); make_map3(&wwo, d_in[5], DM, HD, 32, 64, 5);
  CUtensorMap toa;
  make_map(&toa, sym(g_o), HD, S_LEN, 64, 64);
  make_map3(&wxa, sym(g_xa), DM, S_LEN, 32, 64, 5);
  if (BSL) make_map3(&wacc, sym(g_sl), DM, NSL * 128, 32, 64, 5);
  else {
    cuuint64_t dims[3] = {32, 2 * ACC_ROWS, DM / 32}, strides[2] = {DM * 4, 128}; cuuint32_t box[3] = {32, 64, 5}, es[3] = {1, 1, 1};
    g_enc(&wacc, CU_TENSOR_MAP_DATA_TYPE_FLOAT32, 3, sym(g_acc), dims, strides, box, es, CU_TENSOR_MAP_INTERLEAVE_NONE, CU_TENSOR_MAP_SWIZZLE_128B,
          CU_TENSOR_MAP_L2_PROMOTION_NONE, CU_TENSOR_MAP_FLOAT_OOB_FILL_NONE);
  }
  make_map(&wwb, d_in[8], 3 * DM, DM, 80, 64, false);
  make_map(&bx, sym(g_xa), DM, S_LEN, 64, (BHALF & 1) ? 64 : 128); make_map(&bw1, sym(g_wb1), DM, 3 * DM, 64, 240);
  make_map(&bo, sym(g_bo), DM, S_LEN, 64, (BHALF & 2) ? 64 : 128); make_map(&bos, sym(g_bo), DM, S_LEN, 80, 128, false);
  cudaStream_t st = cudaStreamPerThread;
  for (int layer = 0; layer < dev_layers; layer++) {
    const bf16* x = layer == 0 ? (const bf16*)d_in[0] : (const bf16*)sym(g_xb);
    Sync* sy = (Sync*)sym(g_sync) + layer;
    EV(layer * 5);
    EV(layer * 5 + 1);
    launch(chain_kernel, 96, ch::SMEM, dev_pdl && layer, mq, mk, mv, mo, mx, (const bf16*)d_in[1], x, 0u, layer, toa, wwo);
    EV(layer * 5 + 2);
    launch(worker_kernel, WGRID ? WGRID : CTAIL ? nsm - 96 : nsm, wk::SMEM, dev_pdl, layer, sy, x, (const bf16*)d_in[9], (const bf16*)d_in[10], wx, wq, woa, wos, wwo, wxa, wacc, wwb);
    EV(layer * 5 + 3);
    launch(layerb_kernel, layer ? 128 : BLN ? 132 : PFA_N ? max(128, min(nsm, 132)) : 128, bk::SMEM, dev_pdl, layer, 2u * (nsm - 96), sy, x, layer == 0 ? (bf16*)sym(g_xb) : (bf16*)d_out,
           (const void*)d_in[2], (const void*)d_in[3], (const void*)d_in[4], (const void*)d_in[5], bx, bw1, bo, bos);
    EV(layer * 5 + 4);
  }
}
```
